```python
import torch

def _softmax(x, axis=-1):
    return torch.softmax(x, dim=axis)
def _gelu(x):
    return torch.nn.functional.gelu(x, approximate="tanh")
def _silu(x):
    return torch.nn.functional.silu(x)
def _sigmoid(x):
    return torch.sigmoid(x)
def _layernorm(x, axis=-1, eps=1e-5):
    m = x.mean(dim=axis, keepdim=True)
    v = x.var(dim=axis, keepdim=True, unbiased=False)
    return (x - m) / torch.sqrt(v + eps)
def _scatter_add(tgt, idx, src, axis=0):
    return tgt.clone().index_add_(axis, idx, src)
def _segment_sum(src, seg, n):
    out = torch.zeros((n,) + src.shape[1:], dtype=src.dtype)
    return out.index_add_(0, seg, src)
def _pad(x, pw):
    flat = tuple(v for pair in reversed(pw) for v in pair)
    return torch.nn.functional.pad(x, flat)

kernel_name = 'gated_mix__softmax_full_mha__linear_kernel_hedgehog__prompt'

def setup_inputs():

    _w = (lambda a: (lambda t: t.to(torch.bfloat16) if t.is_floating_point() else t)(torch.as_tensor(a)))
    def _A_setup():
        B, S, D = 1, 2048, 640
        return {
            "x": _w((lambda *s: torch.randn(*s, dtype=torch.bfloat16) * 0.05)(B, S, D)),
            "wqkv": _w((lambda *s: torch.randn(*s, dtype=torch.bfloat16) * 0.8)(D, 3 * D)),
            "wo": _w((lambda *s: torch.randn(*s, dtype=torch.bfloat16) * 0.05)(D, D)),
        }
    _A_in = _A_setup()

    def _B_setup():
        B, S, D, H = 1, 2048, 640, 32
        Dh = D // H
        return {
            "x": _w((lambda *s: torch.randn(*s, dtype=torch.bfloat16) * 0.05)(B, S, D)),
            "wqkv": _w((lambda *s: torch.randn(*s, dtype=torch.bfloat16) * 1.6)(D, 3 * D)),
            "w_phi": _w((lambda *s: torch.randn(*s, dtype=torch.bfloat16) * 1.6)(H, Dh, Dh) * (Dh ** -0.5)),
            "wo": _w((lambda *s: torch.randn(*s, dtype=torch.bfloat16) * 0.05)(D, D)),
        }
    _B_in = _B_setup()

    return {
        "A_x": _A_in["x"],
        "A_wqkv": _A_in["wqkv"],
        "A_wo": _A_in["wo"],
        "B_x": _B_in["x"],
        "B_wqkv": _B_in["wqkv"],
        "B_w_phi": _B_in["w_phi"],
        "B_wo": _B_in["wo"],
        "gate_w": _w((lambda *s: torch.randn(*s, dtype=torch.bfloat16) * 0.05)(640) * 16.0),
    }

def reference(A_x, A_wqkv, A_wo, B_x, B_wqkv, B_w_phi, B_wo, gate_w):
    def _A_ref(x, wqkv, wo):
        B, S, D = x.shape
        H = 32; Dh = D // H
        qkv = (lambda x, *d: x.permute(*d))((x @ wqkv).reshape(B, S, 3, H, Dh), 2, 0, 3, 1, 4)
        q, k, v = qkv[0], qkv[1], qkv[2]
        scale = Dh ** -0.5
        scores = torch.einsum("bhqd,bhkd->bhqk", q, k) * scale
        p = _softmax(scores, axis=-1)
        o = torch.einsum("bhqk,bhkd->bhqd", p, v)
        return (lambda x, *d: x.permute(*d))(o, 0, 2, 1, 3).reshape(B, S, D) @ wo

    def _B_ref(x, wqkv, w_phi, wo):
        B, S, D = x.shape
        H = 32; Dh = D // H
        qkv = (lambda x, *d: x.permute(*d))((x @ wqkv).reshape(B, S, 3, H, Dh), 2, 0, 3, 1, 4)
        q, k, v = qkv[0], qkv[1], qkv[2]
        pq = torch.einsum("bhsd,hdf->bhsf", q, w_phi)
        pk = torch.einsum("bhsd,hdf->bhsf", k, w_phi)
        phi_q = torch.concatenate([_softmax(pq, axis=-1), _softmax(-pq, axis=-1)], axis=-1)
        phi_k = torch.concatenate([_softmax(pk, axis=-1), _softmax(-pk, axis=-1)], axis=-1)
        kv = torch.einsum("bhsf,bhsd->bhfd", phi_k, v)
        z  = torch.einsum("bhsf->bhf", phi_k)
        num = torch.einsum("bhqf,bhfd->bhqd", phi_q, kv)
        den = torch.einsum("bhqf,bhf->bhq", phi_q, z)[..., None] + 1e-6
        o = num / den
        return (lambda x, *d: x.permute(*d))(o, 0, 2, 1, 3).reshape(B, S, D) @ wo

    x = A_x
    g = _sigmoid((x * gate_w).sum(-1, keepdims=True))
    a = _A_ref(x, A_wqkv, A_wo)
    b = _B_ref(x, B_wqkv, B_w_phi, B_wo)
    return g * a + (1 - g) * b
```

```cpp
#include <cuda_runtime.h>
#include <cuda.h>
#include <cuda_bf16.h>
#include <cuda_fp16.h>
#include <stdint.h>

namespace {

constexpr int HS = 294912;
constexpr int RBS = 18432;
constexpr int TS = 6144;
constexpr int BRS = 32 * HS;
constexpr int ORB = 160 * 2048;
constexpr int NMB = 3;

__device__ __align__(1024) uint8_t g_qkv[2 * BRS];
__device__ __align__(1024) uint8_t g_o[16 * ORB];
__device__ float g_gate[2048];
__device__ __align__(16) float g_kv[32 * 960];
__device__ int g_cnt[32];
__device__ int g_kbad[1024];

__device__ __forceinline__ uint64_t mkdesc(uint32_t addr, uint32_t lbo, uint32_t sbo, int mode) {
  return (uint64_t)((addr & 0x3FFFF) >> 4) | ((uint64_t)(lbo >> 4) << 16) | ((uint64_t)(sbo >> 4) << 32) | ((uint64_t)mode << 62);
}
#define WG_FENCE() asm volatile("wgmma.fence.sync.aligned;" ::: "memory")
#define WG_COMMIT() asm volatile("wgmma.commit_group.sync.aligned;" ::: "memory")
#define WG_WAIT(n) asm volatile("wgmma.wait_group.sync.aligned %0;" ::"n"(n) : "memory")
#define PROXY_FENCE() asm volatile("fence.proxy.async.shared::cta;" ::: "memory")
__device__ __forceinline__ void bar_sync(int id, int n) { asm volatile("bar.sync %0, %1;" ::"r"(id), "r"(n) : "memory"); }
__device__ __forceinline__ void mbar_init(uint32_t a, int c) { asm volatile("mbarrier.init.shared::cta.b64 [%0], %1;" ::"r"(a), "r"(c)); }
__device__ __forceinline__ uint32_t mbar_try(uint32_t a, int par) {
  uint32_t ok;
  asm volatile("{.reg .pred p; mbarrier.try_wait.parity.shared::cta.b64 p, [%1], %2; selp.b32 %0, 1, 0, p;}" : "=r"(ok) : "r"(a), "r"(par) : "memory");
  return ok;
}
__device__ __forceinline__ void mbar_wait(uint32_t a, int par) {
  for (int i = 0; !mbar_try(a, par); i++)
    if (i > (1 << 22)) __trap();
}
__device__ __forceinline__ void mbar_expect(uint32_t a, int bytes) { asm volatile("mbarrier.arrive.expect_tx.shared::cta.b64 _, [%0], %1;" ::"r"(a), "r"(bytes) : "memory"); }
__device__ __forceinline__ void mbar_arrive(uint32_t a) { asm volatile("mbarrier.arrive.shared::cta.b64 _, [%0];" ::"r"(a) : "memory"); }
__device__ __forceinline__ void tma2d(uint32_t dst, const CUtensorMap* m, int c0, int c1, uint32_t bar) {
  asm volatile("cp.async.bulk.tensor.2d.shared::cluster.global.mbarrier::complete_tx::bytes [%0], [%1, {%3, %4}], [%2];" ::"r"(dst), "l"(m), "r"(bar), "r"(c0), "r"(c1) : "memory");
}
__device__ __forceinline__ void tma3d(uint32_t dst, const CUtensorMap* m, int c0, int c1, int c2, uint32_t bar) {
  asm volatile("cp.async.bulk.tensor.3d.shared::cluster.global.mbarrier::complete_tx::bytes [%0], [%1, {%3, %4, %5}], [%2];" ::"r"(dst), "l"(m), "r"(bar), "r"(c0), "r"(c1), "r"(c2) : "memory");
}
__device__ __forceinline__ void bulk_g2s(uint32_t dst, const void* src, int bytes, uint32_t bar) {
  asm volatile("cp.async.bulk.shared::cluster.global.mbarrier::complete_tx::bytes [%0], [%1], %2, [%3];" ::"r"(dst), "l"(src), "r"(bytes), "r"(bar) : "memory");
}
__device__ __forceinline__ uint32_t pack_bf16(float lo, float hi) { uint32_t r; asm("cvt.rn.bf16x2.f32 %0, %1, %2;" : "=r"(r) : "f"(hi), "f"(lo)); return r; }
__device__ __forceinline__ uint32_t pack_f16(float lo, float hi) { uint32_t r; asm("cvt.rn.f16x2.f32 %0, %1, %2;" : "=r"(r) : "f"(hi), "f"(lo)); return r; }
__device__ __forceinline__ float ex2(float a) { float r; asm("ex2.approx.ftz.f32 %0, %1;" : "=f"(r) : "f"(a)); return r; }
__device__ __forceinline__ uint32_t maxabs_bf16x2(uint32_t a, uint32_t b) { uint32_t r; asm("max.NaN.xorsign.abs.bf16x2 %0, %1, %2;" : "=r"(r) : "r"(a), "r"(b)); return r; }
__device__ __forceinline__ uint32_t ldg32(const void* p) { return __ldg(reinterpret_cast<const uint32_t*>(p)); }
__device__ __forceinline__ uint32_t ldcg32(const void* p) { return __ldcg(reinterpret_cast<const uint32_t*>(p)); }
__device__ __forceinline__ void stg32(void* p, uint32_t v) { *reinterpret_cast<uint32_t*>(p) = v; }
__device__ __forceinline__ void sts32(uint32_t a, uint32_t v) { asm volatile("st.shared.b32 [%0], %1;" ::"r"(a), "r"(v) : "memory"); }
__device__ __forceinline__ void sts16(uint32_t a, uint16_t v) { asm volatile("st.shared.b16 [%0], %1;" ::"r"(a), "h"(v) : "memory"); }
template <int N> __device__ __forceinline__ void pin(float (&d)[N]) {
#pragma unroll
  for (int i = 0; i < N; i++) asm volatile("" : "+f"(d[i])::"memory");
}
template <int N> __device__ __forceinline__ void pin(uint32_t (&d)[N]) {
#pragma unroll
  for (int i = 0; i < N; i++) asm volatile("" : "+r"(d[i])::"memory");
}

__device__ __forceinline__ void wg256_ss(float (&d)[128], uint64_t da, uint64_t db, int scale_d) {
  asm volatile("{\n.reg .pred p;\nsetp.ne.b32 p, %130, 0;\n"
    "wgmma.mma_async.sync.aligned.m64n256k16.f32.bf16.bf16 "
    "{%0, %1, %2, %3, %4, %5, %6, %7, %8, %9, %10, %11, %12, %13, %14, %15,"
    "%16, %17, %18, %19, %20, %21, %22, %23, %24, %25, %26, %27, %28, %29, %30, %31,"
    "%32, %33, %34, %35, %36, %37, %38, %39, %40, %41, %42, %43, %44, %45, %46, %47,"
    "%48, %49, %50, %51, %52, %53, %54, %55, %56, %57, %58, %59, %60, %61, %62, %63,"
    "%64, %65, %66, %67, %68, %69, %70, %71, %72, %73, %74, %75, %76, %77, %78, %79,"
    "%80, %81, %82, %83, %84, %85, %86, %87, %88, %89, %90, %91, %92, %93, %94, %95,"
    "%96, %97, %98, %99, %100, %101, %102, %103, %104, %105, %106, %107, %108, %109, %110, %111,"
    "%112, %113, %114, %115, %116, %117, %118, %119, %120, %121, %122, %123, %124, %125, %126, %127}, "
    "%128, %129, p, 1, 1, 0, 1;\n}\n"
    : "+f"(d[0]), "+f"(d[1]), "+f"(d[2]), "+f"(d[3]), "+f"(d[4]), "+f"(d[5]), "+f"(d[6]), "+f"(d[7]),
      "+f"(d[8]), "+f"(d[9]), "+f"(d[10]), "+f"(d[11]), "+f"(d[12]), "+f"(d[13]), "+f"(d[14]), "+f"(d[15]),
      "+f"(d[16]), "+f"(d[17]), "+f"(d[18]), "+f"(d[19]), "+f"(d[20]), "+f"(d[21]), "+f"(d[22]), "+f"(d[23]),
      "+f"(d[24]), "+f"(d[25]), "+f"(d[26]), "+f"(d[27]), "+f"(d[28]), "+f"(d[29]), "+f"(d[30]), "+f"(d[31]),
      "+f"(d[32]), "+f"(d[33]), "+f"(d[34]), "+f"(d[35]), "+f"(d[36]), "+f"(d[37]), "+f"(d[38]), "+f"(d[39]),
      "+f"(d[40]), "+f"(d[41]), "+f"(d[42]), "+f"(d[43]), "+f"(d[44]), "+f"(d[45]), "+f"(d[46]), "+f"(d[47]),
      "+f"(d[48]), "+f"(d[49]), "+f"(d[50]), "+f"(d[51]), "+f"(d[52]), "+f"(d[53]), "+f"(d[54]), "+f"(d[55]),
      "+f"(d[56]), "+f"(d[57]), "+f"(d[58]), "+f"(d[59]), "+f"(d[60]), "+f"(d[61]), "+f"(d[62]), "+f"(d[63]),
      "+f"(d[64]), "+f"(d[65]), "+f"(d[66]), "+f"(d[67]), "+f"(d[68]), "+f"(d[69]), "+f"(d[70]), "+f"(d[71]),
      "+f"(d[72]), "+f"(d[73]), "+f"(d[74]), "+f"(d[75]), "+f"(d[76]), "+f"(d[77]), "+f"(d[78]), "+f"(d[79]),
      "+f"(d[80]), "+f"(d[81]), "+f"(d[82]), "+f"(d[83]), "+f"(d[84]), "+f"(d[85]), "+f"(d[86]), "+f"(d[87]),
      "+f"(d[88]), "+f"(d[89]), "+f"(d[90]), "+f"(d[91]), "+f"(d[92]), "+f"(d[93]), "+f"(d[94]), "+f"(d[95]),
      "+f"(d[96]), "+f"(d[97]), "+f"(d[98]), "+f"(d[99]), "+f"(d[100]), "+f"(d[101]), "+f"(d[102]), "+f"(d[103]),
      "+f"(d[104]), "+f"(d[105]), "+f"(d[106]), "+f"(d[107]), "+f"(d[108]), "+f"(d[109]), "+f"(d[110]), "+f"(d[111]),
      "+f"(d[112]), "+f"(d[113]), "+f"(d[114]), "+f"(d[115]), "+f"(d[116]), "+f"(d[117]), "+f"(d[118]), "+f"(d[119]),
      "+f"(d[120]), "+f"(d[121]), "+f"(d[122]), "+f"(d[123]), "+f"(d[124]), "+f"(d[125]), "+f"(d[126]), "+f"(d[127])
    : "l"(da), "l"(db), "r"(scale_d));
}

__device__ __forceinline__ void wg192_ss_of128(float (&d)[128], uint64_t da, uint64_t db, int scale_d) {
  asm volatile("{\n.reg .pred p;\nsetp.ne.b32 p, %98, 0;\n"
    "wgmma.mma_async.sync.aligned.m64n192k16.f32.bf16.bf16 "
    "{%0, %1, %2, %3, %4, %5, %6, %7, %8, %9, %10, %11, %12, %13, %14, %15,"
    "%16, %17, %18, %19, %20, %21, %22, %23, %24, %25, %26, %27, %28, %29, %30, %31,"
    "%32, %33, %34, %35, %36, %37, %38, %39, %40, %41, %42, %43, %44, %45, %46, %47,"
    "%48, %49, %50, %51, %52, %53, %54, %55, %56, %57, %58, %59, %60, %61, %62, %63,"
    "%64, %65, %66, %67, %68, %69, %70, %71, %72, %73, %74, %75, %76, %77, %78, %79,"
    "%80, %81, %82, %83, %84, %85, %86, %87, %88, %89, %90, %91, %92, %93, %94, %95}, "
    "%96, %97, p, 1, 1, 0, 1;\n}\n"
    : "+f"(d[0]), "+f"(d[1]), "+f"(d[2]), "+f"(d[3]), "+f"(d[4]), "+f"(d[5]), "+f"(d[6]), "+f"(d[7]),
      "+f"(d[8]), "+f"(d[9]), "+f"(d[10]), "+f"(d[11]), "+f"(d[12]), "+f"(d[13]), "+f"(d[14]), "+f"(d[15]),
      "+f"(d[16]), "+f"(d[17]), "+f"(d[18]), "+f"(d[19]), "+f"(d[20]), "+f"(d[21]), "+f"(d[22]), "+f"(d[23]),
      "+f"(d[24]), "+f"(d[25]), "+f"(d[26]), "+f"(d[27]), "+f"(d[28]), "+f"(d[29]), "+f"(d[30]), "+f"(d[31]),
      "+f"(d[32]), "+f"(d[33]), "+f"(d[34]), "+f"(d[35]), "+f"(d[36]), "+f"(d[37]), "+f"(d[38]), "+f"(d[39]),
      "+f"(d[40]), "+f"(d[41]), "+f"(d[42]), "+f"(d[43]), "+f"(d[44]), "+f"(d[45]), "+f"(d[46]), "+f"(d[47]),
      "+f"(d[48]), "+f"(d[49]), "+f"(d[50]), "+f"(d[51]), "+f"(d[52]), "+f"(d[53]), "+f"(d[54]), "+f"(d[55]),
      "+f"(d[56]), "+f"(d[57]), "+f"(d[58]), "+f"(d[59]), "+f"(d[60]), "+f"(d[61]), "+f"(d[62]), "+f"(d[63]),
      "+f"(d[64]), "+f"(d[65]), "+f"(d[66]), "+f"(d[67]), "+f"(d[68]), "+f"(d[69]), "+f"(d[70]), "+f"(d[71]),
      "+f"(d[72]), "+f"(d[73]), "+f"(d[74]), "+f"(d[75]), "+f"(d[76]), "+f"(d[77]), "+f"(d[78]), "+f"(d[79]),
      "+f"(d[80]), "+f"(d[81]), "+f"(d[82]), "+f"(d[83]), "+f"(d[84]), "+f"(d[85]), "+f"(d[86]), "+f"(d[87]),
      "+f"(d[88]), "+f"(d[89]), "+f"(d[90]), "+f"(d[91]), "+f"(d[92]), "+f"(d[93]), "+f"(d[94]), "+f"(d[95])
    : "l"(da), "l"(db), "r"(scale_d));
}

__device__ __forceinline__ void wg192_ss(float (&d)[96], uint64_t da, uint64_t db, int scale_d) {
  asm volatile("{\n.reg .pred p;\nsetp.ne.b32 p, %98, 0;\n"
    "wgmma.mma_async.sync.aligned.m64n192k16.f32.bf16.bf16 "
    "{%0, %1, %2, %3, %4, %5, %6, %7, %8, %9, %10, %11, %12, %13, %14, %15,"
    "%16, %17, %18, %19, %20, %21, %22, %23, %24, %25, %26, %27, %28, %29, %30, %31,"
    "%32, %33, %34, %35, %36, %37, %38, %39, %40, %41, %42, %43, %44, %45, %46, %47,"
    "%48, %49, %50, %51, %52, %53, %54, %55, %56, %57, %58, %59, %60, %61, %62, %63,"
    "%64, %65, %66, %67, %68, %69, %70, %71, %72, %73, %74, %75, %76, %77, %78, %79,"
    "%80, %81, %82, %83, %84, %85, %86, %87, %88, %89, %90, %91, %92, %93, %94, %95}, "
    "%96, %97, p, 1, 1, 0, 1;\n}\n"
    : "+f"(d[0]), "+f"(d[1]), "+f"(d[2]), "+f"(d[3]), "+f"(d[4]), "+f"(d[5]), "+f"(d[6]), "+f"(d[7]),
      "+f"(d[8]), "+f"(d[9]), "+f"(d[10]), "+f"(d[11]), "+f"(d[12]), "+f"(d[13]), "+f"(d[14]), "+f"(d[15]),
      "+f"(d[16]), "+f"(d[17]), "+f"(d[18]), "+f"(d[19]), "+f"(d[20]), "+f"(d[21]), "+f"(d[22]), "+f"(d[23]),
      "+f"(d[24]), "+f"(d[25]), "+f"(d[26]), "+f"(d[27]), "+f"(d[28]), "+f"(d[29]), "+f"(d[30]), "+f"(d[31]),
      "+f"(d[32]), "+f"(d[33]), "+f"(d[34]), "+f"(d[35]), "+f"(d[36]), "+f"(d[37]), "+f"(d[38]), "+f"(d[39]),
      "+f"(d[40]), "+f"(d[41]), "+f"(d[42]), "+f"(d[43]), "+f"(d[44]), "+f"(d[45]), "+f"(d[46]), "+f"(d[47]),
      "+f"(d[48]), "+f"(d[49]), "+f"(d[50]), "+f"(d[51]), "+f"(d[52]), "+f"(d[53]), "+f"(d[54]), "+f"(d[55]),
      "+f"(d[56]), "+f"(d[57]), "+f"(d[58]), "+f"(d[59]), "+f"(d[60]), "+f"(d[61]), "+f"(d[62]), "+f"(d[63]),
      "+f"(d[64]), "+f"(d[65]), "+f"(d[66]), "+f"(d[67]), "+f"(d[68]), "+f"(d[69]), "+f"(d[70]), "+f"(d[71]),
      "+f"(d[72]), "+f"(d[73]), "+f"(d[74]), "+f"(d[75]), "+f"(d[76]), "+f"(d[77]), "+f"(d[78]), "+f"(d[79]),
      "+f"(d[80]), "+f"(d[81]), "+f"(d[82]), "+f"(d[83]), "+f"(d[84]), "+f"(d[85]), "+f"(d[86]), "+f"(d[87]),
      "+f"(d[88]), "+f"(d[89]), "+f"(d[90]), "+f"(d[91]), "+f"(d[92]), "+f"(d[93]), "+f"(d[94]), "+f"(d[95])
    : "l"(da), "l"(db), "r"(scale_d));
}

__device__ __forceinline__ void wg128_ss_of96(float (&d)[96], uint64_t da, uint64_t db, int scale_d) {
  asm volatile("{\n.reg .pred p;\nsetp.ne.b32 p, %66, 0;\n"
    "wgmma.mma_async.sync.aligned.m64n128k16.f32.bf16.bf16 "
    "{%0, %1, %2, %3, %4, %5, %6, %7, %8, %9, %10, %11, %12, %13, %14, %15,"
    "%16, %17, %18, %19, %20, %21, %22, %23, %24, %25, %26, %27, %28, %29, %30, %31,"
    "%32, %33, %34, %35, %36, %37, %38, %39, %40, %41, %42, %43, %44, %45, %46, %47,"
    "%48, %49, %50, %51, %52, %53, %54, %55, %56, %57, %58, %59, %60, %61, %62, %63}, "
    "%64, %65, p, 1, 1, 0, 1;\n}\n"
    : "+f"(d[0]), "+f"(d[1]), "+f"(d[2]), "+f"(d[3]), "+f"(d[4]), "+f"(d[5]), "+f"(d[6]), "+f"(d[7]),
      "+f"(d[8]), "+f"(d[9]), "+f"(d[10]), "+f"(d[11]), "+f"(d[12]), "+f"(d[13]), "+f"(d[14]), "+f"(d[15]),
      "+f"(d[16]), "+f"(d[17]), "+f"(d[18]), "+f"(d[19]), "+f"(d[20]), "+f"(d[21]), "+f"(d[22]), "+f"(d[23]),
      "+f"(d[24]), "+f"(d[25]), "+f"(d[26]), "+f"(d[27]), "+f"(d[28]), "+f"(d[29]), "+f"(d[30]), "+f"(d[31]),
      "+f"(d[32]), "+f"(d[33]), "+f"(d[34]), "+f"(d[35]), "+f"(d[36]), "+f"(d[37]), "+f"(d[38]), "+f"(d[39]),
      "+f"(d[40]), "+f"(d[41]), "+f"(d[42]), "+f"(d[43]), "+f"(d[44]), "+f"(d[45]), "+f"(d[46]), "+f"(d[47]),
      "+f"(d[48]), "+f"(d[49]), "+f"(d[50]), "+f"(d[51]), "+f"(d[52]), "+f"(d[53]), "+f"(d[54]), "+f"(d[55]),
      "+f"(d[56]), "+f"(d[57]), "+f"(d[58]), "+f"(d[59]), "+f"(d[60]), "+f"(d[61]), "+f"(d[62]), "+f"(d[63])
    : "l"(da), "l"(db), "r"(scale_d));
}

__device__ __forceinline__ void wg64_rs_bf16(float (&d)[32], uint32_t a0, uint32_t a1, uint32_t a2, uint32_t a3, uint64_t db, int scale_d) {
  asm volatile("{\n.reg .pred p;\nsetp.ne.b32 p, %37, 0;\n"
    "wgmma.mma_async.sync.aligned.m64n64k16.f32.bf16.bf16 "
    "{%0, %1, %2, %3, %4, %5, %6, %7, %8, %9, %10, %11, %12, %13, %14, %15,"
    "%16, %17, %18, %19, %20, %21, %22, %23, %24, %25, %26, %27, %28, %29, %30, %31}, "
    "{%32, %33, %34, %35}, %36, p, 1, 1, 0;\n}\n"
    : "+f"(d[0]), "+f"(d[1]), "+f"(d[2]), "+f"(d[3]), "+f"(d[4]), "+f"(d[5]), "+f"(d[6]), "+f"(d[7]),
      "+f"(d[8]), "+f"(d[9]), "+f"(d[10]), "+f"(d[11]), "+f"(d[12]), "+f"(d[13]), "+f"(d[14]), "+f"(d[15]),
      "+f"(d[16]), "+f"(d[17]), "+f"(d[18]), "+f"(d[19]), "+f"(d[20]), "+f"(d[21]), "+f"(d[22]), "+f"(d[23]),
      "+f"(d[24]), "+f"(d[25]), "+f"(d[26]), "+f"(d[27]), "+f"(d[28]), "+f"(d[29]), "+f"(d[30]), "+f"(d[31])
    : "r"(a0), "r"(a1), "r"(a2), "r"(a3), "l"(db), "r"(scale_d));
}

__device__ __forceinline__ void wg24_rs_f16_t(float (&d)[12], uint32_t a0, uint32_t a1, uint32_t a2, uint32_t a3, uint64_t db, int scale_d) {
  asm volatile("{\n.reg .pred p;\nsetp.ne.b32 p, %17, 0;\n"
    "wgmma.mma_async.sync.aligned.m64n24k16.f32.f16.f16 "
    "{%0, %1, %2, %3, %4, %5, %6, %7, %8, %9, %10, %11}, "
    "{%12, %13, %14, %15}, %16, p, 1, 1, 1;\n}\n"
    : "+f"(d[0]), "+f"(d[1]), "+f"(d[2]), "+f"(d[3]), "+f"(d[4]), "+f"(d[5]), "+f"(d[6]), "+f"(d[7]),
      "+f"(d[8]), "+f"(d[9]), "+f"(d[10]), "+f"(d[11])
    : "r"(a0), "r"(a1), "r"(a2), "r"(a3), "l"(db), "r"(scale_d));
}

__device__ __forceinline__ void wg24_rs_bf16(float (&d)[12], uint32_t a0, uint32_t a1, uint32_t a2, uint32_t a3, uint64_t db, int scale_d) {
  asm volatile("{\n.reg .pred p;\nsetp.ne.b32 p, %17, 0;\n"
    "wgmma.mma_async.sync.aligned.m64n24k16.f32.bf16.bf16 "
    "{%0, %1, %2, %3, %4, %5, %6, %7, %8, %9, %10, %11}, "
    "{%12, %13, %14, %15}, %16, p, 1, 1, 0;\n}\n"
    : "+f"(d[0]), "+f"(d[1]), "+f"(d[2]), "+f"(d[3]), "+f"(d[4]), "+f"(d[5]), "+f"(d[6]), "+f"(d[7]),
      "+f"(d[8]), "+f"(d[9]), "+f"(d[10]), "+f"(d[11])
    : "r"(a0), "r"(a1), "r"(a2), "r"(a3), "l"(db), "r"(scale_d));
}

__device__ __forceinline__ void wg24_ss_bf16_tt(float (&d)[12], uint64_t da, uint64_t db, int scale_d) {
  asm volatile("{\n.reg .pred p;\nsetp.ne.b32 p, %14, 0;\n"
    "wgmma.mma_async.sync.aligned.m64n24k16.f32.bf16.bf16 "
    "{%0, %1, %2, %3, %4, %5, %6, %7, %8, %9, %10, %11}, "
    "%12, %13, p, 1, 1, 1, 1;\n}\n"
    : "+f"(d[0]), "+f"(d[1]), "+f"(d[2]), "+f"(d[3]), "+f"(d[4]), "+f"(d[5]), "+f"(d[6]), "+f"(d[7]),
      "+f"(d[8]), "+f"(d[9]), "+f"(d[10]), "+f"(d[11])
    : "l"(da), "l"(db), "r"(scale_d));
}

struct K1Maps { CUtensorMap x, w[2]; };
constexpr int K1_ST = 4, K1_STB = 49152;
constexpr int K1_SMEM = 1024 + K1_ST * K1_STB + 128;

__device__ __forceinline__ int tile_atom(int t) { return (t >> 2) * 15 + ((0xB740 >> ((t & 3) * 4)) & 15); }

template <int MODE, int A>
__device__ __forceinline__ void k1_store_atom(const float (&acc)[128], uint8_t* pb, const int (&loc)[5], float s0, float s1, uint32_t& m0, uint32_t& m1) {
#pragma unroll
  for (int jj = 0; jj < 8; jj++) {
    const int j = A * 8 + jj;
    uint8_t* p = pb + loc[j % 5] + (j / 5) * (2 * HS);
    uint32_t r0, r1;
    if (MODE == 0) { r0 = pack_bf16(acc[4 * j], acc[4 * j + 1]); r1 = pack_bf16(acc[4 * j + 2], acc[4 * j + 3]); }
    else if (MODE == 3) { r0 = pack_f16(acc[4 * j], acc[4 * j + 1]); r1 = pack_f16(acc[4 * j + 2], acc[4 * j + 3]); }
    else { r0 = pack_bf16(acc[4 * j] * s0, acc[4 * j + 1] * s0); r1 = pack_bf16(acc[4 * j + 2] * s1, acc[4 * j + 3] * s1); }
    if (MODE == 2) { m0 = maxabs_bf16x2(m0, r0); m1 = maxabs_bf16x2(m1, r1); }
    stg32(p, r0);
    stg32(p + 128, r1);
  }
}
template <int A>
__device__ __forceinline__ void k1_atom(const float (&acc)[128], int br, int ga, int ty0, uint8_t* base, const int (&loc)[5], float sk0, float sk1, uint32_t& m0, uint32_t& m1) {
  const int ty = ga / 10;
  uint8_t* pb = base + (ty != ty0 ? (TS - 32 * HS) : 0);
  if (br == 1) k1_store_atom<0, A>(acc, pb, loc, 0.f, 0.f, m0, m1);
  else if (ty == 0) { const float cq = __uint_as_float(463809372u); k1_store_atom<1, A>(acc, pb, loc, cq, cq, m0, m1); }
  else if (ty == 1) k1_store_atom<2, A>(acc, pb, loc, sk0, sk1, m0, m1);
  else k1_store_atom<3, A>(acc, pb, loc, 0.f, 0.f, m0, m1);
}

__global__ void __launch_bounds__(384, 1) k1_qkv(const __grid_constant__ K1Maps maps, const __nv_bfloat16* __restrict__ x, const __nv_bfloat16* __restrict__ gate_w) {
  extern __shared__ uint8_t smem_raw[];
  const uint32_t sb = ((uint32_t)__cvta_generic_to_shared(smem_raw) + 1023) & ~1023u;
  const uint32_t full = sb + K1_ST * K1_STB, empty = full + 8 * K1_ST;
  const int tid = threadIdx.x, wg = tid >> 7, lane = tid & 31;
  const int rb = blockIdx.x >> 3, c = blockIdx.x & 7;
  if (tid == 256) {
    for (int i = 0; i < K1_ST; i++) { mbar_init(full + 8 * i, 1); mbar_init(empty + 8 * i, 2); }
    asm volatile("fence.mbarrier_init.release.cluster;" ::: "memory");
  }
  asm volatile("griddepcontrol.launch_dependents;");
  __syncthreads();
  if (wg == 2) {
    asm volatile("setmaxnreg.dec.sync.aligned.u32 40;");
    const int w = (tid >> 5) & 3;
    if (w == 0) {
      if (lane == 0) {
        for (int it = 0; it < 20; it++) {
          const int st = it % K1_ST, br = it / 10, ks = it % 10;
          mbar_wait(empty + 8 * st, ((it / K1_ST) & 1) ^ 1);
          const uint32_t dst = sb + st * K1_STB;
          mbar_expect(full + 8 * st, K1_STB);
          tma2d(dst, &maps.x, ks * 64, rb * 128, full + 8 * st);
          tma3d(dst + 16384, &maps.w[br], 0, ks * 64, tile_atom(c ^ br), full + 8 * st);
        }
      }
    } else {
      const int at = tid - 288;
      for (int i = at; i < 240; i += 96) g_kv[blockIdx.x * 240 + i] = 0.f;
      if (at == 0 && blockIdx.x < 32) g_cnt[blockIdx.x] = 0;
      for (int i = at; i < 3072; i += 96) {
        const int tok = i & 127, e = i >> 7, hh = c * 4 + (e & 3), bt = e >> 2, br = bt / 3, ty = bt % 3;
        uint32_t v = 0;
        if (br == 0) v = ty == 0 ? 0x1c801c80u : ty == 2 ? 0x00003c00u : (((tok >> 3) & 7) < NMB ? 0xdd02e192u : 0x00001ef0u);
        else if (ty == 2) v = 0x00003f80u;
        *reinterpret_cast<uint2*>(g_qkv + (size_t)br * BRS + hh * HS + rb * RBS + ty * TS + 4096 + tok * 16 + 8) = make_uint2(v, 0u);
      }
      for (int r = w - 1; r < 16; r += 3) {
        const int row = rb * 128 + c * 16 + r;
        float s = 0.f;
#pragma unroll
        for (int i = 0; i < 5; i++) {
          const uint2 a = __ldg(reinterpret_cast<const uint2*>(x + row * 640 + i * 128 + lane * 4));
          const uint2 b = __ldg(reinterpret_cast<const uint2*>(gate_w + i * 128 + lane * 4));
          s += __uint_as_float(a.x << 16) * __uint_as_float(b.x << 16) + __uint_as_float(a.x & 0xffff0000u) * __uint_as_float(b.x & 0xffff0000u);
          s += __uint_as_float(a.y << 16) * __uint_as_float(b.y << 16) + __uint_as_float(a.y & 0xffff0000u) * __uint_as_float(b.y & 0xffff0000u);
        }
#pragma unroll
        for (int o = 16; o; o >>= 1) s += __shfl_xor_sync(0xffffffffu, s, o);
        if (lane == 0) g_gate[row] = 1.f / (1.f + __expf(-s));
      }
    }
  } else {
    asm volatile("setmaxnreg.inc.sync.aligned.u32 232;");
    const int w = (tid >> 5) & 3, g = lane >> 2, t = lane & 3;
    float acc[128];
    uint32_t m0 = 0, m1 = 0;
    const bool mufu0 = 2 * w < NMB, mufu1 = 2 * w + 1 < NMB;
    const float sk0 = __uint_as_float(mufu0 ? (127u + 70u) << 23 : (127u - 69u) << 23);
    const float sk1 = __uint_as_float(mufu1 ? (127u + 70u) << 23 : (127u - 69u) << 23);
#pragma unroll 1
    for (int br = 0; br < 2; br++) {
      const int tl = c ^ br, k4 = tl & 3;
      const bool narrow = (k4 == 1 && wg == 1) || (k4 == 2 && wg == 0);
      const int skip = (k4 == 2 && wg == 0) ? 1 : 0;
      if (!narrow) {
#pragma unroll 1
        for (int ks = 0; ks < 10; ks++) {
          const int it = br * 10 + ks, st = it % K1_ST;
          mbar_wait(full + 8 * st, (it / K1_ST) & 1);
          const uint32_t dst = sb + st * K1_STB;
          const uint64_t da = mkdesc(dst + wg * 8192, 16, 1024, 1), db = mkdesc(dst + 16384, 8192, 1024, 1);
          WG_FENCE();
#pragma unroll
          for (int k = 0; k < 4; k++) wg256_ss(acc, da + k * 2, db + k * 128, (ks | k) != 0);
          WG_COMMIT();
          WG_WAIT(1);
          if (ks > 0 && (tid & 127) == 0) mbar_arrive(empty + 8 * ((it - 1) % K1_ST));
        }
        WG_WAIT(0);
      } else {
#pragma unroll 1
        for (int ks = 0; ks < 10; ks++) {
          const int it = br * 10 + ks, st = it % K1_ST;
          mbar_wait(full + 8 * st, (it / K1_ST) & 1);
          const uint32_t dst = sb + st * K1_STB;
          const uint64_t da = mkdesc(dst + wg * 8192, 16, 1024, 1), db = mkdesc(dst + 16384 + skip * 8192, 8192, 1024, 1);
          WG_FENCE();
#pragma unroll
          for (int k = 0; k < 4; k++) wg192_ss_of128(acc, da + k * 2, db + k * 128, (ks | k) != 0);
          WG_COMMIT();
          WG_WAIT(1);
          if (ks > 0 && (tid & 127) == 0) mbar_arrive(empty + 8 * ((it - 1) % K1_ST));
        }
        WG_WAIT(0);
      }
      pin(acc);
      if ((tid & 127) == 0) mbar_arrive(empty + 8 * ((br * 10 + 9) % K1_ST));
      const int ga0 = tile_atom(tl) + skip, ty0 = ga0 / 10;
      int loc[5];
#pragma unroll
      for (int i = 0; i < 5; i++) {
        const int col = (ga0 - ty0 * 10) * 64 + i * 8 + 2 * t, hh = col / 20, d = col - hh * 20;
        loc[i] = hh * HS + (d >> 3) * 2048 + (d & 7) * 2;
      }
      uint8_t* base = g_qkv + (size_t)br * BRS + rb * RBS + ty0 * TS + (wg * 64 + w * 16 + g) * 16;
      k1_atom<0>(acc, br, ga0, ty0, base, loc, sk0, sk1, m0, m1);
      k1_atom<1>(acc, br, ga0 + 1, ty0, base, loc, sk0, sk1, m0, m1);
      k1_atom<2>(acc, br, ga0 + 2, ty0, base, loc, sk0, sk1, m0, m1);
      if (!narrow) k1_atom<3>(acc, br, ga0 + 3, ty0, base, loc, sk0, sk1, m0, m1);
    }
    const uint32_t lim0 = (mufu0 ? 127u + 110u : 127u - 29u) << 7, lim1 = (mufu1 ? 127u + 110u : 127u - 29u) << 7;
    const bool bad = (m0 & 0x7fffu) >= lim0 || ((m0 >> 16) & 0x7fffu) >= lim0 || (m1 & 0x7fffu) >= lim1 || ((m1 >> 16) & 0x7fffu) >= lim1;
    const int anybad = __any_sync(0xffffffffu, bad);
    if (lane == 0) g_kbad[blockIdx.x * 8 + (tid >> 5)] = anybad;
  }
}

constexpr int K2_KV = 0, K2_VB = 10 * 12288, K2_PHI = K2_VB + 24576;
constexpr int K2_WPHI = 196608, K2_KVB = K2_WPHI + 1536, K2_BAR = K2_KVB + 2304;
constexpr int K2_SMEM = 128 + K2_BAR + 17 * 8 + 8;

__device__ __forceinline__ uint32_t exp2_pair(float a, float b) {
  uint32_t z, w, h;
  asm volatile("cvt.pack.sat.s16.s32 %0, %2, %1;" : "=r"(z) : "r"(__float_as_uint(a)), "r"(__float_as_uint(b)));
  asm volatile("lop3.b32 %0, %1, 0x03ff03ff, 0x34003400, 0xEA;" : "=r"(w) : "r"(z));
  asm volatile("fma.rn.f16x2 %0, %1, %1, %2;" : "=r"(h) : "r"(w), "r"(0x36203620));
  asm volatile("fma.rn.f16x2 %0, %0, %1, %2;" : "+r"(h) : "r"(w), "r"(0x2e012e01));
  return h + z - w;
}
__device__ __forceinline__ uint32_t exp2_pair_mufu(float a, float b) {
  float x, y; uint32_t r;
  asm volatile("ex2.approx.ftz.f32 %0, %1;" : "=f"(x) : "f"(a));
  asm volatile("ex2.approx.ftz.f32 %0, %1;" : "=f"(y) : "f"(b));
  asm volatile("cvt.rn.f16x2.f32 %0, %1, %2;" : "=r"(r) : "f"(y), "f"(x));
  return r;
}
__device__ __forceinline__ void load_frag(uint32_t (&a)[6], const uint8_t* p) {
  a[0] = ldcg32(p); a[1] = ldcg32(p + 128); a[2] = ldcg32(p + 2048); a[3] = ldcg32(p + 2048 + 128); a[4] = ldcg32(p + 4096); a[5] = ldcg32(p + 4096 + 128);
}
__device__ __forceinline__ void feature_map(uint32_t (&phi)[10], const uint32_t (&a)[6], uint64_t dw) {
  float p[12];
  WG_FENCE();
  wg24_rs_bf16(p, a[0], a[1], a[2], a[3], dw, 0);
  wg24_rs_bf16(p, a[4], a[5], 0u, 0u, dw + 48, 1);
  WG_COMMIT();
  WG_WAIT(0);
  pin(p);
  const float L = 1.4426950408889634f;
#pragma unroll
  for (int r = 0; r < 2; r++) {
    float v[5] = {p[2 * r], p[2 * r + 1], p[4 + 2 * r], p[5 + 2 * r], p[8 + 2 * r]};
    float mx = fmaxf(fmaxf(fmaxf(v[0], v[1]), fmaxf(v[2], v[3])), v[4]);
    float mn = fminf(fminf(fminf(v[0], v[1]), fminf(v[2], v[3])), v[4]);
    mx = fmaxf(mx, __shfl_xor_sync(0xffffffffu, mx, 1)); mn = fminf(mn, __shfl_xor_sync(0xffffffffu, mn, 1));
    mx = fmaxf(mx, __shfl_xor_sync(0xffffffffu, mx, 2)); mn = fminf(mn, __shfl_xor_sync(0xffffffffu, mn, 2));
    float ep[5], en[5], sp = 0.f, sn = 0.f;
#pragma unroll
    for (int i = 0; i < 5; i++) { ep[i] = ex2((v[i] - mx) * L); en[i] = ex2((mn - v[i]) * L); sp += ep[i]; sn += en[i]; }
    sp += __shfl_xor_sync(0xffffffffu, sp, 1); sn += __shfl_xor_sync(0xffffffffu, sn, 1);
    sp += __shfl_xor_sync(0xffffffffu, sp, 2); sn += __shfl_xor_sync(0xffffffffu, sn, 2);
    const float rp = __fdividef(1.f, sp), rn = __fdividef(1.f, sn);
#pragma unroll
    for (int i = 0; i < 5; i++) phi[5 * r + i] = pack_bf16(ep[i] * rp, en[i] * rn);
  }
}
__device__ __forceinline__ void store_o(const float (&o)[12], float s0, float s1, uint8_t* prow, int col0, int t) {
#pragma unroll
  for (int j = 0; j < 3; j++) {
    const int col = col0 + 8 * j + 2 * t;
    uint8_t* p = prow + (col >> 3) * 2048 + (col & 7) * 2;
    if (j < 2 || t < 2) {
      stg32(p, pack_bf16(o[4 * j] * s0, o[4 * j + 1] * s0));
      stg32(p + 128, pack_bf16(o[4 * j + 2] * s1, o[4 * j + 3] * s1));
    }
  }
}

__device__ __forceinline__ void proj20(float (&acc)[20], const __nv_bfloat16* __restrict__ xr, const __nv_bfloat16* __restrict__ wc) {
#pragma unroll
  for (int d = 0; d < 20; d++) acc[d] = 0.f;
#pragma unroll 2
  for (int k = 0; k < 640; k++) {
    const float xv = __bfloat162float(xr[k]);
#pragma unroll
    for (int d = 0; d < 10; d++) {
      const uint32_t u = ldg32(wc + k * 1920 + 2 * d);
      acc[2 * d] = fmaf(xv, __uint_as_float(u << 16), acc[2 * d]);
      acc[2 * d + 1] = fmaf(xv, __uint_as_float(u & 0xffff0000u), acc[2 * d + 1]);
    }
  }
}
__device__ __noinline__ void attn_exact(uint32_t* sm, const __nv_bfloat16* __restrict__ x, const __nv_bfloat16* __restrict__ wqkv, int h, int qt) {
  const int tid = threadIdx.x;
  float a[20];
  for (int i = 0; i < 8; i++) {
    const int key = (i >> 1) * 512 + tid, ty = 1 + (i & 1);
    proj20(a, x + key * 640, wqkv + ty * 640 + h * 20);
#pragma unroll
    for (int d = 0; d < 10; d++) sm[key * 20 + (i & 1) * 10 + d] = pack_bf16(a[2 * d], a[2 * d + 1]);
  }
  const int row = qt * 512 + tid;
  proj20(a, x + row * 640, wqkv + h * 20);
#pragma unroll
  for (int d = 0; d < 20; d++) a[d] = __bfloat162float(__float2bfloat16(a[d]));
  __syncthreads();
  float o[20], m = -INFINITY, l = 0.f;
#pragma unroll
  for (int d = 0; d < 20; d++) o[d] = 0.f;
  for (int key = 0; key < 2048; key++) {
    float s = 0.f;
#pragma unroll
    for (int d = 0; d < 10; d++) {
      const uint32_t u = sm[key * 20 + d];
      s = fmaf(a[2 * d], __uint_as_float(u << 16), s);
      s = fmaf(a[2 * d + 1], __uint_as_float(u & 0xffff0000u), s);
    }
    s *= 0.22360679774997896f;
    const float mn = fmaxf(m, s), cr = __expf(m - mn), p = __expf(s - mn);
    m = mn;
    l = l * cr + p;
#pragma unroll
    for (int d = 0; d < 10; d++) {
      const uint32_t u = sm[key * 20 + 10 + d];
      o[2 * d] = fmaf(p, __uint_as_float(u << 16), o[2 * d] * cr);
      o[2 * d + 1] = fmaf(p, __uint_as_float(u & 0xffff0000u), o[2 * d + 1] * cr);
    }
  }
  const float sc = g_gate[row] / l;
  uint8_t* prow = g_o + (row >> 7) * ORB + (row & 127) * 16;
#pragma unroll
  for (int d = 0; d < 10; d++) {
    const int col = h * 20 + 2 * d;
    stg32(prow + (col >> 3) * 2048 + (col & 7) * 2, pack_bf16(o[2 * d] * sc, o[2 * d + 1] * sc));
  }
}

__global__ void __launch_bounds__(512, 1) k2_attn(const __nv_bfloat16* __restrict__ w_phi, const __nv_bfloat16* __restrict__ x, const __nv_bfloat16* __restrict__ wqkv) {
  extern __shared__ uint8_t smem_raw[];
  const uint32_t sb = ((uint32_t)__cvta_generic_to_shared(smem_raw) + 127) & ~127u;
  const int tid = threadIdx.x, lane = tid & 31, w = (tid >> 5) & 3, g = lane >> 2, t = lane & 3;
  const int wg = __shfl_sync(0xffffffffu, tid >> 7, 0);
  const int h = blockIdx.x >> 2, qt = blockIdx.x & 3, rb = qt * 4 + wg;
  const uint32_t bar = sb + K2_BAR;
  asm volatile("griddepcontrol.launch_dependents;");
  if (tid == 0) {
    for (int i = 0; i < 17; i++) mbar_init(bar + 8 * i, 1);
    asm volatile("fence.mbarrier_init.release.cluster;" ::: "memory");
  }
  for (int i = tid; i < 768; i += 512) {
    const int k = i / 24, n = i % 24, ii = 2 * (n >> 3) + (n & 1), f = 4 * ii + ((n & 7) >> 1);
    uint16_t v = 0;
    if (k < 20 && ii < 5) v = reinterpret_cast<const uint16_t*>(w_phi)[h * 400 + k * 20 + f];
    sts16(sb + K2_WPHI + (k >> 3) * 384 + n * 16 + (k & 7) * 2, v);
  }
  PROXY_FENCE();
  __syncthreads();
  asm volatile("griddepcontrol.wait;" ::: "memory");
  const uint8_t* qa = g_qkv + h * HS;
  const uint8_t* qb = qa + BRS;
  if (tid == 0) {
    mbar_expect(bar + 128, 24576);
    for (int i = 0; i < 4; i++) bulk_g2s(sb + K2_VB + i * 6144, qb + (qt * 4 + i) * RBS + 2 * TS, 6144, bar + 128);
    for (int i = 0; i < 10; i++) { mbar_expect(bar + 8 * i, 12288); bulk_g2s(sb + i * 12288, qa + i * RBS + TS, 12288, bar + 8 * i); }
  }
  const int rowoff = rb * RBS + (w * 16 + g) * 16 + t * 4;
  uint32_t q[2][6];
  int bad = g_kbad[tid] | g_kbad[512 + tid];
  const uint64_t dw = mkdesc(sb + K2_WPHI, 384, 128, 0);
  {
    load_frag(q[0], qb + TS + rowoff);
    load_frag(q[1], qb + TS + rowoff + 1024);
    const uint32_t ph = sb + K2_PHI + wg * 10240;
#pragma unroll
    for (int m = 0; m < 2; m++) {
      uint32_t phi[10];
      feature_map(phi, q[m], dw);
#pragma unroll
      for (int i = 0; i < 5; i++) {
        sts32(ph + i * 2048 + (m * 64 + w * 16 + g) * 16 + t * 4, phi[i]);
        sts32(ph + i * 2048 + (m * 64 + w * 16 + g + 8) * 16 + t * 4, phi[5 + i]);
      }
    }
    load_frag(q[0], qa + rowoff);
    load_frag(q[1], qa + rowoff + 1024);
    PROXY_FENCE();
    bar_sync(1 + wg, 128);
    mbar_wait(bar + 128, 0);
    float kv[12];
    const uint64_t da = mkdesc(ph, 128, 2048, 0), db = mkdesc(sb + K2_VB + wg * 6144, 128, 2048, 0);
    WG_FENCE();
#pragma unroll
    for (int kk = 0; kk < 8; kk++) wg24_ss_bf16_tt(kv, da + kk * 16, db + kk * 16, kk != 0);
    WG_COMMIT();
    WG_WAIT(0);
    pin(kv);
    float* dst = g_kv + h * 960 + (w * 16 + g) * 24 + 2 * t;
#pragma unroll
    for (int j = 0; j < 3; j++) {
      if (w < 3) asm volatile("red.global.add.v2.f32 [%0], {%1, %2};" ::"l"(dst + 8 * j), "f"(kv[4 * j]), "f"(kv[4 * j + 1]) : "memory");
      if (w < 2) asm volatile("red.global.add.v2.f32 [%0], {%1, %2};" ::"l"(dst + 192 + 8 * j), "f"(kv[4 * j + 2]), "f"(kv[4 * j + 3]) : "memory");
    }
    __threadfence();
    __syncthreads();
    if (tid == 0) {
      atomicAdd(&g_cnt[h], 1);
      for (int i = 10; i < 16; i++) { mbar_expect(bar + 8 * i, 12288); bulk_g2s(sb + i * 12288, qa + i * RBS + TS, 12288, bar + 8 * i); }
    }
  }
  {
    uint32_t m = 0;
#pragma unroll
    for (int i = 0; i < 6; i++) m = maxabs_bf16x2(m, maxabs_bf16x2(q[0][i], q[1][i]));
    bad |= (m & 0x7fffu) >= ((127u - 50u) << 7) || ((m >> 16) & 0x7fffu) >= ((127u - 50u) << 7);
  }
  float o[2][12];
#pragma unroll
  for (int i = 0; i < 12; i++) { o[0][i] = 0.f; o[1][i] = 0.f; }
  {
    float s[32];
    uint32_t p[16];
    uint64_t dk0 = mkdesc(sb, 2048, 128, 0), dk1 = mkdesc(sb + 4096, 0, 128, 0), dv = mkdesc(sb + 6144, 128, 2048, 0);
#pragma unroll 1
    for (int it = 0; it < 32; it++) {
      if (!(it & 1)) mbar_wait(bar + 4 * it, 0);
#pragma unroll
      for (int m = 0; m < 2; m++) {
        WG_FENCE();
        wg64_rs_bf16(s, q[m][0], q[m][1], q[m][2], q[m][3], dk0, 0);
        wg64_rs_bf16(s, q[m][4], q[m][5], 0u, 0u, dk1, 1);
        WG_COMMIT();
        WG_WAIT(0);
        constexpr int A = 2 * NMB, B = 16 - A;
#pragma unroll
        for (int j = 0; j < B; j++) {
          if ((j * A) % B < A) { const int a = j * A / B; p[a] = exp2_pair_mufu(s[2 * a], s[2 * a + 1]); }
          p[A + j] = exp2_pair(s[2 * (A + j)], s[2 * (A + j) + 1]);
        }
        WG_FENCE();
#pragma unroll
        for (int kk = 0; kk < 4; kk++) wg24_rs_f16_t(o[m], p[4 * kk], p[4 * kk + 1], p[4 * kk + 2], p[4 * kk + 3], dv + kk * 16, 1);
        WG_COMMIT();
      }
      const uint64_t adv = (it & 1) ? (12288 - 1024) / 16 : 1024 / 16;
      dk0 += adv; dk1 += adv; dv += adv;
    }
    WG_WAIT(0);
    pin(o[0]); pin(o[1]);
  }
  if (tid == 0) {
    int v;
    for (int i = 0;; i++) {
      asm volatile("ld.acquire.gpu.global.b32 %0, [%1];" : "=r"(v) : "l"(&g_cnt[h]) : "memory");
      if (v >= 4) break;
      if (i > (1 << 22)) __trap();
    }
  }
  load_frag(q[0], qb + rowoff);
  load_frag(q[1], qb + rowoff + 1024);
  float gt[4];
#pragma unroll
  for (int i = 0; i < 4; i++) gt[i] = __ldcg(&g_gate[rb * 128 + (i >> 1) * 64 + w * 16 + g + (i & 1) * 8]);
  uint8_t* orow = g_o + rb * ORB + (w * 16 + g) * 16;
  int big = 0;
#pragma unroll
  for (int m = 0; m < 2; m++) {
    const float l0 = __shfl_sync(0xffffffffu, o[m][8], (lane & ~3) | 2), l1 = __shfl_sync(0xffffffffu, o[m][10], (lane & ~3) | 2);
    const float r0 = __fdividef(1.f, l0), r1 = __fdividef(1.f, l1);
    float chk = 0.f, mx = 0.f;
#pragma unroll
    for (int i = 0; i < 12; i++) {
      chk = fmaf(o[m][i], 0.f, chk);
      if (i < 8 || t < 2) mx = fmaxf(mx, fabsf(o[m][i]) * ((i & 2) ? r1 : r0));
    }
    bad |= !(chk == 0.f) || !(l0 >= 32.f) || !(l1 >= 32.f);
    big |= mx >= 1.220703125e-4f;
    store_o(o[m], r0 * gt[2 * m], r1 * gt[2 * m + 1], orow + m * 1024, h * 20, t);
  }
  const int anybad = __syncthreads_or(bad);
  for (int i = tid; i < 1152; i += 512) {
    const int f = i / 24, d = i % 24;
    const float v = f < 40 ? __ldcg(&g_kv[h * 960 + i]) : 0.f;
    sts16(sb + K2_KVB + (f >> 3) * 384 + d * 16 + (f & 7) * 2, __bfloat16_as_ushort(__float2bfloat16(v)));
  }
  PROXY_FENCE();
  uint32_t phi[2][10];
  feature_map(phi[0], q[0], dw);
  feature_map(phi[1], q[1], dw);
  const int anybig = __syncthreads_or(big);
  const uint64_t dkv = mkdesc(sb + K2_KVB, 384, 128, 0);
#pragma unroll
  for (int m = 0; m < 2; m++) {
    WG_FENCE();
    wg24_rs_bf16(o[m], phi[m][0], phi[m][5], phi[m][1], phi[m][6], dkv, 0);
    wg24_rs_bf16(o[m], phi[m][2], phi[m][7], phi[m][3], phi[m][8], dkv + 48, 1);
    wg24_rs_bf16(o[m], phi[m][4], phi[m][9], 0u, 0u, dkv + 96, 1);
    WG_COMMIT();
  }
  WG_WAIT(0);
  pin(o[0]); pin(o[1]);
#pragma unroll
  for (int m = 0; m < 2; m++) {
    const float l0 = __shfl_sync(0xffffffffu, o[m][8], (lane & ~3) | 2), l1 = __shfl_sync(0xffffffffu, o[m][10], (lane & ~3) | 2);
    store_o(o[m], (1.f - gt[2 * m]) / (l0 + 1e-6f), (1.f - gt[2 * m + 1]) / (l1 + 1e-6f), orow + m * 1024, 640 + h * 20, t);
  }
  if (anybad || !anybig) attn_exact(reinterpret_cast<uint32_t*>(smem_raw + (sb - (uint32_t)__cvta_generic_to_shared(smem_raw))), x, wqkv, h, qt);
}

struct K3Maps { CUtensorMap w[2], out; };
constexpr int K3_ST = 4, K3_STB = 40960, K3_RX = K3_ST * K3_STB, K3_BAR = K3_RX + 49152;
constexpr int K3_SMEM = 1024 + K3_BAR + 128;

__global__ void __cluster_dims__(2, 1, 1) __launch_bounds__(384, 1) k3_out(const __grid_constant__ K3Maps maps) {
  extern __shared__ uint8_t smem_raw[];
  const uint32_t sb = ((uint32_t)__cvta_generic_to_shared(smem_raw) + 1023) & ~1023u;
  const uint32_t full = sb + K3_BAR, empty = full + 8 * K3_ST, rxbar = empty + 8 * K3_ST;
  const int tid = threadIdx.x, wg = tid >> 7, lane = tid & 31;
  const int br = blockIdx.x & 1, rb = blockIdx.x >> 3, cg = (blockIdx.x >> 1) & 3;
  const int atom0 = (cg >> 1) * 5 + (cg & 1) * 2;
  const bool wide = (cg & 1) == wg;
  if (tid == 256) {
    for (int i = 0; i < K3_ST; i++) { mbar_init(full + 8 * i, 1); mbar_init(empty + 8 * i, 2); }
    mbar_init(rxbar, 1);
    asm volatile("fence.mbarrier_init.release.cluster;" ::: "memory");
    mbar_expect(rxbar, ((cg & 1) == br ? 96 : 64) * 512);
    for (int it = 0; it < K3_ST; it++) {
      mbar_expect(full + 8 * it, K3_STB);
      tma3d(sb + it * K3_STB + 16384, &maps.w[br], 0, it * 64, atom0, full + 8 * it);
    }
  }
  __syncthreads();
  asm volatile("barrier.cluster.arrive.aligned;" ::: "memory");
  if (wg == 2) {
    if (tid == 256) {
      asm volatile("griddepcontrol.wait;" ::: "memory");
      const uint8_t* a = g_o + rb * ORB + br * 80 * 2048;
      for (int it = 0; it < 10; it++) {
        const int st = it % K3_ST;
        if (it >= K3_ST) {
          mbar_wait(empty + 8 * st, ((it / K3_ST) & 1) ^ 1);
          mbar_expect(full + 8 * st, K3_STB);
          tma3d(sb + st * K3_STB + 16384, &maps.w[br], 0, it * 64, atom0, full + 8 * st);
        }
        bulk_g2s(sb + st * K3_STB, a + it * 16384, 16384, full + 8 * st);
      }
    }
    __syncwarp();
    asm volatile("barrier.cluster.wait.aligned;" ::: "memory");
  } else {
    float acc[96];
    const int skip = (!wide && (cg & 1)) ? 1 : 0;
    if (wide) {
#pragma unroll 1
      for (int it = 0; it < 10; it++) {
        const int st = it % K3_ST;
        mbar_wait(full + 8 * st, (it / K3_ST) & 1);
        const uint32_t dst = sb + st * K3_STB;
        const uint64_t da = mkdesc(dst + wg * 1024, 2048, 128, 0), db = mkdesc(dst + 16384, 8192, 1024, 1);
        WG_FENCE();
#pragma unroll
        for (int k = 0; k < 4; k++) wg192_ss(acc, da + k * 256, db + k * 128, (it | k) != 0);
        WG_COMMIT();
        WG_WAIT(1);
        if (it > 0 && (tid & 127) == 0) mbar_arrive(empty + 8 * ((it - 1) % K3_ST));
      }
      WG_WAIT(0);
    } else {
#pragma unroll 1
      for (int it = 0; it < 10; it++) {
        const int st = it % K3_ST;
        mbar_wait(full + 8 * st, (it / K3_ST) & 1);
        const uint32_t dst = sb + st * K3_STB;
        const uint64_t da = mkdesc(dst + wg * 1024, 2048, 128, 0), db = mkdesc(dst + 16384 + skip * 8192, 8192, 1024, 1);
        WG_FENCE();
#pragma unroll
        for (int k = 0; k < 4; k++) wg128_ss_of96(acc, da + k * 256, db + k * 128, (it | k) != 0);
        WG_COMMIT();
        WG_WAIT(1);
        if (it > 0 && (tid & 127) == 0) mbar_arrive(empty + 8 * ((it - 1) % K3_ST));
      }
      WG_WAIT(0);
    }
    pin(acc);
    asm volatile("barrier.cluster.wait.aligned;" ::: "memory");
    const int nq = wide ? 24 : 16;
    if (wg != br) {
      uint32_t ra, rbar;
      asm("mapa.shared::cluster.u32 %0, %1, %2;" : "=r"(ra) : "r"(sb + K3_RX + (tid & 127) * 16), "r"(br ^ 1));
      asm("mapa.shared::cluster.u32 %0, %1, %2;" : "=r"(rbar) : "r"(rxbar), "r"(br ^ 1));
#pragma unroll
      for (int i = 0; i < 24; i++)
        if (i < nq)
          asm volatile("st.async.weak.shared::cluster.mbarrier::complete_tx::bytes.v4.f32 [%0], {%1, %2, %3, %4}, [%5];" ::"r"(ra + i * 2048),
                       "f"(acc[4 * i]), "f"(acc[4 * i + 1]), "f"(acc[4 * i + 2]), "f"(acc[4 * i + 3]), "r"(rbar) : "memory");
      bar_sync(1, 256);
    } else {
      bar_sync(1, 256);
      mbar_wait(rxbar, 0);
      const int w = (tid >> 5) & 3;
      const int r = w * 16 + (lane & 7) + ((lane >> 3) & 1) * 8;
#pragma unroll
      for (int i = 0; i < 24; i += 2)
        if (i < nq) {
          uint32_t u[4];
#pragma unroll
          for (int e = 0; e < 2; e++) {
            float4 v;
            asm volatile("ld.shared.v4.f32 {%0, %1, %2, %3}, [%4];" : "=f"(v.x), "=f"(v.y), "=f"(v.z), "=f"(v.w) : "r"(sb + K3_RX + (tid & 127) * 16 + (i + e) * 2048));
            u[2 * e] = pack_bf16(acc[4 * (i + e)] + v.x, acc[4 * (i + e) + 1] + v.y);
            u[2 * e + 1] = pack_bf16(acc[4 * (i + e) + 2] + v.z, acc[4 * (i + e) + 3] + v.w);
          }
          const int ch = (i & 7) + (lane >> 4);
          asm volatile("stmatrix.sync.aligned.m8n8.x4.shared.b16 [%0], {%1, %2, %3, %4};" ::"r"(sb + (i >> 3) * 8192 + r * 128 + ((ch ^ (r & 7)) << 4)),
                       "r"(u[0]), "r"(u[1]), "r"(u[2]), "r"(u[3]) : "memory");
        }
      PROXY_FENCE();
      bar_sync(2, 128);
      if ((tid & 127) == 0) {
        for (int a = 0; a < nq / 8; a++)
          asm volatile("cp.async.bulk.tensor.2d.global.shared::cta.bulk_group [%0, {%2, %3}], [%1];" ::"l"(&maps.out), "r"(sb + a * 8192), "r"((atom0 + skip + a) * 64), "r"(rb * 128 + wg * 64) : "memory");
        asm volatile("cp.async.bulk.commit_group;" ::: "memory");
        asm volatile("cp.async.bulk.wait_group 0;" ::: "memory");
      }
    }
  }
}

typedef CUresult (*EncodeFn)(CUtensorMap*, CUtensorMapDataType, cuuint32_t, void*, const cuuint64_t*, const cuuint64_t*, const cuuint32_t*, const cuuint32_t*,
                             CUtensorMapInterleave, CUtensorMapSwizzle, CUtensorMapL2promotion, CUtensorMapFloatOOBfill);
void encode(EncodeFn enc, CUtensorMap* m, void* p, int rank, const cuuint64_t* gd, const cuuint64_t* gs, const cuuint32_t* bd) {
  const cuuint32_t es[3] = {1, 1, 1};
  enc(m, CU_TENSOR_MAP_DATA_TYPE_BFLOAT16, rank, p, gd, gs, bd, es, CU_TENSOR_MAP_INTERLEAVE_NONE, CU_TENSOR_MAP_SWIZZLE_128B,
      CU_TENSOR_MAP_L2_PROMOTION_L2_128B, CU_TENSOR_MAP_FLOAT_OOB_FILL_NONE);
}

}

extern "C" void kernel_launch(void* const* d_in, const int* in_sizes, int n_in, void* d_out, int out_size) {
  static EncodeFn enc = nullptr;
  if (!enc) {
    cudaDriverEntryPointQueryResult qr;
    cudaGetDriverEntryPoint("cuTensorMapEncodeTiled", (void**)&enc, cudaEnableDefault, &qr);
    cudaFuncSetAttribute(k1_qkv, cudaFuncAttributeMaxDynamicSharedMemorySize, K1_SMEM);
    cudaFuncSetAttribute(k2_attn, cudaFuncAttributeMaxDynamicSharedMemorySize, K2_SMEM);
    cudaFuncSetAttribute(k3_out, cudaFuncAttributeMaxDynamicSharedMemorySize, K3_SMEM);
  }
  const __nv_bfloat16* x = (const __nv_bfloat16*)d_in[0];
  K1Maps m1;
  K3Maps m3;
  {
    const cuuint64_t gd[2] = {640, 2048}, gs[1] = {1280};
    const cuuint32_t bx[2] = {64, 128}, bo[2] = {64, 64};
    encode(enc, &m1.x, d_in[0], 2, gd, gs, bx);
    encode(enc, &m3.out, d_out, 2, gd, gs, bo);
  }
  for (int b = 0; b < 2; b++) {
    const cuuint64_t gd[3] = {64, 640, 30}, gs[2] = {3840, 128}, gd3[3] = {64, 640, 10}, gs3[2] = {1280, 128};
    const cuuint32_t bd[3] = {64, 64, 4}, bd3[3] = {64, 64, 3};
    encode(enc, &m1.w[b], d_in[b ? 4 : 1], 3, gd, gs, bd);
    encode(enc, &m3.w[b], d_in[b ? 6 : 2], 3, gd3, gs3, bd3);
  }
  cudaStream_t st = cudaStreamPerThread;
  k1_qkv<<<128, 384, K1_SMEM, st>>>(m1, x, (const __nv_bfloat16*)d_in[7]);
  cudaLaunchAttribute at[1];
  at[0].id = cudaLaunchAttributeProgrammaticStreamSerialization;
  at[0].val.programmaticStreamSerializationAllowed = 1;
  cudaLaunchConfig_t cfg = {};
  cfg.gridDim = dim3(128); cfg.blockDim = dim3(512); cfg.dynamicSmemBytes = K2_SMEM; cfg.stream = st; cfg.attrs = at; cfg.numAttrs = 1;
  cudaLaunchKernelEx(&cfg, k2_attn, (const __nv_bfloat16*)d_in[5], x, (const __nv_bfloat16*)d_in[1]);
  cfg.blockDim = dim3(384); cfg.dynamicSmemBytes = K3_SMEM;
  cudaLaunchKernelEx(&cfg, k3_out, m3);
}
```

```cpp
#include <cuda_runtime.h>
#include <cuda.h>
#include <cuda_bf16.h>
#include <cuda_fp16.h>
#include <stdint.h>

namespace {

constexpr int QRB = 240 * 2048;
constexpr int QBR = 16 * QRB;
constexpr int QTY = 80 * 2048;
constexpr int ORB = 160 * 2048;
constexpr int NMB = 3;

__device__ __align__(1024) uint8_t g_qkv[2 * QBR];
__device__ __align__(1024) uint8_t g_o[16 * ORB];
__device__ float g_gate[2048];
__device__ __align__(16) float g_kv[32 * 960];
__device__ __align__(16) int g_kbad[2048];
__device__ uint32_t g_fb[128 * 2048 * 20];
__device__ uint32_t g_cnt[192];
constexpr int C_EPOCH = 0, C_TA = 32, C_TB = 64, C_KV = 96, C_OB = 128, C_OA = 160;

#define TS_MARK(i)

__device__ __forceinline__ uint64_t mkdesc(uint32_t addr, uint32_t lbo, uint32_t sbo, int mode) {
  return (uint64_t)((addr & 0x3FFFF) >> 4) | ((uint64_t)(lbo >> 4) << 16) | ((uint64_t)(sbo >> 4) << 32) | ((uint64_t)mode << 62);
}
__device__ __forceinline__ uint64_t desc_lohi(uint32_t lo, uint32_t hi) { return ((uint64_t)hi << 32) | lo; }
#define WG_FENCE() asm volatile("wgmma.fence.sync.aligned;" ::: "memory")
#define WG_COMMIT() asm volatile("wgmma.commit_group.sync.aligned;" ::: "memory")
#define WG_WAIT(n) asm volatile("wgmma.wait_group.sync.aligned %0;" ::"n"(n) : "memory")
#define PROXY_FENCE() asm volatile("fence.proxy.async.shared::cta;" ::: "memory")
#define PROXY_FENCE_G() asm volatile("fence.proxy.async.global;" ::: "memory")
__device__ __forceinline__ void bar_sync(int id, int n) { asm volatile("bar.sync %0, %1;" ::"r"(id), "r"(n) : "memory"); }
__device__ __forceinline__ void mbar_init(uint32_t a, int c) { asm volatile("mbarrier.init.shared::cta.b64 [%0], %1;" ::"r"(a), "r"(c)); }
__device__ __forceinline__ uint32_t mbar_try(uint32_t a, int par) {
  uint32_t ok;
  asm volatile("{.reg .pred p; mbarrier.try_wait.parity.shared::cta.b64 p, [%1], %2; selp.b32 %0, 1, 0, p;}" : "=r"(ok) : "r"(a), "r"(par) : "memory");
  return ok;
}
__device__ __forceinline__ void mbar_wait(uint32_t a, int par) {
  for (int i = 0; !mbar_try(a, par); i++)
    if (i > (1 << 22)) break;
}
__device__ __forceinline__ void mbar_arrive(uint32_t a) { asm volatile("mbarrier.arrive.shared::cta.b64 _, [%0];" ::"r"(a) : "memory"); }
__device__ __forceinline__ void mbar_arrive_if(bool p, uint32_t a) {
  asm volatile("{.reg .pred p; setp.ne.b32 p, %0, 0; @p mbarrier.arrive.shared::cta.b64 _, [%1];}" ::"r"((int)p), "r"(a) : "memory");
}
__device__ __forceinline__ void mbar_expect_if(bool p, uint32_t a, int bytes) {
  asm volatile("{.reg .pred p; setp.ne.b32 p, %0, 0; @p mbarrier.arrive.expect_tx.shared::cta.b64 _, [%1], %2;}" ::"r"((int)p), "r"(a), "r"(bytes) : "memory");
}
__device__ __forceinline__ void tma2d_if(bool p, uint32_t dst, const CUtensorMap* m, int c0, int c1, uint32_t bar) {
  asm volatile("{.reg .pred p; setp.ne.b32 p, %0, 0; @p cp.async.bulk.tensor.2d.shared::cluster.global.mbarrier::complete_tx::bytes [%1], [%2, {%4, %5}], [%3];}"
               ::"r"((int)p), "r"(dst), "l"(m), "r"(bar), "r"(c0), "r"(c1) : "memory");
}
__device__ __forceinline__ void tma3d_if(bool p, uint32_t dst, const CUtensorMap* m, int c1, int c2, uint32_t bar) {
  asm volatile("{.reg .pred p; setp.ne.b32 p, %0, 0; @p cp.async.bulk.tensor.3d.shared::cluster.global.mbarrier::complete_tx::bytes [%1], [%2, {%6, %4, %5}], [%3];}"
               ::"r"((int)p), "r"(dst), "l"(m), "r"(bar), "r"(c1), "r"(c2), "r"(0) : "memory");
}
__device__ __forceinline__ void bulk_g2s_if(bool p, uint32_t dst, const void* src, int bytes, uint32_t bar) {
  asm volatile("{.reg .pred p; setp.ne.b32 p, %0, 0; @p cp.async.bulk.shared::cluster.global.mbarrier::complete_tx::bytes [%1], [%2], %3, [%4];}"
               ::"r"((int)p), "r"(dst), "l"(src), "r"(bytes), "r"(bar) : "memory");
}
__device__ __forceinline__ void bulk_s2g_if(bool p, void* dst, uint32_t src, int bytes) {
  asm volatile("{.reg .pred p; setp.ne.b32 p, %0, 0; @p cp.async.bulk.global.shared::cta.bulk_group [%1], [%2], %3; cp.async.bulk.commit_group;}"
               ::"r"((int)p), "l"(dst), "r"(src), "r"(bytes) : "memory");
}
__device__ __forceinline__ void signal_if(bool p, uint32_t* c) {
  asm volatile("{.reg .pred p; setp.ne.b32 p, %0, 0; @p fence.proxy.async.global; @p fence.acq_rel.gpu; @p red.relaxed.gpu.global.add.u32 [%1], 1;}" ::"r"((int)p), "l"(c) : "memory");
}
__device__ __forceinline__ void wait_count(const uint32_t* c, uint32_t target) {
  for (int i = 0;; i++) {
    uint32_t v;
    asm volatile("ld.acquire.gpu.global.u32 %0, [%1];" : "=r"(v) : "l"(c) : "memory");
    if ((int)(v - target) >= 0) break;
    if (i > (1 << 20)) break;
  }
  PROXY_FENCE_G();
}
__device__ __forceinline__ uint32_t pack_bf16(float lo, float hi) { uint32_t r; asm("cvt.rn.bf16x2.f32 %0, %1, %2;" : "=r"(r) : "f"(hi), "f"(lo)); return r; }
__device__ __forceinline__ uint32_t pack_f16(float lo, float hi) { uint32_t r; asm("cvt.rn.f16x2.f32 %0, %1, %2;" : "=r"(r) : "f"(hi), "f"(lo)); return r; }
__device__ __forceinline__ float ex2(float a) { float r; asm("ex2.approx.ftz.f32 %0, %1;" : "=f"(r) : "f"(a)); return r; }
__device__ __forceinline__ uint32_t maxabs_bf16x2(uint32_t a, uint32_t b) { uint32_t r; asm("max.NaN.xorsign.abs.bf16x2 %0, %1, %2;" : "=r"(r) : "r"(a), "r"(b)); return r; }
__device__ __forceinline__ uint32_t ldg32(const void* p) { return __ldg(reinterpret_cast<const uint32_t*>(p)); }
__device__ __forceinline__ uint32_t ldcg32(const void* p) { uint32_t v; asm volatile("ld.global.cg.u32 %0, [%1];" : "=r"(v) : "l"(p) : "memory"); return v; }
__device__ __forceinline__ void stg32(void* p, uint32_t v) { *reinterpret_cast<uint32_t*>(p) = v; }
__device__ __forceinline__ void sts32(uint32_t a, uint32_t v) { asm volatile("st.shared.b32 [%0], %1;" ::"r"(a), "r"(v) : "memory"); }
__device__ __forceinline__ void sts16(uint32_t a, uint16_t v) { asm volatile("st.shared.b16 [%0], %1;" ::"r"(a), "h"(v) : "memory"); }
__device__ __forceinline__ void stsm4(uint32_t a, uint32_t r0, uint32_t r1, uint32_t r2, uint32_t r3) {
  asm volatile("stmatrix.sync.aligned.m8n8.x4.shared.b16 [%0], {%1, %2, %3, %4};" ::"r"(a), "r"(r0), "r"(r1), "r"(r2), "r"(r3) : "memory");
}
template <int N> __device__ __forceinline__ void pin(float (&d)[N]) {
#pragma unroll
  for (int i = 0; i < N; i++) asm volatile("" : "+f"(d[i])::"memory");
}

__device__ __forceinline__ void wg128_ss(float (&d)[64], uint64_t da, uint64_t db, int scale_d) {
  asm volatile("{\n.reg .pred p;\nsetp.ne.b32 p, %66, 0;\n"
    "wgmma.mma_async.sync.aligned.m64n128k16.f32.bf16.bf16 "
    "{%0, %1, %2, %3, %4, %5, %6, %7, %8, %9, %10, %11, %12, %13, %14, %15,"
    "%16, %17, %18, %19, %20, %21, %22, %23, %24, %25, %26, %27, %28, %29, %30, %31,"
    "%32, %33, %34, %35, %36, %37, %38, %39, %40, %41, %42, %43, %44, %45, %46, %47,"
    "%48, %49, %50, %51, %52, %53, %54, %55, %56, %57, %58, %59, %60, %61, %62, %63}, "
    "%64, %65, p, 1, 1, 0, 1;\n}\n"
    : "+f"(d[0]), "+f"(d[1]), "+f"(d[2]), "+f"(d[3]), "+f"(d[4]), "+f"(d[5]), "+f"(d[6]), "+f"(d[7]),
      "+f"(d[8]), "+f"(d[9]), "+f"(d[10]), "+f"(d[11]), "+f"(d[12]), "+f"(d[13]), "+f"(d[14]), "+f"(d[15]),
      "+f"(d[16]), "+f"(d[17]), "+f"(d[18]), "+f"(d[19]), "+f"(d[20]), "+f"(d[21]), "+f"(d[22]), "+f"(d[23]),
      "+f"(d[24]), "+f"(d[25]), "+f"(d[26]), "+f"(d[27]), "+f"(d[28]), "+f"(d[29]), "+f"(d[30]), "+f"(d[31]),
      "+f"(d[32]), "+f"(d[33]), "+f"(d[34]), "+f"(d[35]), "+f"(d[36]), "+f"(d[37]), "+f"(d[38]), "+f"(d[39]),
      "+f"(d[40]), "+f"(d[41]), "+f"(d[42]), "+f"(d[43]), "+f"(d[44]), "+f"(d[45]), "+f"(d[46]), "+f"(d[47]),
      "+f"(d[48]), "+f"(d[49]), "+f"(d[50]), "+f"(d[51]), "+f"(d[52]), "+f"(d[53]), "+f"(d[54]), "+f"(d[55]),
      "+f"(d[56]), "+f"(d[57]), "+f"(d[58]), "+f"(d[59]), "+f"(d[60]), "+f"(d[61]), "+f"(d[62]), "+f"(d[63])
    : "l"(da), "l"(db), "r"(scale_d));
}

__device__ __forceinline__ void wg64_ss_of64(float (&d)[64], uint64_t da, uint64_t db, int scale_d) {
  asm volatile("{\n.reg .pred p;\nsetp.ne.b32 p, %34, 0;\n"
    "wgmma.mma_async.sync.aligned.m64n64k16.f32.bf16.bf16 "
    "{%0, %1, %2, %3, %4, %5, %6, %7, %8, %9, %10, %11, %12, %13, %14, %15,"
    "%16, %17, %18, %19, %20, %21, %22, %23, %24, %25, %26, %27, %28, %29, %30, %31}, "
    "%32, %33, p, 1, 1, 0, 1;\n}\n"
    : "+f"(d[0]), "+f"(d[1]), "+f"(d[2]), "+f"(d[3]), "+f"(d[4]), "+f"(d[5]), "+f"(d[6]), "+f"(d[7]),
      "+f"(d[8]), "+f"(d[9]), "+f"(d[10]), "+f"(d[11]), "+f"(d[12]), "+f"(d[13]), "+f"(d[14]), "+f"(d[15]),
      "+f"(d[16]), "+f"(d[17]), "+f"(d[18]), "+f"(d[19]), "+f"(d[20]), "+f"(d[21]), "+f"(d[22]), "+f"(d[23]),
      "+f"(d[24]), "+f"(d[25]), "+f"(d[26]), "+f"(d[27]), "+f"(d[28]), "+f"(d[29]), "+f"(d[30]), "+f"(d[31])
    : "l"(da), "l"(db), "r"(scale_d));
}

__device__ __forceinline__ void wg192_ss(float (&d)[96], uint64_t da, uint64_t db, int scale_d) {
  asm volatile("{\n.reg .pred p;\nsetp.ne.b32 p, %98, 0;\n"
    "wgmma.mma_async.sync.aligned.m64n192k16.f32.bf16.bf16 "
    "{%0, %1, %2, %3, %4, %5, %6, %7, %8, %9, %10, %11, %12, %13, %14, %15,"
    "%16, %17, %18, %19, %20, %21, %22, %23, %24, %25, %26, %27, %28, %29, %30, %31,"
    "%32, %33, %34, %35, %36, %37, %38, %39, %40, %41, %42, %43, %44, %45, %46, %47,"
    "%48, %49, %50, %51, %52, %53, %54, %55, %56, %57, %58, %59, %60, %61, %62, %63,"
    "%64, %65, %66, %67, %68, %69, %70, %71, %72, %73, %74, %75, %76, %77, %78, %79,"
    "%80, %81, %82, %83, %84, %85, %86, %87, %88, %89, %90, %91, %92, %93, %94, %95}, "
    "%96, %97, p, 1, 1, 0, 1;\n}\n"
    : "+f"(d[0]), "+f"(d[1]), "+f"(d[2]), "+f"(d[3]), "+f"(d[4]), "+f"(d[5]), "+f"(d[6]), "+f"(d[7]),
      "+f"(d[8]), "+f"(d[9]), "+f"(d[10]), "+f"(d[11]), "+f"(d[12]), "+f"(d[13]), "+f"(d[14]), "+f"(d[15]),
      "+f"(d[16]), "+f"(d[17]), "+f"(d[18]), "+f"(d[19]), "+f"(d[20]), "+f"(d[21]), "+f"(d[22]), "+f"(d[23]),
      "+f"(d[24]), "+f"(d[25]), "+f"(d[26]), "+f"(d[27]), "+f"(d[28]), "+f"(d[29]), "+f"(d[30]), "+f"(d[31]),
      "+f"(d[32]), "+f"(d[33]), "+f"(d[34]), "+f"(d[35]), "+f"(d[36]), "+f"(d[37]), "+f"(d[38]), "+f"(d[39]),
      "+f"(d[40]), "+f"(d[41]), "+f"(d[42]), "+f"(d[43]), "+f"(d[44]), "+f"(d[45]), "+f"(d[46]), "+f"(d[47]),
      "+f"(d[48]), "+f"(d[49]), "+f"(d[50]), "+f"(d[51]), "+f"(d[52]), "+f"(d[53]), "+f"(d[54]), "+f"(d[55]),
      "+f"(d[56]), "+f"(d[57]), "+f"(d[58]), "+f"(d[59]), "+f"(d[60]), "+f"(d[61]), "+f"(d[62]), "+f"(d[63]),
      "+f"(d[64]), "+f"(d[65]), "+f"(d[66]), "+f"(d[67]), "+f"(d[68]), "+f"(d[69]), "+f"(d[70]), "+f"(d[71]),
      "+f"(d[72]), "+f"(d[73]), "+f"(d[74]), "+f"(d[75]), "+f"(d[76]), "+f"(d[77]), "+f"(d[78]), "+f"(d[79]),
      "+f"(d[80]), "+f"(d[81]), "+f"(d[82]), "+f"(d[83]), "+f"(d[84]), "+f"(d[85]), "+f"(d[86]), "+f"(d[87]),
      "+f"(d[88]), "+f"(d[89]), "+f"(d[90]), "+f"(d[91]), "+f"(d[92]), "+f"(d[93]), "+f"(d[94]), "+f"(d[95])
    : "l"(da), "l"(db), "r"(scale_d));
}

__device__ __forceinline__ void wg128_ss_of96(float (&d)[96], uint64_t da, uint64_t db, int scale_d) {
  asm volatile("{\n.reg .pred p;\nsetp.ne.b32 p, %66, 0;\n"
    "wgmma.mma_async.sync.aligned.m64n128k16.f32.bf16.bf16 "
    "{%0, %1, %2, %3, %4, %5, %6, %7, %8, %9, %10, %11, %12, %13, %14, %15,"
    "%16, %17, %18, %19, %20, %21, %22, %23, %24, %25, %26, %27, %28, %29, %30, %31,"
    "%32, %33, %34, %35, %36, %37, %38, %39, %40, %41, %42, %43, %44, %45, %46, %47,"
    "%48, %49, %50, %51, %52, %53, %54, %55, %56, %57, %58, %59, %60, %61, %62, %63}, "
    "%64, %65, p, 1, 1, 0, 1;\n}\n"
    : "+f"(d[0]), "+f"(d[1]), "+f"(d[2]), "+f"(d[3]), "+f"(d[4]), "+f"(d[5]), "+f"(d[6]), "+f"(d[7]),
      "+f"(d[8]), "+f"(d[9]), "+f"(d[10]), "+f"(d[11]), "+f"(d[12]), "+f"(d[13]), "+f"(d[14]), "+f"(d[15]),
      "+f"(d[16]), "+f"(d[17]), "+f"(d[18]), "+f"(d[19]), "+f"(d[20]), "+f"(d[21]), "+f"(d[22]), "+f"(d[23]),
      "+f"(d[24]), "+f"(d[25]), "+f"(d[26]), "+f"(d[27]), "+f"(d[28]), "+f"(d[29]), "+f"(d[30]), "+f"(d[31]),
      "+f"(d[32]), "+f"(d[33]), "+f"(d[34]), "+f"(d[35]), "+f"(d[36]), "+f"(d[37]), "+f"(d[38]), "+f"(d[39]),
      "+f"(d[40]), "+f"(d[41]), "+f"(d[42]), "+f"(d[43]), "+f"(d[44]), "+f"(d[45]), "+f"(d[46]), "+f"(d[47]),
      "+f"(d[48]), "+f"(d[49]), "+f"(d[50]), "+f"(d[51]), "+f"(d[52]), "+f"(d[53]), "+f"(d[54]), "+f"(d[55]),
      "+f"(d[56]), "+f"(d[57]), "+f"(d[58]), "+f"(d[59]), "+f"(d[60]), "+f"(d[61]), "+f"(d[62]), "+f"(d[63])
    : "l"(da), "l"(db), "r"(scale_d));
}

__device__ __forceinline__ void wg64_rs_bf16(float (&d)[32], uint32_t a0, uint32_t a1, uint32_t a2, uint32_t a3, uint64_t db, int scale_d) {
  asm volatile("{\n.reg .pred p;\nsetp.ne.b32 p, %37, 0;\n"
    "wgmma.mma_async.sync.aligned.m64n64k16.f32.bf16.bf16 "
    "{%0, %1, %2, %3, %4, %5, %6, %7, %8, %9, %10, %11, %12, %13, %14, %15,"
    "%16, %17, %18, %19, %20, %21, %22, %23, %24, %25, %26, %27, %28, %29, %30, %31}, "
    "{%32, %33, %34, %35}, %36, p, 1, 1, 0;\n}\n"
    : "+f"(d[0]), "+f"(d[1]), "+f"(d[2]), "+f"(d[3]), "+f"(d[4]), "+f"(d[5]), "+f"(d[6]), "+f"(d[7]),
      "+f"(d[8]), "+f"(d[9]), "+f"(d[10]), "+f"(d[11]), "+f"(d[12]), "+f"(d[13]), "+f"(d[14]), "+f"(d[15]),
      "+f"(d[16]), "+f"(d[17]), "+f"(d[18]), "+f"(d[19]), "+f"(d[20]), "+f"(d[21]), "+f"(d[22]), "+f"(d[23]),
      "+f"(d[24]), "+f"(d[25]), "+f"(d[26]), "+f"(d[27]), "+f"(d[28]), "+f"(d[29]), "+f"(d[30]), "+f"(d[31])
    : "r"(a0), "r"(a1), "r"(a2), "r"(a3), "l"(db), "r"(scale_d));
}

__device__ __forceinline__ void wg24_rs_f16_t(float (&d)[12], uint32_t a0, uint32_t a1, uint32_t a2, uint32_t a3, uint64_t db, int scale_d) {
  asm volatile("{\n.reg .pred p;\nsetp.ne.b32 p, %17, 0;\n"
    "wgmma.mma_async.sync.aligned.m64n24k16.f32.f16.f16 "
    "{%0, %1, %2, %3, %4, %5, %6, %7, %8, %9, %10, %11}, "
    "{%12, %13, %14, %15}, %16, p, 1, 1, 1;\n}\n"
    : "+f"(d[0]), "+f"(d[1]), "+f"(d[2]), "+f"(d[3]), "+f"(d[4]), "+f"(d[5]), "+f"(d[6]), "+f"(d[7]),
      "+f"(d[8]), "+f"(d[9]), "+f"(d[10]), "+f"(d[11])
    : "r"(a0), "r"(a1), "r"(a2), "r"(a3), "l"(db), "r"(scale_d));
}

__device__ __forceinline__ void wg24_rs_bf16(float (&d)[12], uint32_t a0, uint32_t a1, uint32_t a2, uint32_t a3, uint64_t db, int scale_d) {
  asm volatile("{\n.reg .pred p;\nsetp.ne.b32 p, %17, 0;\n"
    "wgmma.mma_async.sync.aligned.m64n24k16.f32.bf16.bf16 "
    "{%0, %1, %2, %3, %4, %5, %6, %7, %8, %9, %10, %11}, "
    "{%12, %13, %14, %15}, %16, p, 1, 1, 0;\n}\n"
    : "+f"(d[0]), "+f"(d[1]), "+f"(d[2]), "+f"(d[3]), "+f"(d[4]), "+f"(d[5]), "+f"(d[6]), "+f"(d[7]),
      "+f"(d[8]), "+f"(d[9]), "+f"(d[10]), "+f"(d[11])
    : "r"(a0), "r"(a1), "r"(a2), "r"(a3), "l"(db), "r"(scale_d));
}

__device__ __forceinline__ void wg24_ss_bf16_tt(float (&d)[12], uint64_t da, uint64_t db, int scale_d) {
  asm volatile("{\n.reg .pred p;\nsetp.ne.b32 p, %14, 0;\n"
    "wgmma.mma_async.sync.aligned.m64n24k16.f32.bf16.bf16 "
    "{%0, %1, %2, %3, %4, %5, %6, %7, %8, %9, %10, %11}, "
    "%12, %13, p, 1, 1, 1, 1;\n}\n"
    : "+f"(d[0]), "+f"(d[1]), "+f"(d[2]), "+f"(d[3]), "+f"(d[4]), "+f"(d[5]), "+f"(d[6]), "+f"(d[7]),
      "+f"(d[8]), "+f"(d[9]), "+f"(d[10]), "+f"(d[11])
    : "l"(da), "l"(db), "r"(scale_d));
}

__device__ __forceinline__ void wg64_rs_bf16_i(float (&d)[32], uint32_t a0, uint32_t a1, uint32_t a2, uint32_t a3, uint64_t db) {
  asm volatile("{\n.reg .pred p;\nsetp.ne.b32 p, 0, 0;\n"
    "wgmma.mma_async.sync.aligned.m64n64k16.f32.bf16.bf16 "
    "{%0, %1, %2, %3, %4, %5, %6, %7, %8, %9, %10, %11, %12, %13, %14, %15,"
    "%16, %17, %18, %19, %20, %21, %22, %23, %24, %25, %26, %27, %28, %29, %30, %31}, "
    "{%32, %33, %34, %35}, %36, p, 1, 1, 0;\n}\n"
    : "=f"(d[0]), "=f"(d[1]), "=f"(d[2]), "=f"(d[3]), "=f"(d[4]), "=f"(d[5]), "=f"(d[6]), "=f"(d[7]),
      "=f"(d[8]), "=f"(d[9]), "=f"(d[10]), "=f"(d[11]), "=f"(d[12]), "=f"(d[13]), "=f"(d[14]), "=f"(d[15]),
      "=f"(d[16]), "=f"(d[17]), "=f"(d[18]), "=f"(d[19]), "=f"(d[20]), "=f"(d[21]), "=f"(d[22]), "=f"(d[23]),
      "=f"(d[24]), "=f"(d[25]), "=f"(d[26]), "=f"(d[27]), "=f"(d[28]), "=f"(d[29]), "=f"(d[30]), "=f"(d[31])
    : "r"(a0), "r"(a1), "r"(a2), "r"(a3), "l"(db));
}

__device__ __forceinline__ void wg24_rs_bf16_i(float (&d)[12], uint32_t a0, uint32_t a1, uint32_t a2, uint32_t a3, uint64_t db) {
  asm volatile("{\n.reg .pred p;\nsetp.ne.b32 p, 0, 0;\n"
    "wgmma.mma_async.sync.aligned.m64n24k16.f32.bf16.bf16 "
    "{%0, %1, %2, %3, %4, %5, %6, %7, %8, %9, %10, %11}, "
    "{%12, %13, %14, %15}, %16, p, 1, 1, 0;\n}\n"
    : "=f"(d[0]), "=f"(d[1]), "=f"(d[2]), "=f"(d[3]), "=f"(d[4]), "=f"(d[5]), "=f"(d[6]), "=f"(d[7]),
      "=f"(d[8]), "=f"(d[9]), "=f"(d[10]), "=f"(d[11])
    : "r"(a0), "r"(a1), "r"(a2), "r"(a3), "l"(db));
}

__device__ __forceinline__ void wg24_ss_bf16_tt_i(float (&d)[12], uint64_t da, uint64_t db) {
  asm volatile("{\n.reg .pred p;\nsetp.ne.b32 p, 0, 0;\n"
    "wgmma.mma_async.sync.aligned.m64n24k16.f32.bf16.bf16 "
    "{%0, %1, %2, %3, %4, %5, %6, %7, %8, %9, %10, %11}, "
    "%12, %13, p, 1, 1, 1, 1;\n}\n"
    : "=f"(d[0]), "=f"(d[1]), "=f"(d[2]), "=f"(d[3]), "=f"(d[4]), "=f"(d[5]), "=f"(d[6]), "=f"(d[7]),
      "=f"(d[8]), "=f"(d[9]), "=f"(d[10]), "=f"(d[11])
    : "l"(da), "l"(db));
}

constexpr int P1_STB = 49152, P3_STB = 40960;
constexpr int SM_X = 196608;
constexpr int SM_VB = SM_X, SM_PHI = SM_X + 6144, SM_KVB = SM_X + 24576;
constexpr int SM_CONST = SM_X + 32768, SM_WPHI = SM_CONST + 1024, SM_BAR = SM_WPHI + 1536;
constexpr int SMEM_BYTES = SM_BAR + 512;
constexpr int B_FULL = 0, B_EMPTY = 4, B_STG = 8, B_STG2 = 9, B_VB = 10, B_LINK = 11, B_KVB = 14, B_P3FREE = 15, B_KVFULL = 16, B_READY = 32, B_P3FULL = 48, B_P3EMPTY = 52;

struct Maps { CUtensorMap x, w[2], wo[2], out; };

__device__ __forceinline__ int tile_atom(int t) { return (t >> 2) * 15 + ((0xB740 >> ((t & 3) * 4)) & 15); }

template <int MODE, int A>
__device__ __forceinline__ void stage_atom(const float (&acc)[64], uint32_t sa, float s0, float s1, uint32_t& m0, uint32_t& m1) {
#pragma unroll
  for (int jj = 0; jj < 8; jj += 2) {
    uint32_t r[4];
#pragma unroll
    for (int e = 0; e < 4; e++) {
      const int i = (A * 8 + jj) * 4 + 2 * e;
      const float s = (e & 1) ? s1 : s0;
      if (MODE == 0) r[e] = pack_bf16(acc[i], acc[i + 1]);
      else if (MODE == 3) r[e] = pack_f16(acc[i], acc[i + 1]);
      else r[e] = pack_bf16(acc[i] * s, acc[i + 1] * s);
    }
    if (MODE == 2) { m0 = maxabs_bf16x2(m0, maxabs_bf16x2(r[0], r[2])); m1 = maxabs_bf16x2(m1, maxabs_bf16x2(r[1], r[3])); }
    stsm4(sa + (A * 8 + jj) * 1024, r[0], r[1], r[2], r[3]);
  }
}
template <int A>
__device__ __forceinline__ void stage_atom_a(const float (&acc)[64], int ga, uint32_t sa, float sk0, float sk1, uint32_t& m0, uint32_t& m1) {
  if (ga < 10) { const float cq = __uint_as_float(463809372u); stage_atom<1, A>(acc, sa, cq, cq, m0, m1); }
  else if (ga < 20) stage_atom<2, A>(acc, sa, sk0, sk1, m0, m1);
  else stage_atom<3, A>(acc, sa, 0.f, 0.f, m0, m1);
}

__device__ __forceinline__ uint32_t exp2_pair(float a, float b) {
  uint32_t z, w, h;
  asm volatile("cvt.pack.sat.s16.s32 %0, %2, %1;" : "=r"(z) : "r"(__float_as_uint(a)), "r"(__float_as_uint(b)));
  asm volatile("lop3.b32 %0, %1, 0x03ff03ff, 0x34003400, 0xEA;" : "=r"(w) : "r"(z));
  asm volatile("fma.rn.f16x2 %0, %1, %1, %2;" : "=r"(h) : "r"(w), "r"(0x36203620));
  asm volatile("fma.rn.f16x2 %0, %0, %1, %2;" : "+r"(h) : "r"(w), "r"(0x2e012e01));
  return h + z - w;
}
__device__ __forceinline__ uint32_t exp2_pair_mufu(float a, float b) {
  float x, y; uint32_t r;
  asm volatile("ex2.approx.ftz.f32 %0, %1;" : "=f"(x) : "f"(a));
  asm volatile("ex2.approx.ftz.f32 %0, %1;" : "=f"(y) : "f"(b));
  asm volatile("cvt.rn.f16x2.f32 %0, %1, %2;" : "=r"(r) : "f"(y), "f"(x));
  return r;
}
__device__ __forceinline__ void load_frag(uint32_t (&a)[6], const uint8_t* p) {
  a[0] = ldcg32(p); a[1] = ldcg32(p + 128); a[2] = ldcg32(p + 2048); a[3] = ldcg32(p + 2048 + 128); a[4] = ldcg32(p + 4096); a[5] = ldcg32(p + 4096 + 128);
}
__device__ __forceinline__ void feature_map(uint32_t (&phi)[10], const uint32_t (&a)[6], uint64_t dw) {
  float p[12];
  WG_FENCE();
  wg24_rs_bf16_i(p, a[0], a[1], a[2], a[3], dw);
  wg24_rs_bf16(p, a[4], a[5], 0u, 0u, dw + 48, 1);
  WG_COMMIT();
  WG_WAIT(0);
  pin(p);
  const float L = 1.4426950408889634f;
#pragma unroll
  for (int r = 0; r < 2; r++) {
    float v[5] = {p[2 * r], p[2 * r + 1], p[4 + 2 * r], p[5 + 2 * r], p[8 + 2 * r]};
    float mx = fmaxf(fmaxf(fmaxf(v[0], v[1]), fmaxf(v[2], v[3])), v[4]);
    float mn = fminf(fminf(fminf(v[0], v[1]), fminf(v[2], v[3])), v[4]);
    mx = fmaxf(mx, __shfl_xor_sync(0xffffffffu, mx, 1)); mn = fminf(mn, __shfl_xor_sync(0xffffffffu, mn, 1));
    mx = fmaxf(mx, __shfl_xor_sync(0xffffffffu, mx, 2)); mn = fminf(mn, __shfl_xor_sync(0xffffffffu, mn, 2));
    float ep[5], en[5], sp = 0.f, sn = 0.f;
#pragma unroll
    for (int i = 0; i < 5; i++) { ep[i] = ex2((v[i] - mx) * L); en[i] = ex2((mn - v[i]) * L); sp += ep[i]; sn += en[i]; }
    sp += __shfl_xor_sync(0xffffffffu, sp, 1); sn += __shfl_xor_sync(0xffffffffu, sn, 1);
    sp += __shfl_xor_sync(0xffffffffu, sp, 2); sn += __shfl_xor_sync(0xffffffffu, sn, 2);
    const float rp = __fdividef(1.f, sp), rn = __fdividef(1.f, sn);
#pragma unroll
    for (int i = 0; i < 5; i++) phi[5 * r + i] = pack_bf16(ep[i] * rp, en[i] * rn);
  }
}
__device__ __forceinline__ void store_o(const float (&o)[12], float s0, float s1, uint8_t* p, bool v0, bool v2) {
#pragma unroll
  for (int j = 0; j < 3; j++)
    if (j == 1 || (j == 0 ? v0 : v2)) {
      stg32(p + j * 2048, pack_bf16(o[4 * j] * s0, o[4 * j + 1] * s0));
      stg32(p + j * 2048 + 128, pack_bf16(o[4 * j + 2] * s1, o[4 * j + 3] * s1));
    }
}

__device__ __forceinline__ void proj20(float (&acc)[20], const __nv_bfloat16* __restrict__ xr, const __nv_bfloat16* __restrict__ wc) {
#pragma unroll
  for (int d = 0; d < 20; d++) acc[d] = 0.f;
#pragma unroll 2
  for (int k = 0; k < 640; k++) {
    const float xv = __bfloat162float(xr[k]);
#pragma unroll
    for (int d = 0; d < 10; d++) {
      const uint32_t u = ldg32(wc + k * 1920 + 2 * d);
      acc[2 * d] = fmaf(xv, __uint_as_float(u << 16), acc[2 * d]);
      acc[2 * d + 1] = fmaf(xv, __uint_as_float(u & 0xffff0000u), acc[2 * d + 1]);
    }
  }
}
__device__ __noinline__ void attn_exact(const __nv_bfloat16* __restrict__ x, const __nv_bfloat16* __restrict__ wqkv, int h, int qt) {
  const int tid = threadIdx.x;
  uint32_t* kvs = g_fb + blockIdx.x * (2048 * 20);
  float a[20];
  for (int i = 0; i < 8; i++) {
    const int key = (i >> 1) * 512 + tid, ty = 1 + (i & 1);
    proj20(a, x + key * 640, wqkv + ty * 640 + h * 20);
#pragma unroll
    for (int d = 0; d < 10; d++) kvs[key * 20 + (i & 1) * 10 + d] = pack_bf16(a[2 * d], a[2 * d + 1]);
  }
  const int row = qt * 512 + tid;
  proj20(a, x + row * 640, wqkv + h * 20);
#pragma unroll
  for (int d = 0; d < 20; d++) a[d] = __bfloat162float(__float2bfloat16(a[d]));
  __syncthreads();
  float o[20], m = -INFINITY, l = 0.f;
#pragma unroll
  for (int d = 0; d < 20; d++) o[d] = 0.f;
  for (int key = 0; key < 2048; key++) {
    uint32_t u[20];
#pragma unroll
    for (int d = 0; d < 5; d++) {
      const uint4 t4 = *reinterpret_cast<const uint4*>(kvs + key * 20 + 4 * d);
      u[4 * d] = t4.x; u[4 * d + 1] = t4.y; u[4 * d + 2] = t4.z; u[4 * d + 3] = t4.w;
    }
    float s = 0.f;
#pragma unroll
    for (int d = 0; d < 10; d++) {
      s = fmaf(a[2 * d], __uint_as_float(u[d] << 16), s);
      s = fmaf(a[2 * d + 1], __uint_as_float(u[d] & 0xffff0000u), s);
    }
    s *= 0.22360679774997896f;
    const float mn = fmaxf(m, s), cr = __expf(m - mn), p = __expf(s - mn);
    m = mn;
    l = l * cr + p;
#pragma unroll
    for (int d = 0; d < 10; d++) {
      o[2 * d] = fmaf(p, __uint_as_float(u[10 + d] << 16), o[2 * d] * cr);
      o[2 * d + 1] = fmaf(p, __uint_as_float(u[10 + d] & 0xffff0000u), o[2 * d + 1] * cr);
    }
  }
  const float sc = __ldcg(&g_gate[row]) / l;
  uint8_t* prow = g_o + (row >> 7) * ORB + (row & 127) * 16;
#pragma unroll
  for (int d = 0; d < 10; d++) {
    const int col = h * 20 + 2 * d;
    stg32(prow + (col >> 3) * 2048 + (col & 7) * 2, pack_bf16(o[2 * d] * sc, o[2 * d + 1] * sc));
  }
  __syncthreads();
}

__global__ void __launch_bounds__(512, 1)
gated_mix_kernel(const __grid_constant__ Maps maps, const __nv_bfloat16* __restrict__ x, const __nv_bfloat16* __restrict__ wqkv, const __nv_bfloat16* __restrict__ w_phi,
                 const __nv_bfloat16* __restrict__ gate_w, uint4* __restrict__ out) {
  extern __shared__ __align__(1024) uint8_t smem_raw[];
  const uint32_t sb = (uint32_t)__cvta_generic_to_shared(smem_raw);
  const uint32_t bar = sb + SM_BAR;
  const int tid = threadIdx.x, lane = tid & 31, w = (tid >> 5) & 3, g = lane >> 2, t = lane & 3, wt = tid & 127;
  const int wg = __shfl_sync(0xffffffffu, tid >> 7, 0);
  const int bid = blockIdx.x;
  const int rb1 = bid >> 3, c1 = bid & 7;
  const int h = bid >> 2, qt = bid & 3, rb = qt * 4 + wg;
  const bool odd = h & 1;
  TS_MARK(0);

  auto p1_load = [&](bool p, int it) {
    const int st = it & 3, br = it >= 10, ks = it - br * 10;
    const uint32_t dst = sb + st * P1_STB, fb = bar + 8 * (B_FULL + st);
    mbar_expect_if(p, fb, P1_STB);
    tma2d_if(p, dst, &maps.x, ks * 64, rb1 * 128, fb);
    tma3d_if(p, dst + 16384, &maps.w[br], ks * 64, tile_atom(c1 ^ br), fb);
  };
  if (tid == 0) {
    if (sb & 1023) __trap();
    for (int i = 0; i < 4; i++) { mbar_init(bar + 8 * (B_FULL + i), 1); mbar_init(bar + 8 * (B_EMPTY + i), 4); }
    asm volatile("fence.mbarrier_init.release.cluster;" ::: "memory");
    for (int i = 0; i < 4; i++) p1_load(true, i);
  }
  if (tid == 32) {
    mbar_init(bar + 8 * B_STG, 2); mbar_init(bar + 8 * B_STG2, 4); mbar_init(bar + 8 * B_VB, 1);
    for (int i = 0; i < 3; i++) mbar_init(bar + 8 * (B_LINK + i), 4);
    mbar_init(bar + 8 * B_KVB, 128); mbar_init(bar + 8 * B_P3FREE, 4);
    for (int i = 0; i < 16; i++) { mbar_init(bar + 8 * (B_KVFULL + i), 2); mbar_init(bar + 8 * (B_READY + i), 128); }
    for (int i = 0; i < 4; i++) { mbar_init(bar + 8 * (B_P3FULL + i), 1); mbar_init(bar + 8 * (B_P3EMPTY + i), 2); }
    asm volatile("fence.mbarrier_init.release.cluster;" ::: "memory");
  }
  const uint32_t epoch = (ldcg32(&g_cnt[C_EPOCH]) >> 7) + 1;
  {
    const int row = rb1 * 128 + c1 * 16 + (tid >> 5);
    float s = 0.f;
#pragma unroll
    for (int i = 0; i < 5; i++) {
      const uint2 a = __ldg(reinterpret_cast<const uint2*>(x + row * 640 + i * 128 + lane * 4));
      const uint2 b = __ldg(reinterpret_cast<const uint2*>(gate_w + i * 128 + lane * 4));
      s += __uint_as_float(a.x << 16) * __uint_as_float(b.x << 16) + __uint_as_float(a.x & 0xffff0000u) * __uint_as_float(b.x & 0xffff0000u);
      s += __uint_as_float(a.y << 16) * __uint_as_float(b.y << 16) + __uint_as_float(a.y & 0xffff0000u) * __uint_as_float(b.y & 0xffff0000u);
    }
    for (int i = tid; i < 768; i += 512) {
      const int k = i / 24, n = i % 24, ii = 2 * (n >> 3) + (n & 1), f = 4 * ii + ((n & 7) >> 1), d = k - (odd ? 4 : 0);
      uint16_t v = 0;
      if (d >= 0 && d < 20 && ii < 5) v = reinterpret_cast<const uint16_t*>(w_phi)[h * 400 + d * 20 + f];
      sts16(sb + SM_WPHI + (k >> 3) * 384 + n * 16 + (k & 7) * 2, v);
    }
    if (tid < 256) sts32(sb + SM_CONST + tid * 4, (tid & 3) ? 0u : ((tid >> 5) < NMB ? 0xdd02e192u : 0x00001ef0u));
    for (int i = tid; i < 1280; i += 512) out[bid * 1280 + i] = make_uint4(0u, 0u, 0u, 0u);
    if (tid < 240) g_kv[bid * 240 + tid] = 0.f;
#pragma unroll
    for (int o = 16; o; o >>= 1) s += __shfl_xor_sync(0xffffffffu, s, o);
    if (lane == 0) g_gate[row] = 1.f / (1.f + __expf(-s));
    PROXY_FENCE();
  }
  __syncthreads();

  const uint8_t* qa = g_qkv + ((h * 5) >> 1) * 2048;
  const int rowoff = rb * QRB + (w * 16 + g) * 16 + t * 4;
  uint32_t q[2][6];
  int bad;
  {
    float acc[64];
    const int r = wg & 1, ch = wg >> 1;
    const bool mufu0 = 2 * w < NMB, mufu1 = 2 * w + 1 < NMB;
#pragma unroll 1
    for (int br = 0; br < 2; br++) {
      const int tl = c1 ^ br, k4 = tl & 3;
      const bool narrow = (k4 == 1 && wg == 3) || (k4 == 2 && wg == 0);
      const int a0 = 2 * ch + ((k4 == 2 && wg == 0) ? 1 : 0);
      uint8_t* gdst = g_qkv + br * QBR + rb1 * QRB + ((tile_atom(tl) + a0) * 8 + lane) * 2048 + r * 1024;
      auto duties = [&](int it) {
        if (wg == (it & 3) && it >= 1 && it <= 16 && it != 10) {
          mbar_wait(bar + 8 * (B_EMPTY + ((it - 1) & 3)), ((it - 1) >> 2) & 1);
          p1_load(wt == 0, it + 3);
        }
        if (it == 12) {
          if (wg >= 2) {
            asm volatile("cp.async.bulk.wait_group.read 0;" ::: "memory");
            __syncwarp();
            mbar_arrive_if(wt == 0, bar + 8 * B_STG);
          }
          mbar_wait(bar + 8 * B_STG, 0);
          if (wg == 3) p1_load(wt == 0, 13);
          if (wg < 2) {
            const int tl0 = c1, k40 = tl0 & 3, skip = (k40 == 2 && wg == 0) ? 1 : 0;
            bulk_s2g_if(wt < 16 - 8 * skip, g_qkv + rb1 * QRB + ((tile_atom(tl0) + skip) * 8 + lane) * 2048 + r * 1024, sb + SM_X + wg * 16384 + lane * 1024, 1024);
          }
        }
        if (it == 16) {
          asm volatile("cp.async.bulk.wait_group 0;" ::: "memory");
          __syncwarp();
          signal_if(wt == 0, &g_cnt[C_TA]);
        }
        if (it >= 18 && wg == (it & 3)) {
          if (it == 18) wait_count(&g_cnt[C_TA], epoch * 512);
          else mbar_wait(bar + 8 * (B_KVFULL + 0), 0);
          mbar_wait(bar + 8 * (B_EMPTY + (it - 18)), 0);
          const int b = (it - 18) * 4 + (lane >> 1), kv = lane & 1;
          mbar_expect_if(wt < 8, bar + 8 * (B_KVFULL + b), 6144);
          bulk_g2s_if(wt < 8, sb + b * 12288 + kv * 6144, qa + b * QRB + (1 + kv) * QTY, 6144, bar + 8 * (B_KVFULL + b));
        }
      };
      if (!narrow) {
#pragma unroll 1
        for (int ks = 0; ks < 10; ks++) {
          const int it = br * 10 + ks, st = it & 3;
          mbar_wait(bar + 8 * (B_FULL + st), (it >> 2) & 1);
          if (it == 0) TS_MARK(1);
          const uint32_t dst = sb + st * P1_STB;
          const uint64_t da = mkdesc(dst + r * 8192, 16, 1024, 1), db = mkdesc(dst + 16384 + a0 * 8192, 8192, 1024, 1);
          WG_FENCE();
#pragma unroll
          for (int k = 0; k < 4; k++) wg128_ss(acc, da + k * 2, db + k * 128, (ks | k) != 0);
          WG_COMMIT();
          WG_WAIT(1);
          mbar_arrive_if(ks > 0 && wt == 0, bar + 8 * (B_EMPTY + ((it - 1) & 3)));
          duties(it);
        }
        WG_WAIT(0);
      } else {
#pragma unroll 1
        for (int ks = 0; ks < 10; ks++) {
          const int it = br * 10 + ks, st = it & 3;
          mbar_wait(bar + 8 * (B_FULL + st), (it >> 2) & 1);
          const uint32_t dst = sb + st * P1_STB;
          const uint64_t da = mkdesc(dst + r * 8192, 16, 1024, 1), db = mkdesc(dst + 16384 + a0 * 8192, 8192, 1024, 1);
          WG_FENCE();
#pragma unroll
          for (int k = 0; k < 4; k++) wg64_ss_of64(acc, da + k * 2, db + k * 128, (ks | k) != 0);
          WG_COMMIT();
          WG_WAIT(1);
          mbar_arrive_if(ks > 0 && wt == 0, bar + 8 * (B_EMPTY + ((it - 1) & 3)));
          duties(it);
        }
        WG_WAIT(0);
      }
      pin(acc);
      TS_MARK(2 + 2 * br);
      mbar_arrive_if(wt == 0, bar + 8 * (B_EMPTY + ((br * 10 + 9) & 3)));
      const uint32_t lrow = (w * 16 + (lane & 15)) * 16 + (lane >> 4) * 1024;
      if (br == 0) {
        uint32_t m0 = 0, m1 = 0;
        const float sk0 = __uint_as_float(mufu0 ? (127u + 70u) << 23 : (127u - 69u) << 23);
        const float sk1 = __uint_as_float(mufu1 ? (127u + 70u) << 23 : (127u - 69u) << 23);
        if (wg >= 2) mbar_wait(bar + 8 * (B_EMPTY + 1), 0);
        const uint32_t stg = wg < 2 ? sb + SM_X + wg * 16384 : sb + P1_STB + (wg - 2) * 16384;
        const int ga = tile_atom(tl) + a0;
        stage_atom_a<0>(acc, ga, stg + lrow, sk0, sk1, m0, m1);
        if (!narrow) stage_atom_a<1>(acc, ga + 1, stg + lrow, sk0, sk1, m0, m1);
        const uint32_t lim0 = (mufu0 ? 127u + 110u : 127u - 29u) << 7, lim1 = (mufu1 ? 127u + 110u : 127u - 29u) << 7;
        const int kb = __any_sync(0xffffffffu, (m0 & 0x7fffu) >= lim0 || ((m0 >> 16) & 0x7fffu) >= lim0 || (m1 & 0x7fffu) >= lim1 || ((m1 >> 16) & 0x7fffu) >= lim1);
        if (lane == 0) g_kbad[bid * 16 + (tid >> 5)] = kb;
        PROXY_FENCE();
        bar_sync(1 + wg, 128);
        if (wg >= 2) bulk_s2g_if(wt < (narrow ? 8 : 16), gdst, stg + lane * 1024, 1024);
      } else {
        mbar_wait(bar + 8 * (B_KVFULL + wg), 0);
        load_frag(q[0], qa + rowoff);
        load_frag(q[1], qa + rowoff + 1024);
        const int4 kb = __ldcg(reinterpret_cast<const int4*>(g_kbad) + tid);
        bad = kb.x | kb.y | kb.z | kb.w;
        mbar_wait(bar + 8 * (B_EMPTY + 2 + ch), 0);
        const uint32_t stg = sb + (2 + ch) * P1_STB + r * 16384;
        uint32_t m0, m1;
        stage_atom<0, 0>(acc, stg + lrow, 0.f, 0.f, m0, m1);
        if (!narrow) stage_atom<0, 1>(acc, stg + lrow, 0.f, 0.f, m0, m1);
        PROXY_FENCE();
        bar_sync(1 + wg, 128);
        bulk_s2g_if(wt < (narrow ? 8 : 16), gdst, stg + lane * 1024, 1024);
      }
      TS_MARK(3 + 2 * br);
    }
  }

  const int onepos = odd ? 0 : 4096 + 8;
  auto patch_v = [&](int b) {
    sts16(sb + b * 12288 + 6144 + onepos + wt * 16, 0x3c00);
    PROXY_FENCE();
    mbar_arrive(bar + 8 * (B_READY + b));
  };
  patch_v(wg);
  if (odd ? t < 2 : t >= 2) {
    if (odd) { q[0][0] = 0; q[0][1] = 0; q[1][0] = 0; q[1][1] = 0; }
    else { q[0][4] = 0; q[0][5] = 0; q[1][4] = 0; q[1][5] = 0; }
  }
  {
    uint32_t m = 0;
#pragma unroll
    for (int i = 0; i < 6; i++) m = maxabs_bf16x2(m, maxabs_bf16x2(q[0][i], q[1][i]));
    bad |= (m & 0x7fffu) >= ((127u - 50u) << 7) || ((m >> 16) & 0x7fffu) >= ((127u - 50u) << 7);
  }
  uint32_t qc[4];
#pragma unroll
  for (int i = 0; i < 4; i++) { qc[i] = t == 0 ? 0x1c801c80u : 0u; asm volatile("" : "+r"(qc[i])); }
  const int lsrc = (lane & ~3) | (odd ? 0 : 2);
  const bool v0 = !odd || t >= 2, v2 = odd || t < 2;
  uint8_t* orow = g_o + rb * ORB + ((h * 5) >> 1) * 2048 + (w * 16 + g) * 16 + t * 4;
  const int kh = bid & 1, cg = (bid >> 1) & 3, atom3 = (cg >> 1) * 5 + (cg & 1) * 2;
  auto p3_load_w = [&](bool p, int j) {
    const uint32_t fb = bar + 8 * (B_P3FULL + (j & 3));
    mbar_expect_if(p, fb, P3_STB);
    tma3d_if(p, sb + (j & 3) * P3_STB + 16384, &maps.wo[j < 5], (kh * 5 + (j < 5 ? j : j - 5)) * 64, atom3, fb);
  };
  auto p3_load_a = [&](bool p, int j) {
    bulk_g2s_if(p, sb + (j & 3) * P3_STB, g_o + rb1 * ORB + ((j < 5 ? 10 + j : j - 5) + kh * 5) * 16384, 16384, bar + 8 * (B_P3FULL + (j & 3)));
  };
  float o[2][12];
#pragma unroll
  for (int i = 0; i < 12; i++) { o[0][i] = 0.f; o[1][i] = 0.f; }
  {
    float s[32];
    uint32_t p[16];
    uint32_t dk0 = (uint32_t)mkdesc(sb, 2048, 0, 0), dk1 = (uint32_t)mkdesc(sb + 4096, SM_CONST - 4096, 0, 0), dv = (uint32_t)mkdesc(sb + 6144, 128, 0, 0);
    const uint64_t dw = mkdesc(sb + SM_WPHI, 384, 128, 0);
    TS_MARK(6);
#pragma unroll 1
    for (int b = 0; b < 16; b++) {
      if (wg == (b & 3) && b < 12) { mbar_wait(bar + 8 * (B_KVFULL + b + 4), 0); patch_v(b + 4); }
      if (b == 2) {
        asm volatile("cp.async.bulk.wait_group 0;" ::: "memory");
        __syncwarp();
        mbar_arrive_if(wt == 0, bar + 8 * B_STG2);
        signal_if(wt == 0, &g_cnt[C_TB]);
      }
      if (b == 3 && wg == 3) {
        mbar_wait(bar + 8 * B_STG2, 0);
        const int bb = 8 + (lane >> 1), kv = lane & 1;
        mbar_expect_if(wt < 16, bar + 8 * (B_KVFULL + bb), 6144);
        bulk_g2s_if(wt < 16, sb + bb * 12288 + kv * 6144, qa + bb * QRB + (1 + kv) * QTY, 6144, bar + 8 * (B_KVFULL + bb));
      }
      if (b == 4 + wg) {
        WG_WAIT(0);
        TS_MARK(7);
        if (wg > 0) mbar_wait(bar + 8 * (B_LINK + wg - 1), 0);
        wait_count(&g_cnt[C_TB], epoch * 512);
        mbar_expect_if(wt == 0, bar + 8 * B_VB, 6144);
        bulk_g2s_if(wt == 0, sb + SM_VB, qa + QBR + rb * QRB + 2 * QTY, 6144, bar + 8 * B_VB);
        uint32_t a[2][6];
        load_frag(a[0], qa + QBR + QTY + rowoff);
        load_frag(a[1], qa + QBR + QTY + rowoff + 1024);
#pragma unroll
        for (int m = 0; m < 2; m++) {
          uint32_t phi[10];
          feature_map(phi, a[m], dw);
#pragma unroll
          for (int i = 0; i < 5; i++) {
            sts32(sb + SM_PHI + i * 2048 + (m * 64 + w * 16 + g) * 16 + t * 4, phi[i]);
            sts32(sb + SM_PHI + i * 2048 + (m * 64 + w * 16 + g + 8) * 16 + t * 4, phi[5 + i]);
          }
        }
        mbar_wait(bar + 8 * B_VB, wg & 1);
        sts16(sb + SM_VB + onepos + wt * 16, 0x3f80);
        PROXY_FENCE();
        bar_sync(1 + wg, 128);
        float kv[12];
        const uint64_t da = mkdesc(sb + SM_PHI, 128, 2048, 0), db = mkdesc(sb + SM_VB, 128, 2048, 0);
        WG_FENCE();
#pragma unroll
        for (int kk = 0; kk < 8; kk++) { if (kk == 0) wg24_ss_bf16_tt_i(kv, da, db); else wg24_ss_bf16_tt(kv, da + kk * 16, db + kk * 16, 1); }
        WG_COMMIT();
        WG_WAIT(0);
        pin(kv);
        mbar_arrive_if(lane == 0 && wg < 3, bar + 8 * (B_LINK + wg));
        float* dst = g_kv + h * 960 + (w * 16 + g) * 24 + 2 * t;
#pragma unroll
        for (int j = 0; j < 3; j++) {
          if (w < 3) asm volatile("red.global.add.v2.f32 [%0], {%1, %2};" ::"l"(dst + 8 * j), "f"(kv[4 * j]), "f"(kv[4 * j + 1]) : "memory");
          if (w < 2) asm volatile("red.global.add.v2.f32 [%0], {%1, %2};" ::"l"(dst + 192 + 8 * j), "f"(kv[4 * j + 2]), "f"(kv[4 * j + 3]) : "memory");
        }
        __syncwarp();
        signal_if(lane == 0, &g_cnt[C_KV + h]);
        TS_MARK(8);
      }
      if (b == 9 + wg) {
        WG_WAIT(0);
        TS_MARK(9);
        uint32_t a[2][6];
        load_frag(a[0], qa + QBR + rowoff);
        load_frag(a[1], qa + QBR + rowoff + 1024);
        if (wg == 0) {
          wait_count(&g_cnt[C_KV + h], epoch * 64);
#pragma unroll
          for (int i = wt; i < 1152; i += 128) {
            const int f = i / 24, d = i % 24;
            const float v = f < 40 ? __ldcg(&g_kv[h * 960 + i]) : 0.f;
            sts16(sb + SM_KVB + (f >> 3) * 384 + d * 16 + (f & 7) * 2, __bfloat16_as_ushort(__float2bfloat16(v)));
          }
          PROXY_FENCE();
          mbar_arrive(bar + 8 * B_KVB);
        }
        const uint64_t dkv = mkdesc(sb + SM_KVB, 384, 128, 0);
#pragma unroll
        for (int m = 0; m < 2; m++) {
          const float g0 = 1.f - __ldcg(&g_gate[rb * 128 + m * 64 + w * 16 + g]), g1 = 1.f - __ldcg(&g_gate[rb * 128 + m * 64 + w * 16 + g + 8]);
          uint32_t phi[10];
          feature_map(phi, a[m], dw);
          if (m == 0) mbar_wait(bar + 8 * B_KVB, 0);
          float nb[12];
          WG_FENCE();
          wg24_rs_bf16_i(nb, phi[0], phi[5], phi[1], phi[6], dkv);
          wg24_rs_bf16(nb, phi[2], phi[7], phi[3], phi[8], dkv + 48, 1);
          wg24_rs_bf16(nb, phi[4], phi[9], 0u, 0u, dkv + 96, 1);
          WG_COMMIT();
          WG_WAIT(0);
          pin(nb);
          const float l0 = __shfl_sync(0xffffffffu, odd ? nb[0] : nb[8], lsrc), l1 = __shfl_sync(0xffffffffu, odd ? nb[2] : nb[10], lsrc);
          store_o(nb, g0 / (l0 + 1e-6f), g1 / (l1 + 1e-6f), orow + 80 * 2048 + m * 1024, v0, v2);
        }
        __syncwarp();
        signal_if(lane == 0, &g_cnt[C_OB + rb * 2 + (h >> 4)]);
        TS_MARK(10);
      }
      if (b == 15 && wg == 2) {
        mbar_wait(bar + 8 * B_P3FREE, 0);
#pragma unroll
        for (int j = 0; j < 4; j++) p3_load_w(wt == 0, j);
        wait_count(&g_cnt[C_OB + rb1 * 2 + kh], epoch * 64);
#pragma unroll
        for (int j = 0; j < 4; j++) p3_load_a(wt == 0, j);
      }
      mbar_wait(bar + 8 * (B_READY + b), 0);
#pragma unroll
      for (int hf = 0; hf < 2; hf++) {
#pragma unroll
        for (int m = 0; m < 2; m++) {
          WG_FENCE();
          wg64_rs_bf16_i(s, q[m][0], q[m][1], q[m][2], q[m][3], desc_lohi(dk0 + hf * 64, 8));
          wg64_rs_bf16(s, q[m][4], q[m][5], qc[2 * m], qc[2 * m + 1], desc_lohi(dk1 + hf * (64u - (64u << 16)), 8), 1);
          WG_COMMIT();
          WG_WAIT(0);
          if (hf == 0 && m == 0) mbar_arrive_if(b == 14 && wt == 0, bar + 8 * B_P3FREE);
          constexpr int A = 2 * NMB, B = 16 - A;
#pragma unroll
          for (int j = 0; j < B; j++) {
            if ((j * A) % B < A) { const int a = j * A / B; p[a] = exp2_pair_mufu(s[2 * a], s[2 * a + 1]); }
            p[A + j] = exp2_pair(s[2 * (A + j)], s[2 * (A + j) + 1]);
          }
          WG_FENCE();
#pragma unroll
          for (int kk = 0; kk < 4; kk++) wg24_rs_f16_t(o[m], p[4 * kk], p[4 * kk + 1], p[4 * kk + 2], p[4 * kk + 3], desc_lohi(dv + hf * 64 + kk * 16, 128), 1);
          WG_COMMIT();
        }
      }
      dk0 += 768; dk1 += 768u - (768u << 16); dv += 768;
    }
    WG_WAIT(0);
    pin(o[0]); pin(o[1]);
  }
  TS_MARK(11);
  {
    int big = 0;
#pragma unroll
    for (int m = 0; m < 2; m++) {
      const float g0 = __ldcg(&g_gate[rb * 128 + m * 64 + w * 16 + g]), g1 = __ldcg(&g_gate[rb * 128 + m * 64 + w * 16 + g + 8]);
      const float l0 = __shfl_sync(0xffffffffu, odd ? o[m][0] : o[m][8], lsrc), l1 = __shfl_sync(0xffffffffu, odd ? o[m][2] : o[m][10], lsrc);
      const float r0 = __fdividef(1.f, l0), r1 = __fdividef(1.f, l1);
      float chk = 0.f, mx = 0.f;
#pragma unroll
      for (int i = 0; i < 12; i++) {
        chk = fmaf(o[m][i], 0.f, chk);
        if (i < 4 ? v0 : (i < 8 || v2)) mx = fmaxf(mx, fabsf(o[m][i]) * ((i & 2) ? r1 : r0));
      }
      bad |= !(chk == 0.f) || !(l0 >= 32.f) || !(l1 >= 32.f);
      big |= mx >= 1.220703125e-4f;
      store_o(o[m], r0 * g0, r1 * g1, orow + m * 1024, v0, v2);
    }
    const int anybad = __syncthreads_or(bad), anybig = __syncthreads_or(big);
    if (anybad || !anybig) attn_exact(x, wqkv, h, qt);
  }
  TS_MARK(12);

  if (wg == 3) {
    signal_if(wt < 4, &g_cnt[C_OA + (qt * 4 + (wt & 3)) * 2 + (h >> 4)]);
    if (wt == 0) atomicAdd(&g_cnt[C_EPOCH], 1);
  } else if (wg == 2) {
    if (w == 0) {
      const bool p = lane == 0;
      mbar_wait(bar + 8 * (B_P3EMPTY + 0), 0);
      p3_load_w(p, 4); p3_load_a(p, 4);
      for (int j = 5; j < 8; j++) { mbar_wait(bar + 8 * (B_P3EMPTY + (j & 3)), 0); p3_load_w(p, j); }
      wait_count(&g_cnt[C_OA + rb1 * 2 + kh], epoch * 16);
      TS_MARK(16);
      for (int j = 5; j < 8; j++) p3_load_a(p, j);
      for (int j = 8; j < 10; j++) { mbar_wait(bar + 8 * (B_P3EMPTY + (j & 3)), 1); p3_load_w(p, j); p3_load_a(p, j); }
    }
  } else {
    float acc[96];
    const bool wide = (cg & 1) == wg;
    const int skip = (!wide && (cg & 1)) ? 1 : 0;
    if (wide) {
#pragma unroll 1
      for (int j = 0; j < 10; j++) {
        mbar_wait(bar + 8 * (B_P3FULL + (j & 3)), (j >> 2) & 1);
        if (j == 5) TS_MARK(13);
        const uint32_t dst = sb + (j & 3) * P3_STB;
        const uint64_t da = mkdesc(dst + wg * 1024, 2048, 128, 0), db = mkdesc(dst + 16384, 8192, 1024, 1);
        WG_FENCE();
#pragma unroll
        for (int k = 0; k < 4; k++) wg192_ss(acc, da + k * 256, db + k * 128, (j | k) != 0);
        WG_COMMIT();
        WG_WAIT(1);
        mbar_arrive_if(j > 0 && wt == 0, bar + 8 * (B_P3EMPTY + ((j - 1) & 3)));
      }
      WG_WAIT(0);
    } else {
#pragma unroll 1
      for (int j = 0; j < 10; j++) {
        mbar_wait(bar + 8 * (B_P3FULL + (j & 3)), (j >> 2) & 1);
        if (j == 5) TS_MARK(13);
        const uint32_t dst = sb + (j & 3) * P3_STB;
        const uint64_t da = mkdesc(dst + wg * 1024, 2048, 128, 0), db = mkdesc(dst + 16384 + skip * 8192, 8192, 1024, 1);
        WG_FENCE();
#pragma unroll
        for (int k = 0; k < 4; k++) wg128_ss_of96(acc, da + k * 256, db + k * 128, (j | k) != 0);
        WG_COMMIT();
        WG_WAIT(1);
        mbar_arrive_if(j > 0 && wt == 0, bar + 8 * (B_P3EMPTY + ((j - 1) & 3)));
      }
      WG_WAIT(0);
    }
    pin(acc);
    TS_MARK(14);
    const uint32_t stg = sb + (wide ? 4 * P3_STB : SM_X);
    const int r = w * 16 + (lane & 15);
#pragma unroll
    for (int i = 0; i < 24; i += 2)
      if (i < 16 || wide) {
        const int ch = (i & 7) + (lane >> 4);
        stsm4(stg + (i >> 3) * 8192 + r * 128 + ((ch ^ (r & 7)) << 4), pack_bf16(acc[4 * i], acc[4 * i + 1]), pack_bf16(acc[4 * i + 2], acc[4 * i + 3]),
              pack_bf16(acc[4 * i + 4], acc[4 * i + 5]), pack_bf16(acc[4 * i + 6], acc[4 * i + 7]));
      }
    PROXY_FENCE();
    bar_sync(1 + wg, 128);
    if (wt < (wide ? 3 : 2)) {
      PROXY_FENCE_G();
      asm volatile("cp.reduce.async.bulk.tensor.2d.global.shared::cta.add.bulk_group [%0, {%2, %3}], [%1];" ::"l"(&maps.out), "r"(stg + wt * 8192),
                   "r"((atom3 + skip + wt) * 64), "r"(rb1 * 128 + wg * 64) : "memory");
      asm volatile("cp.async.bulk.commit_group;" ::: "memory");
      asm volatile("cp.async.bulk.wait_group 0;" ::: "memory");
    }
    TS_MARK(15);
  }
}

typedef CUresult (*EncodeFn)(CUtensorMap*, CUtensorMapDataType, cuuint32_t, void*, const cuuint64_t*, const cuuint64_t*, const cuuint32_t*, const cuuint32_t*,
                             CUtensorMapInterleave, CUtensorMapSwizzle, CUtensorMapL2promotion, CUtensorMapFloatOOBfill);
void encode(EncodeFn enc, CUtensorMap* m, void* p, int rank, const cuuint64_t* gd, const cuuint64_t* gs, const cuuint32_t* bd) {
  const cuuint32_t es[3] = {1, 1, 1};
  enc(m, CU_TENSOR_MAP_DATA_TYPE_BFLOAT16, rank, p, gd, gs, bd, es, CU_TENSOR_MAP_INTERLEAVE_NONE, CU_TENSOR_MAP_SWIZZLE_128B,
      CU_TENSOR_MAP_L2_PROMOTION_L2_128B, CU_TENSOR_MAP_FLOAT_OOB_FILL_NONE);
}

}

extern "C" void kernel_launch(void* const* d_in, const int* in_sizes, int n_in, void* d_out, int out_size) {
  static EncodeFn enc = nullptr;
  if (!enc) {
    cudaDriverEntryPointQueryResult qr;
    cudaGetDriverEntryPoint("cuTensorMapEncodeTiled", (void**)&enc, cudaEnableDefault, &qr);
    cudaFuncSetAttribute(gated_mix_kernel, cudaFuncAttributeMaxDynamicSharedMemorySize, SMEM_BYTES);
  }
  Maps m;
  {
    const cuuint64_t gd[2] = {640, 2048}, gs[1] = {1280};
    const cuuint32_t bx[2] = {64, 128}, bo[2] = {64, 64};
    encode(enc, &m.x, d_in[0], 2, gd, gs, bx);
    encode(enc, &m.out, d_out, 2, gd, gs, bo);
  }
  for (int b = 0; b < 2; b++) {
    const cuuint64_t gd[3] = {64, 640, 30}, gs[2] = {3840, 128}, gd3[3] = {64, 640, 10}, gs3[2] = {1280, 128};
    const cuuint32_t bd[3] = {64, 64, 4}, bd3[3] = {64, 64, 3};
    encode(enc, &m.w[b], d_in[b ? 4 : 1], 3, gd, gs, bd);
    encode(enc, &m.wo[b], d_in[b ? 6 : 2], 3, gd3, gs3, bd3);
  }
  gated_mix_kernel<<<128, 512, SMEM_BYTES, cudaStreamPerThread>>>(m, (const __nv_bfloat16*)d_in[0], (const __nv_bfloat16*)d_in[1], (const __nv_bfloat16*)d_in[5],
                                                                 (const __nv_bfloat16*)d_in[7], (uint4*)d_out);
}
```

```cpp
#include <cuda_runtime.h>
#include <cuda.h>
#include <cuda_bf16.h>
#include <cuda_fp16.h>
#include <stdint.h>
#pragma nv_diag_suppress 550

namespace {

constexpr int QRB = 240 * 2048;
constexpr int QBR = 16 * QRB;
constexpr int QTY = 80 * 2048;
constexpr int ORB = 160 * 2048;
constexpr int NMB = 3;

__device__ __align__(1024) uint8_t g_qkv[2 * QBR];
__device__ __align__(1024) uint8_t g_o[16 * ORB];
__device__ float g_gate[2048];
__device__ __align__(16) float g_kv[32 * 960];
__device__ uint32_t g_kbad;
__device__ uint32_t g_fb[128 * 2048 * 20];
__device__ uint32_t g_cnt[192];
constexpr int C_EPOCH = 0, C_TA = 32, C_TB = 64, C_KV = 96, C_OB = 128, C_OA = 160;

#define TS_MARK(i)

__device__ __forceinline__ uint64_t mkdesc(uint32_t addr, uint32_t lbo, uint32_t sbo, int mode) {
  return (uint64_t)((addr & 0x3FFFF) >> 4) | ((uint64_t)(lbo >> 4) << 16) | ((uint64_t)(sbo >> 4) << 32) | ((uint64_t)mode << 62);
}
__device__ __forceinline__ uint64_t desc_lohi(uint32_t lo, uint32_t hi) { return ((uint64_t)hi << 32) | lo; }
#define WG_FENCE() asm volatile("wgmma.fence.sync.aligned;" ::: "memory")
#define WG_COMMIT() asm volatile("wgmma.commit_group.sync.aligned;" ::: "memory")
#define WG_WAIT(n) asm volatile("wgmma.wait_group.sync.aligned %0;" ::"n"(n) : "memory")
#define PROXY_FENCE() asm volatile("fence.proxy.async.shared::cta;" ::: "memory")
#define PROXY_FENCE_G() asm volatile("fence.proxy.async.global;" ::: "memory")
__device__ __forceinline__ void bar_sync(int id, int n) { asm volatile("bar.sync %0, %1;" ::"r"(id), "r"(n) : "memory"); }
__device__ __forceinline__ void mbar_init(uint32_t a, int c) { asm volatile("mbarrier.init.shared::cta.b64 [%0], %1;" ::"r"(a), "r"(c)); }
__device__ __forceinline__ uint32_t mbar_try(uint32_t a, int par) {
  uint32_t ok;
  asm volatile("{.reg .pred p; mbarrier.try_wait.parity.shared::cta.b64 p, [%1], %2; selp.b32 %0, 1, 0, p;}" : "=r"(ok) : "r"(a), "r"(par) : "memory");
  return ok;
}
__device__ __forceinline__ void mbar_wait(uint32_t a, int par) {
  for (int i = 0; !mbar_try(a, par); i++)
    if (i > (1 << 22)) break;
}
__device__ __forceinline__ void mbar_arrive(uint32_t a) { asm volatile("mbarrier.arrive.shared::cta.b64 _, [%0];" ::"r"(a) : "memory"); }
__device__ __forceinline__ void mbar_arrive_if(bool p, uint32_t a) {
  asm volatile("{.reg .pred p; setp.ne.b32 p, %0, 0; @p mbarrier.arrive.shared::cta.b64 _, [%1];}" ::"r"((int)p), "r"(a) : "memory");
}
__device__ __forceinline__ void mbar_expect_if(bool p, uint32_t a, int bytes) {
  asm volatile("{.reg .pred p; setp.ne.b32 p, %0, 0; @p mbarrier.arrive.expect_tx.shared::cta.b64 _, [%1], %2;}" ::"r"((int)p), "r"(a), "r"(bytes) : "memory");
}
__device__ __forceinline__ void tma2d_if(bool p, uint32_t dst, const CUtensorMap* m, int c0, int c1, uint32_t bar) {
  asm volatile("{.reg .pred p; setp.ne.b32 p, %0, 0; @p cp.async.bulk.tensor.2d.shared::cluster.global.mbarrier::complete_tx::bytes [%1], [%2, {%4, %5}], [%3];}"
               ::"r"((int)p), "r"(dst), "l"(m), "r"(bar), "r"(c0), "r"(c1) : "memory");
}
__device__ __forceinline__ void tma3d_if(bool p, uint32_t dst, const CUtensorMap* m, int c1, int c2, uint32_t bar) {
  asm volatile("{.reg .pred p; setp.ne.b32 p, %0, 0; @p cp.async.bulk.tensor.3d.shared::cluster.global.mbarrier::complete_tx::bytes [%1], [%2, {%6, %4, %5}], [%3];}"
               ::"r"((int)p), "r"(dst), "l"(m), "r"(bar), "r"(c1), "r"(c2), "r"(0) : "memory");
}
__device__ __forceinline__ void bulk_g2s_if(bool p, uint32_t dst, const void* src, int bytes, uint32_t bar) {
  asm volatile("{.reg .pred p; setp.ne.b32 p, %0, 0; @p cp.async.bulk.shared::cluster.global.mbarrier::complete_tx::bytes [%1], [%2], %3, [%4];}"
               ::"r"((int)p), "r"(dst), "l"(src), "r"(bytes), "r"(bar) : "memory");
}
__device__ __forceinline__ void tma5d_if(bool p, uint32_t dst, const CUtensorMap* m, int c1, int c2, int c4, uint32_t bar) {
  asm volatile("{.reg .pred p; setp.ne.b32 p, %0, 0; @p cp.async.bulk.tensor.5d.shared::cluster.global.mbarrier::complete_tx::bytes [%1], [%2, {%7, %4, %5, %7, %6}], [%3];}"
               ::"r"((int)p), "r"(dst), "l"(m), "r"(bar), "r"(c1), "r"(c2), "r"(c4), "r"(0) : "memory");
}
__device__ __forceinline__ void tma5d_store_if(bool p, const CUtensorMap* m, uint32_t src, int c1, int c2, int c3, int c4) {
  asm volatile("{.reg .pred p; setp.ne.b32 p, %0, 0; @p cp.async.bulk.tensor.5d.global.shared::cta.bulk_group [%1, {%7, %3, %4, %5, %6}], [%2];}"
               ::"r"((int)p), "l"(m), "r"(src), "r"(c1), "r"(c2), "r"(c3), "r"(c4), "r"(0) : "memory");
}
__device__ __forceinline__ void bulk_s2g_if(bool p, void* dst, uint32_t src, int bytes) {
  asm volatile("{.reg .pred p; setp.ne.b32 p, %0, 0; @p cp.async.bulk.global.shared::cta.bulk_group [%1], [%2], %3;}" ::"r"((int)p), "l"(dst), "r"(src), "r"(bytes) : "memory");
}
__device__ __forceinline__ void bulk_or_if(bool p, void* dst, uint32_t src, int bytes) {
  asm volatile("{.reg .pred p; setp.ne.b32 p, %0, 0; @p cp.reduce.async.bulk.global.shared::cta.bulk_group.or.b32 [%1], [%2], %3;}" ::"r"((int)p), "l"(dst), "r"(src), "r"(bytes) : "memory");
}
__device__ __forceinline__ void bulk_addf_if(bool p, void* dst, uint32_t src, int bytes) {
  asm volatile("{.reg .pred p; setp.ne.b32 p, %0, 0; @p cp.reduce.async.bulk.global.shared::cta.bulk_group.add.f32 [%1], [%2], %3;}" ::"r"((int)p), "l"(dst), "r"(src), "r"(bytes) : "memory");
}
#define BULK_COMMIT() asm volatile("cp.async.bulk.commit_group;" ::: "memory")
#define BULK_WAIT() asm volatile("cp.async.bulk.wait_group 0;" ::: "memory")
#define BULK_WAIT_READ() asm volatile("cp.async.bulk.wait_group.read 0;" ::: "memory")
__device__ __forceinline__ void signal_if(bool p, uint32_t* c) {
  asm volatile("{.reg .pred p; setp.ne.b32 p, %0, 0; @p fence.proxy.async.global; @p fence.acq_rel.gpu; @p red.relaxed.gpu.global.add.u32 [%1], 1;}" ::"r"((int)p), "l"(c) : "memory");
}
__device__ __forceinline__ void wait_count(const uint32_t* c, uint32_t target) {
  for (int i = 0;; i++) {
    uint32_t v;
    asm volatile("ld.acquire.gpu.global.u32 %0, [%1];" : "=r"(v) : "l"(c) : "memory");
    if ((int)(v - target) >= 0) break;
    if (i > (1 << 20)) break;
  }
  PROXY_FENCE_G();
}
__device__ __forceinline__ uint32_t pack_bf16(float lo, float hi) { uint32_t r; asm("cvt.rn.bf16x2.f32 %0, %1, %2;" : "=r"(r) : "f"(hi), "f"(lo)); return r; }
__device__ __forceinline__ uint32_t pack_f16(float lo, float hi) { uint32_t r; asm("cvt.rn.f16x2.f32 %0, %1, %2;" : "=r"(r) : "f"(hi), "f"(lo)); return r; }
__device__ __forceinline__ float ex2(float a) { float r; asm("ex2.approx.ftz.f32 %0, %1;" : "=f"(r) : "f"(a)); return r; }
__device__ __forceinline__ float rcp(float a) { float r; asm("rcp.approx.ftz.f32 %0, %1;" : "=f"(r) : "f"(a)); return r; }
__device__ __forceinline__ uint32_t maxabs_bf16x2(uint32_t a, uint32_t b) { uint32_t r; asm("max.NaN.xorsign.abs.bf16x2 %0, %1, %2;" : "=r"(r) : "r"(a), "r"(b)); return r; }
__device__ __forceinline__ uint32_t ldg32(const void* p) { return __ldg(reinterpret_cast<const uint32_t*>(p)); }
__device__ __forceinline__ uint32_t ldcg32(const void* p) { uint32_t v; asm volatile("ld.global.cg.u32 %0, [%1];" : "=r"(v) : "l"(p) : "memory"); return v; }
__device__ __forceinline__ void sts32(uint32_t a, uint32_t v) { asm volatile("st.shared.b32 [%0], %1;" ::"r"(a), "r"(v) : "memory"); }
__device__ __forceinline__ void sts16(uint32_t a, uint16_t v) { asm volatile("st.shared.b16 [%0], %1;" ::"r"(a), "h"(v) : "memory"); }
__device__ __forceinline__ void stsm4(uint32_t a, uint32_t r0, uint32_t r1, uint32_t r2, uint32_t r3) {
  asm volatile("stmatrix.sync.aligned.m8n8.x4.shared.b16 [%0], {%1, %2, %3, %4};" ::"r"(a), "r"(r0), "r"(r1), "r"(r2), "r"(r3) : "memory");
}
template <int N> __device__ __forceinline__ void pin(float (&d)[N]) {
#pragma unroll
  for (int i = 0; i < N; i++) asm volatile("" : "+f"(d[i])::"memory");
}

__device__ __forceinline__ void wg128_ss(float (&d)[64], uint64_t da, uint64_t db, int scale_d) {
  asm volatile("{\n.reg .pred p;\nsetp.ne.b32 p, %66, 0;\n"
    "wgmma.mma_async.sync.aligned.m64n128k16.f32.bf16.bf16 "
    "{%0, %1, %2, %3, %4, %5, %6, %7, %8, %9, %10, %11, %12, %13, %14, %15,"
    "%16, %17, %18, %19, %20, %21, %22, %23, %24, %25, %26, %27, %28, %29, %30, %31,"
    "%32, %33, %34, %35, %36, %37, %38, %39, %40, %41, %42, %43, %44, %45, %46, %47,"
    "%48, %49, %50, %51, %52, %53, %54, %55, %56, %57, %58, %59, %60, %61, %62, %63}, "
    "%64, %65, p, 1, 1, 0, 1;\n}\n"
    : "+f"(d[0]), "+f"(d[1]), "+f"(d[2]), "+f"(d[3]), "+f"(d[4]), "+f"(d[5]), "+f"(d[6]), "+f"(d[7]),
      "+f"(d[8]), "+f"(d[9]), "+f"(d[10]), "+f"(d[11]), "+f"(d[12]), "+f"(d[13]), "+f"(d[14]), "+f"(d[15]),
      "+f"(d[16]), "+f"(d[17]), "+f"(d[18]), "+f"(d[19]), "+f"(d[20]), "+f"(d[21]), "+f"(d[22]), "+f"(d[23]),
      "+f"(d[24]), "+f"(d[25]), "+f"(d[26]), "+f"(d[27]), "+f"(d[28]), "+f"(d[29]), "+f"(d[30]), "+f"(d[31]),
      "+f"(d[32]), "+f"(d[33]), "+f"(d[34]), "+f"(d[35]), "+f"(d[36]), "+f"(d[37]), "+f"(d[38]), "+f"(d[39]),
      "+f"(d[40]), "+f"(d[41]), "+f"(d[42]), "+f"(d[43]), "+f"(d[44]), "+f"(d[45]), "+f"(d[46]), "+f"(d[47]),
      "+f"(d[48]), "+f"(d[49]), "+f"(d[50]), "+f"(d[51]), "+f"(d[52]), "+f"(d[53]), "+f"(d[54]), "+f"(d[55]),
      "+f"(d[56]), "+f"(d[57]), "+f"(d[58]), "+f"(d[59]), "+f"(d[60]), "+f"(d[61]), "+f"(d[62]), "+f"(d[63])
    : "l"(da), "l"(db), "r"(scale_d));
}

__device__ __forceinline__ void wg64_ss_of64(float (&d)[64], uint64_t da, uint64_t db, int scale_d) {
  asm volatile("{\n.reg .pred p;\nsetp.ne.b32 p, %34, 0;\n"
    "wgmma.mma_async.sync.aligned.m64n64k16.f32.bf16.bf16 "
    "{%0, %1, %2, %3, %4, %5, %6, %7, %8, %9, %10, %11, %12, %13, %14, %15,"
    "%16, %17, %18, %19, %20, %21, %22, %23, %24, %25, %26, %27, %28, %29, %30, %31}, "
    "%32, %33, p, 1, 1, 0, 1;\n}\n"
    : "+f"(d[0]), "+f"(d[1]), "+f"(d[2]), "+f"(d[3]), "+f"(d[4]), "+f"(d[5]), "+f"(d[6]), "+f"(d[7]),
      "+f"(d[8]), "+f"(d[9]), "+f"(d[10]), "+f"(d[11]), "+f"(d[12]), "+f"(d[13]), "+f"(d[14]), "+f"(d[15]),
      "+f"(d[16]), "+f"(d[17]), "+f"(d[18]), "+f"(d[19]), "+f"(d[20]), "+f"(d[21]), "+f"(d[22]), "+f"(d[23]),
      "+f"(d[24]), "+f"(d[25]), "+f"(d[26]), "+f"(d[27]), "+f"(d[28]), "+f"(d[29]), "+f"(d[30]), "+f"(d[31])
    : "l"(da), "l"(db), "r"(scale_d));
}

__device__ __forceinline__ void wg192_ss(float (&d)[96], uint64_t da, uint64_t db, int scale_d) {
  asm volatile("{\n.reg .pred p;\nsetp.ne.b32 p, %98, 0;\n"
    "wgmma.mma_async.sync.aligned.m64n192k16.f32.bf16.bf16 "
    "{%0, %1, %2, %3, %4, %5, %6, %7, %8, %9, %10, %11, %12, %13, %14, %15,"
    "%16, %17, %18, %19, %20, %21, %22, %23, %24, %25, %26, %27, %28, %29, %30, %31,"
    "%32, %33, %34, %35, %36, %37, %38, %39, %40, %41, %42, %43, %44, %45, %46, %47,"
    "%48, %49, %50, %51, %52, %53, %54, %55, %56, %57, %58, %59, %60, %61, %62, %63,"
    "%64, %65, %66, %67, %68, %69, %70, %71, %72, %73, %74, %75, %76, %77, %78, %79,"
    "%80, %81, %82, %83, %84, %85, %86, %87, %88, %89, %90, %91, %92, %93, %94, %95}, "
    "%96, %97, p, 1, 1, 0, 1;\n}\n"
    : "+f"(d[0]), "+f"(d[1]), "+f"(d[2]), "+f"(d[3]), "+f"(d[4]), "+f"(d[5]), "+f"(d[6]), "+f"(d[7]),
      "+f"(d[8]), "+f"(d[9]), "+f"(d[10]), "+f"(d[11]), "+f"(d[12]), "+f"(d[13]), "+f"(d[14]), "+f"(d[15]),
      "+f"(d[16]), "+f"(d[17]), "+f"(d[18]), "+f"(d[19]), "+f"(d[20]), "+f"(d[21]), "+f"(d[22]), "+f"(d[23]),
      "+f"(d[24]), "+f"(d[25]), "+f"(d[26]), "+f"(d[27]), "+f"(d[28]), "+f"(d[29]), "+f"(d[30]), "+f"(d[31]),
      "+f"(d[32]), "+f"(d[33]), "+f"(d[34]), "+f"(d[35]), "+f"(d[36]), "+f"(d[37]), "+f"(d[38]), "+f"(d[39]),
      "+f"(d[40]), "+f"(d[41]), "+f"(d[42]), "+f"(d[43]), "+f"(d[44]), "+f"(d[45]), "+f"(d[46]), "+f"(d[47]),
      "+f"(d[48]), "+f"(d[49]), "+f"(d[50]), "+f"(d[51]), "+f"(d[52]), "+f"(d[53]), "+f"(d[54]), "+f"(d[55]),
      "+f"(d[56]), "+f"(d[57]), "+f"(d[58]), "+f"(d[59]), "+f"(d[60]), "+f"(d[61]), "+f"(d[62]), "+f"(d[63]),
      "+f"(d[64]), "+f"(d[65]), "+f"(d[66]), "+f"(d[67]), "+f"(d[68]), "+f"(d[69]), "+f"(d[70]), "+f"(d[71]),
      "+f"(d[72]), "+f"(d[73]), "+f"(d[74]), "+f"(d[75]), "+f"(d[76]), "+f"(d[77]), "+f"(d[78]), "+f"(d[79]),
      "+f"(d[80]), "+f"(d[81]), "+f"(d[82]), "+f"(d[83]), "+f"(d[84]), "+f"(d[85]), "+f"(d[86]), "+f"(d[87]),
      "+f"(d[88]), "+f"(d[89]), "+f"(d[90]), "+f"(d[91]), "+f"(d[92]), "+f"(d[93]), "+f"(d[94]), "+f"(d[95])
    : "l"(da), "l"(db), "r"(scale_d));
}

__device__ __forceinline__ void wg128_ss_of96(float (&d)[96], uint64_t da, uint64_t db, int scale_d) {
  asm volatile("{\n.reg .pred p;\nsetp.ne.b32 p, %66, 0;\n"
    "wgmma.mma_async.sync.aligned.m64n128k16.f32.bf16.bf16 "
    "{%0, %1, %2, %3, %4, %5, %6, %7, %8, %9, %10, %11, %12, %13, %14, %15,"
    "%16, %17, %18, %19, %20, %21, %22, %23, %24, %25, %26, %27, %28, %29, %30, %31,"
    "%32, %33, %34, %35, %36, %37, %38, %39, %40, %41, %42, %43, %44, %45, %46, %47,"
    "%48, %49, %50, %51, %52, %53, %54, %55, %56, %57, %58, %59, %60, %61, %62, %63}, "
    "%64, %65, p, 1, 1, 0, 1;\n}\n"
    : "+f"(d[0]), "+f"(d[1]), "+f"(d[2]), "+f"(d[3]), "+f"(d[4]), "+f"(d[5]), "+f"(d[6]), "+f"(d[7]),
      "+f"(d[8]), "+f"(d[9]), "+f"(d[10]), "+f"(d[11]), "+f"(d[12]), "+f"(d[13]), "+f"(d[14]), "+f"(d[15]),
      "+f"(d[16]), "+f"(d[17]), "+f"(d[18]), "+f"(d[19]), "+f"(d[20]), "+f"(d[21]), "+f"(d[22]), "+f"(d[23]),
      "+f"(d[24]), "+f"(d[25]), "+f"(d[26]), "+f"(d[27]), "+f"(d[28]), "+f"(d[29]), "+f"(d[30]), "+f"(d[31]),
      "+f"(d[32]), "+f"(d[33]), "+f"(d[34]), "+f"(d[35]), "+f"(d[36]), "+f"(d[37]), "+f"(d[38]), "+f"(d[39]),
      "+f"(d[40]), "+f"(d[41]), "+f"(d[42]), "+f"(d[43]), "+f"(d[44]), "+f"(d[45]), "+f"(d[46]), "+f"(d[47]),
      "+f"(d[48]), "+f"(d[49]), "+f"(d[50]), "+f"(d[51]), "+f"(d[52]), "+f"(d[53]), "+f"(d[54]), "+f"(d[55]),
      "+f"(d[56]), "+f"(d[57]), "+f"(d[58]), "+f"(d[59]), "+f"(d[60]), "+f"(d[61]), "+f"(d[62]), "+f"(d[63])
    : "l"(da), "l"(db), "r"(scale_d));
}

__device__ __forceinline__ void wg64_rs_bf16(float (&d)[32], uint32_t a0, uint32_t a1, uint32_t a2, uint32_t a3, uint64_t db, int scale_d) {
  asm volatile("{\n.reg .pred p;\nsetp.ne.b32 p, %37, 0;\n"
    "wgmma.mma_async.sync.aligned.m64n64k16.f32.bf16.bf16 "
    "{%0, %1, %2, %3, %4, %5, %6, %7, %8, %9, %10, %11, %12, %13, %14, %15,"
    "%16, %17, %18, %19, %20, %21, %22, %23, %24, %25, %26, %27, %28, %29, %30, %31}, "
    "{%32, %33, %34, %35}, %36, p, 1, 1, 0;\n}\n"
    : "+f"(d[0]), "+f"(d[1]), "+f"(d[2]), "+f"(d[3]), "+f"(d[4]), "+f"(d[5]), "+f"(d[6]), "+f"(d[7]),
      "+f"(d[8]), "+f"(d[9]), "+f"(d[10]), "+f"(d[11]), "+f"(d[12]), "+f"(d[13]), "+f"(d[14]), "+f"(d[15]),
      "+f"(d[16]), "+f"(d[17]), "+f"(d[18]), "+f"(d[19]), "+f"(d[20]), "+f"(d[21]), "+f"(d[22]), "+f"(d[23]),
      "+f"(d[24]), "+f"(d[25]), "+f"(d[26]), "+f"(d[27]), "+f"(d[28]), "+f"(d[29]), "+f"(d[30]), "+f"(d[31])
    : "r"(a0), "r"(a1), "r"(a2), "r"(a3), "l"(db), "r"(scale_d));
}

__device__ __forceinline__ void wg24_rs_f16_t(float (&d)[12], uint32_t a0, uint32_t a1, uint32_t a2, uint32_t a3, uint64_t db, int scale_d) {
  asm volatile("{\n.reg .pred p;\nsetp.ne.b32 p, %17, 0;\n"
    "wgmma.mma_async.sync.aligned.m64n24k16.f32.f16.f16 "
    "{%0, %1, %2, %3, %4, %5, %6, %7, %8, %9, %10, %11}, "
    "{%12, %13, %14, %15}, %16, p, 1, 1, 1;\n}\n"
    : "+f"(d[0]), "+f"(d[1]), "+f"(d[2]), "+f"(d[3]), "+f"(d[4]), "+f"(d[5]), "+f"(d[6]), "+f"(d[7]),
      "+f"(d[8]), "+f"(d[9]), "+f"(d[10]), "+f"(d[11])
    : "r"(a0), "r"(a1), "r"(a2), "r"(a3), "l"(db), "r"(scale_d));
}

__device__ __forceinline__ void wg24_rs_bf16(float (&d)[12], uint32_t a0, uint32_t a1, uint32_t a2, uint32_t a3, uint64_t db, int scale_d) {
  asm volatile("{\n.reg .pred p;\nsetp.ne.b32 p, %17, 0;\n"
    "wgmma.mma_async.sync.aligned.m64n24k16.f32.bf16.bf16 "
    "{%0, %1, %2, %3, %4, %5, %6, %7, %8, %9, %10, %11}, "
    "{%12, %13, %14, %15}, %16, p, 1, 1, 0;\n}\n"
    : "+f"(d[0]), "+f"(d[1]), "+f"(d[2]), "+f"(d[3]), "+f"(d[4]), "+f"(d[5]), "+f"(d[6]), "+f"(d[7]),
      "+f"(d[8]), "+f"(d[9]), "+f"(d[10]), "+f"(d[11])
    : "r"(a0), "r"(a1), "r"(a2), "r"(a3), "l"(db), "r"(scale_d));
}

__device__ __forceinline__ void wg24_ss_bf16_tt(float (&d)[12], uint64_t da, uint64_t db, int scale_d) {
  asm volatile("{\n.reg .pred p;\nsetp.ne.b32 p, %14, 0;\n"
    "wgmma.mma_async.sync.aligned.m64n24k16.f32.bf16.bf16 "
    "{%0, %1, %2, %3, %4, %5, %6, %7, %8, %9, %10, %11}, "
    "%12, %13, p, 1, 1, 1, 1;\n}\n"
    : "+f"(d[0]), "+f"(d[1]), "+f"(d[2]), "+f"(d[3]), "+f"(d[4]), "+f"(d[5]), "+f"(d[6]), "+f"(d[7]),
      "+f"(d[8]), "+f"(d[9]), "+f"(d[10]), "+f"(d[11])
    : "l"(da), "l"(db), "r"(scale_d));
}

__device__ __forceinline__ void wg64_rs_bf16_i(float (&d)[32], uint32_t a0, uint32_t a1, uint32_t a2, uint32_t a3, uint64_t db) {
  asm volatile("{\n.reg .pred p;\nsetp.ne.b32 p, 0, 0;\n"
    "wgmma.mma_async.sync.aligned.m64n64k16.f32.bf16.bf16 "
    "{%0, %1, %2, %3, %4, %5, %6, %7, %8, %9, %10, %11, %12, %13, %14, %15,"
    "%16, %17, %18, %19, %20, %21, %22, %23, %24, %25, %26, %27, %28, %29, %30, %31}, "
    "{%32, %33, %34, %35}, %36, p, 1, 1, 0;\n}\n"
    : "=f"(d[0]), "=f"(d[1]), "=f"(d[2]), "=f"(d[3]), "=f"(d[4]), "=f"(d[5]), "=f"(d[6]), "=f"(d[7]),
      "=f"(d[8]), "=f"(d[9]), "=f"(d[10]), "=f"(d[11]), "=f"(d[12]), "=f"(d[13]), "=f"(d[14]), "=f"(d[15]),
      "=f"(d[16]), "=f"(d[17]), "=f"(d[18]), "=f"(d[19]), "=f"(d[20]), "=f"(d[21]), "=f"(d[22]), "=f"(d[23]),
      "=f"(d[24]), "=f"(d[25]), "=f"(d[26]), "=f"(d[27]), "=f"(d[28]), "=f"(d[29]), "=f"(d[30]), "=f"(d[31])
    : "r"(a0), "r"(a1), "r"(a2), "r"(a3), "l"(db));
}

__device__ __forceinline__ void wg24_rs_bf16_i(float (&d)[12], uint32_t a0, uint32_t a1, uint32_t a2, uint32_t a3, uint64_t db) {
  asm volatile("{\n.reg .pred p;\nsetp.ne.b32 p, 0, 0;\n"
    "wgmma.mma_async.sync.aligned.m64n24k16.f32.bf16.bf16 "
    "{%0, %1, %2, %3, %4, %5, %6, %7, %8, %9, %10, %11}, "
    "{%12, %13, %14, %15}, %16, p, 1, 1, 0;\n}\n"
    : "=f"(d[0]), "=f"(d[1]), "=f"(d[2]), "=f"(d[3]), "=f"(d[4]), "=f"(d[5]), "=f"(d[6]), "=f"(d[7]),
      "=f"(d[8]), "=f"(d[9]), "=f"(d[10]), "=f"(d[11])
    : "r"(a0), "r"(a1), "r"(a2), "r"(a3), "l"(db));
}

__device__ __forceinline__ void wg24_ss_bf16_tt_i(float (&d)[12], uint64_t da, uint64_t db) {
  asm volatile("{\n.reg .pred p;\nsetp.ne.b32 p, 0, 0;\n"
    "wgmma.mma_async.sync.aligned.m64n24k16.f32.bf16.bf16 "
    "{%0, %1, %2, %3, %4, %5, %6, %7, %8, %9, %10, %11}, "
    "%12, %13, p, 1, 1, 1, 1;\n}\n"
    : "=f"(d[0]), "=f"(d[1]), "=f"(d[2]), "=f"(d[3]), "=f"(d[4]), "=f"(d[5]), "=f"(d[6]), "=f"(d[7]),
      "=f"(d[8]), "=f"(d[9]), "=f"(d[10]), "=f"(d[11])
    : "l"(da), "l"(db));
}

__device__ __forceinline__ void wg24_ss_bf16(float (&d)[12], uint64_t da, uint64_t db, int scale_d) {
  asm volatile("{\n.reg .pred p;\nsetp.ne.b32 p, %14, 0;\n"
    "wgmma.mma_async.sync.aligned.m64n24k16.f32.bf16.bf16 "
    "{%0, %1, %2, %3, %4, %5, %6, %7, %8, %9, %10, %11}, "
    "%12, %13, p, 1, 1, 0, 0;\n}\n"
    : "+f"(d[0]), "+f"(d[1]), "+f"(d[2]), "+f"(d[3]), "+f"(d[4]), "+f"(d[5]), "+f"(d[6]), "+f"(d[7]),
      "+f"(d[8]), "+f"(d[9]), "+f"(d[10]), "+f"(d[11])
    : "l"(da), "l"(db), "r"(scale_d));
}

__device__ __forceinline__ void wg24_ss_bf16_i(float (&d)[12], uint64_t da, uint64_t db) {
  asm volatile("{\n.reg .pred p;\nsetp.ne.b32 p, 0, 0;\n"
    "wgmma.mma_async.sync.aligned.m64n24k16.f32.bf16.bf16 "
    "{%0, %1, %2, %3, %4, %5, %6, %7, %8, %9, %10, %11}, "
    "%12, %13, p, 1, 1, 0, 0;\n}\n"
    : "=f"(d[0]), "=f"(d[1]), "=f"(d[2]), "=f"(d[3]), "=f"(d[4]), "=f"(d[5]), "=f"(d[6]), "=f"(d[7]),
      "=f"(d[8]), "=f"(d[9]), "=f"(d[10]), "=f"(d[11])
    : "l"(da), "l"(db));
}

constexpr int P1_STB = 49152, P3_STB = 40960;
constexpr int SM_X = 196608;
constexpr int SM_KVB = SM_X + 24576;
constexpr int SM_CONST = SM_X + 32768, SM_WPHI = SM_CONST + 1024, SM_BAR = SM_WPHI + 1536;
constexpr int SMEM_BYTES = SM_BAR + 512;
constexpr int B_FULL = 0, B_EMPTY = 4, B_STG = 8, B_STG2 = 9, B_KB = 10, B_QB = 11, B_LINK = 12, B_KVB = 14, B_FREE = 15, B_KVFULL = 18, B_READY = 22, B_P3FULL = 26, B_P3EMPTY = 30;

struct Maps { CUtensorMap x, w[2], wo[2], out, qld, qst; };

__device__ __forceinline__ int tile_atom(int t) { return (t >> 2) * 15 + ((0xB740 >> ((t & 3) * 4)) & 15); }

template <int MODE, int A>
__device__ __forceinline__ void stage_atom(const float (&acc)[64], uint32_t sa, float s0, float s1, uint32_t& m0, uint32_t& m1) {
#pragma unroll
  for (int jj = 0; jj < 8; jj += 2) {
    uint32_t r[4];
#pragma unroll
    for (int e = 0; e < 4; e++) {
      const int i = (A * 8 + jj) * 4 + 2 * e;
      const float s = (e & 1) ? s1 : s0;
      if (MODE == 0) r[e] = pack_bf16(acc[i], acc[i + 1]);
      else if (MODE == 3) r[e] = pack_f16(acc[i], acc[i + 1]);
      else r[e] = pack_bf16(acc[i] * s, acc[i + 1] * s);
    }
    if (MODE == 2) { m0 = maxabs_bf16x2(m0, maxabs_bf16x2(r[0], r[2])); m1 = maxabs_bf16x2(m1, maxabs_bf16x2(r[1], r[3])); }
    stsm4(sa + (A * 8 + jj) * 1024, r[0], r[1], r[2], r[3]);
  }
}
template <int A>
__device__ __forceinline__ void stage_atom_a(const float (&acc)[64], int ga, uint32_t sa, float sk0, float sk1, uint32_t& m0, uint32_t& m1) {
  if (ga < 10) { const float cq = __uint_as_float(463809372u); stage_atom<1, A>(acc, sa, cq, cq, m0, m1); }
  else if (ga < 20) stage_atom<2, A>(acc, sa, sk0, sk1, m0, m1);
  else stage_atom<3, A>(acc, sa, 0.f, 0.f, m0, m1);
}

__device__ __forceinline__ uint32_t exp2_pair(float a, float b) {
  uint32_t z, w, h;
  asm volatile("cvt.pack.sat.s16.s32 %0, %2, %1;" : "=r"(z) : "r"(__float_as_uint(a)), "r"(__float_as_uint(b)));
  asm volatile("lop3.b32 %0, %1, 0x03ff03ff, 0x34003400, 0xEA;" : "=r"(w) : "r"(z));
  asm volatile("fma.rn.f16x2 %0, %1, %1, %2;" : "=r"(h) : "r"(w), "r"(0x36203620));
  asm volatile("fma.rn.f16x2 %0, %0, %1, %2;" : "+r"(h) : "r"(w), "r"(0x2e012e01));
  return h + z - w;
}
__device__ __forceinline__ uint32_t exp2_pair_mufu(float a, float b) {
  float x, y; uint32_t r;
  asm volatile("ex2.approx.ftz.f32 %0, %1;" : "=f"(x) : "f"(a));
  asm volatile("ex2.approx.ftz.f32 %0, %1;" : "=f"(y) : "f"(b));
  asm volatile("cvt.rn.f16x2.f32 %0, %1, %2;" : "=r"(r) : "f"(y), "f"(x));
  return r;
}
__device__ __forceinline__ void load_frag(uint32_t (&a)[6], const uint8_t* p) {
  a[0] = ldcg32(p); a[1] = ldcg32(p + 128); a[2] = ldcg32(p + 2048); a[3] = ldcg32(p + 2048 + 128); a[4] = ldcg32(p + 4096); a[5] = ldcg32(p + 4096 + 128);
}
__device__ __forceinline__ void feature_map(uint32_t (&phi)[10], const float (&p)[12]) {
  const float L = 1.4426950408889634f;
#pragma unroll
  for (int r = 0; r < 2; r++) {
    const float v[5] = {p[2 * r], p[2 * r + 1], p[4 + 2 * r], p[5 + 2 * r], p[8 + 2 * r]};
    float mx = fmaxf(fmaxf(fmaxf(v[0], v[1]), fmaxf(v[2], v[3])), v[4]);
    float mn = fminf(fminf(fminf(v[0], v[1]), fminf(v[2], v[3])), v[4]);
    mx = fmaxf(mx, __shfl_xor_sync(0xffffffffu, mx, 1)); mn = fminf(mn, __shfl_xor_sync(0xffffffffu, mn, 1));
    mx = fmaxf(mx, __shfl_xor_sync(0xffffffffu, mx, 2)); mn = fminf(mn, __shfl_xor_sync(0xffffffffu, mn, 2));
    const float mxl = -mx * L, mnl = mn * L;
    float ep[5], en[5];
#pragma unroll
    for (int i = 0; i < 5; i++) { ep[i] = ex2(fmaf(v[i], L, mxl)); en[i] = ex2(fmaf(v[i], -L, mnl)); }
    float sp = (ep[0] + ep[1]) + (ep[2] + ep[3]) + ep[4], sn = (en[0] + en[1]) + (en[2] + en[3]) + en[4];
    sp += __shfl_xor_sync(0xffffffffu, sp, 1); sn += __shfl_xor_sync(0xffffffffu, sn, 1);
    sp += __shfl_xor_sync(0xffffffffu, sp, 2); sn += __shfl_xor_sync(0xffffffffu, sn, 2);
    const float rp = rcp(sp), rn = rcp(sn);
#pragma unroll
    for (int i = 0; i < 5; i++) phi[5 * r + i] = pack_bf16(ep[i] * rp, en[i] * rn);
  }
}
__device__ __forceinline__ void phi_proj(float (&p0)[12], float (&p1)[12], uint32_t a, uint64_t dw) {
  const uint64_t da = mkdesc(a, 1024, 128, 0), db = mkdesc(a + 2048, 0, 128, 0);
  WG_FENCE();
  wg24_ss_bf16_i(p0, da, dw);
  wg24_ss_bf16(p0, db, dw + 48, 1);
  wg24_ss_bf16_i(p1, da + 384, dw);
  wg24_ss_bf16(p1, db + 384, dw + 48, 1);
  WG_COMMIT();
  WG_WAIT(0);
  pin(p0); pin(p1);
}
__device__ __forceinline__ void stage_o(const float (&o)[12], float s0, float s1, uint32_t a, bool v0, bool v2) {
#pragma unroll
  for (int j = 0; j < 3; j++) {
    const bool v = j == 1 || (j == 0 ? v0 : v2);
    sts32(a + j * 2048, v ? pack_bf16(o[4 * j] * s0, o[4 * j + 1] * s0) : 0u);
    sts32(a + j * 2048 + 128, v ? pack_bf16(o[4 * j + 2] * s1, o[4 * j + 3] * s1) : 0u);
  }
}
__device__ __forceinline__ void flush_o(bool p, uint8_t* dst, uint32_t src, bool odd) {
  bulk_s2g_if(p, dst + (odd ? 2048 : 0), src + (odd ? 2048 : 0), 4096);
  bulk_or_if(p, dst + (odd ? 0 : 4096), src + (odd ? 0 : 4096), 2048);
  BULK_COMMIT();
}

__device__ __forceinline__ void proj20(float (&acc)[20], const __nv_bfloat16* __restrict__ xr, const __nv_bfloat16* __restrict__ wc) {
#pragma unroll
  for (int d = 0; d < 20; d++) acc[d] = 0.f;
#pragma unroll 2
  for (int k = 0; k < 640; k++) {
    const float xv = __bfloat162float(xr[k]);
#pragma unroll
    for (int d = 0; d < 10; d++) {
      const uint32_t u = ldg32(wc + k * 1920 + 2 * d);
      acc[2 * d] = fmaf(xv, __uint_as_float(u << 16), acc[2 * d]);
      acc[2 * d + 1] = fmaf(xv, __uint_as_float(u & 0xffff0000u), acc[2 * d + 1]);
    }
  }
}
__device__ __noinline__ void attn_exact(const __nv_bfloat16* __restrict__ x, const __nv_bfloat16* __restrict__ wqkv, int h, int qt, uint32_t stg) {
  const int tid = threadIdx.x;
  uint32_t* kvs = g_fb + blockIdx.x * (2048 * 20);
  float a[20];
  for (int i = 0; i < 8; i++) {
    const int key = (i >> 1) * 512 + tid, ty = 1 + (i & 1);
    proj20(a, x + key * 640, wqkv + ty * 640 + h * 20);
#pragma unroll
    for (int d = 0; d < 10; d++) kvs[key * 20 + (i & 1) * 10 + d] = pack_bf16(a[2 * d], a[2 * d + 1]);
  }
  const int row = qt * 512 + tid;
  proj20(a, x + row * 640, wqkv + h * 20);
#pragma unroll
  for (int d = 0; d < 20; d++) a[d] = __bfloat162float(__float2bfloat16(a[d]));
  __syncthreads();
  float o[20], m = -INFINITY, l = 0.f;
#pragma unroll
  for (int d = 0; d < 20; d++) o[d] = 0.f;
  for (int key = 0; key < 2048; key++) {
    uint32_t u[20];
#pragma unroll
    for (int d = 0; d < 5; d++) {
      const uint4 t4 = *reinterpret_cast<const uint4*>(kvs + key * 20 + 4 * d);
      u[4 * d] = t4.x; u[4 * d + 1] = t4.y; u[4 * d + 2] = t4.z; u[4 * d + 3] = t4.w;
    }
    float s = 0.f;
#pragma unroll
    for (int d = 0; d < 10; d++) {
      s = fmaf(a[2 * d], __uint_as_float(u[d] << 16), s);
      s = fmaf(a[2 * d + 1], __uint_as_float(u[d] & 0xffff0000u), s);
    }
    s *= 0.22360679774997896f;
    const float mn = fmaxf(m, s), cr = __expf(m - mn), p = __expf(s - mn);
    m = mn;
    l = l * cr + p;
#pragma unroll
    for (int d = 0; d < 10; d++) {
      o[2 * d] = fmaf(p, __uint_as_float(u[10 + d] << 16), o[2 * d] * cr);
      o[2 * d + 1] = fmaf(p, __uint_as_float(u[10 + d] & 0xffff0000u), o[2 * d + 1] * cr);
    }
  }
  const float sc = __ldcg(&g_gate[row]) / l;
#pragma unroll
  for (int d = 0; d < 10; d++) {
    const int col = (h & 1) * 4 + 2 * d;
    sts32(stg + (tid >> 7) * 6144 + (col >> 3) * 2048 + (tid & 127) * 16 + (col & 7) * 2, pack_bf16(o[2 * d] * sc, o[2 * d + 1] * sc));
  }
  PROXY_FENCE();
  __syncthreads();
}

#define COORDS()                                                                                                        \
  int tid, bid;                                                                                                         \
  asm volatile("mov.u32 %0, %%tid.x;" : "=r"(tid));                                                                     \
  asm volatile("mov.u32 %0, %%ctaid.x;" : "=r"(bid));                                                                   \
  const int lane = tid & 31, w = (tid >> 5) & 3, g = lane >> 2, t = lane & 3, wt = tid & 127;                           \
  const int rb1 = bid >> 3, c1 = bid & 7;                                       \
  const int h = bid >> 2, qt = bid & 3, rb = qt * 4 + wg;                    \
  const bool odd = h & 1;                                                                                               \
  const int c0 = (h * 5) >> 1;                                               \
  const int lsrc = (lane & ~3) | (odd ? 0 : 2);                                                                         \
  const bool v0 = !odd || t >= 2, v2 = odd || t < 2;                                                                    \
  const uint32_t ostg = sb + SM_X + wg * 6144, orow = (w * 16 + g) * 16 + t * 4;                                        \
  const int kh = bid & 1, cg = (bid >> 1) & 3, atom3 = (cg >> 1) * 5 + (cg & 1) * 2;                                    \
  auto p3_load_w = [&](bool p, int j) {                                                                                 \
    const uint32_t fb = bar + 8 * (B_P3FULL + (j & 3));                                                                 \
    mbar_expect_if(p, fb, P3_STB);                                                                                      \
    tma3d_if(p, sb + (j & 3) * P3_STB + 16384, &maps.wo[j < 5], (kh * 5 + (j < 5 ? j : j - 5)) * 64, atom3, fb);       \
  };                                                                                                                    \
  auto p3_load_a = [&](bool p, int j) {                                                                                 \
    bulk_g2s_if(p, sb + (j & 3) * P3_STB, g_o + rb1 * ORB + ((j < 5 ? 10 + j : j - 5) + kh * 5) * 16384, 16384,         \
                bar + 8 * (B_P3FULL + (j & 3)));                                                                        \
  };                                                                                                                    \
  (void)g; (void)t; (void)wt; (void)rb1; (void)c1; (void)rb; (void)c0; (void)lsrc; (void)v0; (void)v2; (void)ostg;      \
  (void)orow; (void)atom3; (void)p3_load_w; (void)p3_load_a

__global__ void __launch_bounds__(512, 1)
gated_mix_kernel(const __grid_constant__ Maps maps, const __nv_bfloat16* __restrict__ x, const __nv_bfloat16* __restrict__ wqkv, const __nv_bfloat16* __restrict__ w_phi,
                 const __nv_bfloat16* __restrict__ gate_w, const void* wqkv_b, const void* wo_a, const void* wo_b, uint4* __restrict__ out) {
  extern __shared__ __align__(1024) uint8_t smem_raw[];
  const uint32_t sb = (uint32_t)__cvta_generic_to_shared(smem_raw);
  const uint32_t bar = sb + SM_BAR;
  const int wg = __shfl_sync(0xffffffffu, threadIdx.x >> 7, 0);
  uint32_t q[2][6], qc[4], epoch;
  int bad;
  {
  COORDS();
  TS_MARK(0);

  auto p1_load = [&](bool p, int it) {
    const int st = it & 3, br = it >= 10, ks = it - br * 10;
    const uint32_t dst = sb + st * P1_STB, fb = bar + 8 * (B_FULL + st);
    mbar_expect_if(p, fb, P1_STB);
    tma2d_if(p, dst, &maps.x, ks * 64, rb1 * 128, fb);
    tma3d_if(p, dst + 16384, &maps.w[br], ks * 64, tile_atom(c1 ^ br), fb);
  };
  if (tid == 0) {
    if (sb & 1023) __trap();
    for (int i = 0; i < 4; i++) { mbar_init(bar + 8 * (B_FULL + i), 1); mbar_init(bar + 8 * (B_EMPTY + i), 4); }
    asm volatile("fence.mbarrier_init.release.cluster;" ::: "memory");
    for (int i = 0; i < 4; i++) p1_load(true, i);
  }
  if (tid == 32) {
    mbar_init(bar + 8 * B_STG, 2); mbar_init(bar + 8 * B_STG2, 4); mbar_init(bar + 8 * B_KB, 1); mbar_init(bar + 8 * B_QB, 1);
    mbar_init(bar + 8 * B_LINK, 4); mbar_init(bar + 8 * (B_LINK + 1), 4); mbar_init(bar + 8 * B_KVB, 128);
    for (int i = 0; i < 3; i++) mbar_init(bar + 8 * (B_FREE + i), 4);
    for (int i = 0; i < 4; i++) {
      mbar_init(bar + 8 * (B_KVFULL + i), 1); mbar_init(bar + 8 * (B_READY + i), 512);
      mbar_init(bar + 8 * (B_P3FULL + i), 1); mbar_init(bar + 8 * (B_P3EMPTY + i), 2);
    }
    asm volatile("fence.mbarrier_init.release.cluster;" ::: "memory");
  }
  epoch = (__ldcg(&g_cnt[C_EPOCH]) >> 7) + 1;
  uint2 xa[5], ga[5];
  uint16_t wv[2];
#pragma unroll
  for (int i = 0; i < 5; i++) {
    xa[i] = __ldg(reinterpret_cast<const uint2*>(x + (rb1 * 128 + c1 * 16 + (tid >> 5)) * 640 + i * 128 + lane * 4));
    ga[i] = __ldg(reinterpret_cast<const uint2*>(gate_w + i * 128 + lane * 4));
  }
#pragma unroll
  for (int u = 0; u < 2; u++) {
    const int i = tid + u * 512, k = i / 24, n = i % 24, ii = 2 * (n >> 3) + (n & 1), f = 4 * ii + ((n & 7) >> 1), d = k - (odd ? 4 : 0);
    wv[u] = (d >= 0 && d < 20 && ii < 5) ? __ldg(reinterpret_cast<const uint16_t*>(w_phi) + h * 400 + d * 20 + f) : (uint16_t)0;
  }
  __syncthreads();

  {
    float acc[64];
    const int r = wg & 1, ch = wg >> 1;
    const bool mufu0 = 2 * w < NMB, mufu1 = 2 * w + 1 < NMB;
    auto store_tile = [&](int br, uint32_t stg) {
      const int tl = c1 ^ br, k4 = tl & 3;
      const bool narrow = (k4 == 1 && wg == 3) || (k4 == 2 && wg == 0);
      const int ga0 = tile_atom(tl) + 2 * ch + ((k4 == 2 && wg == 0) ? 1 : 0), ga1 = ga0 + 1;
      tma5d_store_if(wt == 0, &maps.qst, stg, (ga0 % 10) * 8, ga0 / 10, r, br * 16 + rb1);
      tma5d_store_if(wt == 0 && !narrow, &maps.qst, stg + 8192, (ga1 % 10) * 8, ga1 / 10, r, br * 16 + rb1);
      BULK_COMMIT();
    };
    auto duties = [&](int it) {
      if (wg == (it & 3) && it >= 1 && it <= 16 && it != 10) {
        mbar_wait(bar + 8 * (B_EMPTY + ((it - 1) & 3)), ((it - 1) >> 2) & 1);
        p1_load(wt == 0, it + 3);
      }
      if (it == 0) {
        float s = 0.f;
#pragma unroll
        for (int i = 0; i < 5; i++) {
          s += __uint_as_float(xa[i].x << 16) * __uint_as_float(ga[i].x << 16) + __uint_as_float(xa[i].x & 0xffff0000u) * __uint_as_float(ga[i].x & 0xffff0000u);
          s += __uint_as_float(xa[i].y << 16) * __uint_as_float(ga[i].y << 16) + __uint_as_float(xa[i].y & 0xffff0000u) * __uint_as_float(ga[i].y & 0xffff0000u);
        }
#pragma unroll
        for (int o = 16; o; o >>= 1) s += __shfl_xor_sync(0xffffffffu, s, o);
        if (lane == 0) g_gate[rb1 * 128 + c1 * 16 + (tid >> 5)] = 1.f / (1.f + __expf(-s));
#pragma unroll
        for (int u = 0; u < 2; u++) {
          const int i = tid + u * 512, k = i / 24, n = i % 24;
          if (i < 768) sts16(sb + SM_WPHI + (k >> 3) * 384 + n * 16 + (k & 7) * 2, wv[u]);
        }
        if (tid < 256) sts32(sb + SM_CONST + tid * 4, (tid & 3) ? 0u : ((tid >> 5) < NMB ? 0xdd02e192u : 0x00001ef0u));
        const uint4 z4 = make_uint4(0u, 0u, 0u, 0u);
        out[bid * 1280 + tid] = z4; out[bid * 1280 + 512 + tid] = z4;
        if (tid < 256) out[bid * 1280 + 1024 + tid] = z4;
        *reinterpret_cast<uint4*>(g_o + rb1 * ORB + ((c1 * 4 + wg) * 5 + 2) * 2048 + wt * 16) = z4;
        if (tid < 240) g_kv[bid * 240 + tid] = 0.f;
      }
      if (it == 1 && wg == 0 && wt < 3) {
        const int bytes = wt == 0 ? 19200 : 6400;
        const uint8_t* p = reinterpret_cast<const uint8_t*>(wt == 0 ? wqkv_b : wt == 1 ? wo_a : wo_b) + bid * bytes;
        asm volatile("cp.async.bulk.prefetch.L2.global [%0], %1;" ::"l"(p), "r"(bytes) : "memory");
      }
      if (it == 12) {
        if (wg >= 2) { BULK_WAIT_READ(); mbar_arrive_if(wt == 0, bar + 8 * B_STG); }
        mbar_wait(bar + 8 * B_STG, 0);
        if (wg == 3) p1_load(wt == 0, 13);
        if (wg < 2) store_tile(0, sb + SM_X + wg * 16384);
      }
      if (it == 16 - (wg & 2)) { BULK_WAIT(); signal_if(wt == 0, &g_cnt[C_TA]); }
      if (it >= 18 && wg == (it & 3)) {
        if (it == 18) wait_count(&g_cnt[C_TA], epoch * 512);
        else mbar_wait(bar + 8 * (B_KVFULL + 0), 0);
        mbar_wait(bar + 8 * (B_EMPTY + (it - 18)), 0);
        mbar_expect_if(wt == 0, bar + 8 * (B_KVFULL + it - 18), P1_STB);
        tma5d_if(wt == 0, sb + (it - 18) * P1_STB, &maps.qld, c0, 1, (it - 18) * 4, bar + 8 * (B_KVFULL + it - 18));
      }
    };
#pragma unroll 1
    for (int br = 0; br < 2; br++) {
      const int tl = c1 ^ br, k4 = tl & 3;
      const bool narrow = (k4 == 1 && wg == 3) || (k4 == 2 && wg == 0);
      const int a0 = 2 * ch + ((k4 == 2 && wg == 0) ? 1 : 0);
      if (!narrow) {
#pragma unroll 1
        for (int ks = 0; ks < 10; ks++) {
          const int it = br * 10 + ks, st = it & 3;
          mbar_wait(bar + 8 * (B_FULL + st), (it >> 2) & 1);
          TS_MARK(20 + it);
          const uint32_t dst = sb + st * P1_STB;
          const uint64_t da = mkdesc(dst + r * 8192, 16, 1024, 1), db = mkdesc(dst + 16384 + a0 * 8192, 8192, 1024, 1);
          WG_FENCE();
#pragma unroll
          for (int k = 0; k < 4; k++) wg128_ss(acc, da + k * 2, db + k * 128, (ks | k) != 0);
          WG_COMMIT();
          WG_WAIT(1);
          mbar_arrive_if(ks > 0 && wt == 0, bar + 8 * (B_EMPTY + ((it - 1) & 3)));
          duties(it);
        }
        WG_WAIT(0);
      } else {
#pragma unroll 1
        for (int ks = 0; ks < 10; ks++) {
          const int it = br * 10 + ks, st = it & 3;
          mbar_wait(bar + 8 * (B_FULL + st), (it >> 2) & 1);
          TS_MARK(20 + it);
          const uint32_t dst = sb + st * P1_STB;
          const uint64_t da = mkdesc(dst + r * 8192, 16, 1024, 1), db = mkdesc(dst + 16384 + a0 * 8192, 8192, 1024, 1);
          WG_FENCE();
#pragma unroll
          for (int k = 0; k < 4; k++) wg64_ss_of64(acc, da + k * 2, db + k * 128, (ks | k) != 0);
          WG_COMMIT();
          WG_WAIT(1);
          mbar_arrive_if(ks > 0 && wt == 0, bar + 8 * (B_EMPTY + ((it - 1) & 3)));
          duties(it);
        }
        WG_WAIT(0);
      }
      pin(acc);
      TS_MARK(2 + 2 * br);
      mbar_arrive_if(wt == 0, bar + 8 * (B_EMPTY + ((br * 10 + 9) & 3)));
      const uint32_t lrow = (w * 16 + (lane & 15)) * 16 + (lane >> 4) * 1024;
      if (br == 0) {
        uint32_t m0 = 0, m1 = 0;
        const float sk0 = __uint_as_float(mufu0 ? (127u + 70u) << 23 : (127u - 69u) << 23);
        const float sk1 = __uint_as_float(mufu1 ? (127u + 70u) << 23 : (127u - 69u) << 23);
        if (wg >= 2) mbar_wait(bar + 8 * (B_EMPTY + 1), 0);
        const uint32_t stg = wg < 2 ? sb + SM_X + wg * 16384 : sb + P1_STB + (wg - 2) * 16384;
        const int ga0 = tile_atom(tl) + a0;
        stage_atom_a<0>(acc, ga0, stg + lrow, sk0, sk1, m0, m1);
        if (!narrow) stage_atom_a<1>(acc, ga0 + 1, stg + lrow, sk0, sk1, m0, m1);
        const uint32_t lim0 = (mufu0 ? 127u + 110u : 127u - 29u) << 7, lim1 = (mufu1 ? 127u + 110u : 127u - 29u) << 7;
        if ((m0 & 0x7fffu) >= lim0 || ((m0 >> 16) & 0x7fffu) >= lim0 || (m1 & 0x7fffu) >= lim1 || ((m1 >> 16) & 0x7fffu) >= lim1) g_kbad = epoch;
        PROXY_FENCE();
        bar_sync(1 + wg, 128);
        if (wg >= 2) store_tile(0, stg);
      } else {
        mbar_wait(bar + 8 * (B_KVFULL + 0), 0);
        const uint8_t* qp = g_qkv + rb * QRB + c0 * 2048 + (w * 16 + g) * 16 + t * 4;
        load_frag(q[0], qp);
        load_frag(q[1], qp + 1024);
        bad = ldcg32(&g_kbad) == epoch;
        sts16(sb + wg * 12288 + (wt >> 6) * 6144 + 3072 + (odd ? 0 : 2048 + 8) + (wt & 63) * 16, 0x3c00);
        mbar_wait(bar + 8 * (B_EMPTY + 2 + ch), 0);
        const uint32_t stg = sb + (2 + ch) * P1_STB + r * 16384;
        uint32_t m0, m1;
        stage_atom<0, 0>(acc, stg + lrow, 0.f, 0.f, m0, m1);
        if (!narrow) stage_atom<0, 1>(acc, stg + lrow, 0.f, 0.f, m0, m1);
        PROXY_FENCE();
        mbar_arrive(bar + 8 * (B_READY + 0));
        bar_sync(1 + wg, 128);
        store_tile(1, stg);
      }
      TS_MARK(3 + 2 * br);
    }
  }

  if (odd ? t < 2 : t >= 2) {
    if (odd) { q[0][0] = 0; q[0][1] = 0; q[1][0] = 0; q[1][1] = 0; }
    else { q[0][4] = 0; q[0][5] = 0; q[1][4] = 0; q[1][5] = 0; }
  }
  {
    uint32_t m = 0;
#pragma unroll
    for (int i = 0; i < 6; i++) m = maxabs_bf16x2(m, maxabs_bf16x2(q[0][i], q[1][i]));
    bad |= (m & 0x7fffu) >= ((127u - 50u) << 7) || ((m >> 16) & 0x7fffu) >= ((127u - 50u) << 7);
  }
#pragma unroll
  for (int i = 0; i < 4; i++) { qc[i] = t == 0 ? 0x1c801c80u : 0u; asm volatile("" : "+r"(qc[i])); }
  }
  float o[2][12];
#pragma unroll
  for (int i = 0; i < 12; i++) { o[0][i] = 0.f; o[1][i] = 0.f; }
  {
    uint32_t dk0 = (uint32_t)mkdesc(sb, 1024, 0, 0), dk1 = (uint32_t)mkdesc(sb + 2048, SM_CONST - 2048, 0, 0), dv = (uint32_t)mkdesc(sb + 3072, 128, 0, 0);
    const uint32_t events = 0x01038105u | (0x281810u << wg) | (wg == 2 ? 0x2000200u : wg == 1 ? 0x10000000u : 0u);
    TS_MARK(6);
#pragma unroll 1
    for (int i = 0; i < 32; i++) {
      if ((events >> i) & 1) {
        WG_WAIT(0);
        COORDS();
        const uint64_t dw = mkdesc(sb + SM_WPHI, 384, 128, 0);
        const uint32_t onepos = (wt >> 6) * 6144 + 3072 + (odd ? 0 : 2048 + 8) + (wt & 63) * 16;
        if ((i & 7) == 0 && i > 0) mbar_arrive_if(wt == 0, bar + 8 * (B_FREE + (i >> 3) - 1));
        if (i == 4 + wg) {
          BULK_WAIT();
          mbar_arrive_if(wt == 0, bar + 8 * B_STG2);
          signal_if(wt == 0, &g_cnt[C_TB]);
        }
        if (i == 8 && wg == 3) {
          mbar_wait(bar + 8 * B_STG2, 0);
#pragma unroll
          for (int u = 2; u < 4; u++) {
            mbar_expect_if(wt == 0, bar + 8 * (B_KVFULL + u), P1_STB);
            tma5d_if(wt == 0, sb + u * P1_STB, &maps.qld, c0, 1, u * 4, bar + 8 * (B_KVFULL + u));
          }
        }
        if (i == 9 && wg == 2) {
          mbar_wait(bar + 8 * (B_FREE + 0), 0);
          wait_count(&g_cnt[C_TB], epoch * 512);
          mbar_expect_if(wt == 0, bar + 8 * B_KB, P1_STB);
          tma5d_if(wt == 0, sb, &maps.qld, c0, 1, 16 + qt * 4, bar + 8 * B_KB);
        }
        if (i == 2 || i == 15 || i == 17) {
          const int u = i == 2 ? 1 : i == 15 ? 2 : 3;
          mbar_wait(bar + 8 * (B_KVFULL + u), 0);
          sts16(sb + u * P1_STB + wg * 12288 + onepos, 0x3c00);
          PROXY_FENCE();
          mbar_arrive(bar + 8 * (B_READY + u));
        }
        if (i == 11 + wg) {
          TS_MARK(7);
          const uint32_t kb = sb + wg * 12288, ph = sb + SM_X + (wg & 1) * 10240;
          mbar_wait(bar + 8 * B_KB, 0);
          sts16(kb + onepos, 0x3f80);
          float p0[12], p1[12];
          phi_proj(p0, p1, kb, dw);
          if (wg >= 2) mbar_wait(bar + 8 * (B_LINK + (wg & 1)), 0);
          uint32_t phi[10];
          feature_map(phi, p0);
#pragma unroll
          for (int u = 0; u < 10; u++) sts32(ph + (u % 5) * 2048 + orow + (u / 5) * 128, phi[u]);
          feature_map(phi, p1);
#pragma unroll
          for (int u = 0; u < 10; u++) sts32(ph + (u % 5) * 2048 + orow + (u / 5) * 128 + 1024, phi[u]);
          PROXY_FENCE();
          bar_sync(1 + wg, 128);
          const uint64_t da = mkdesc(ph, 128, 2048, 0), db = mkdesc(kb + 3072, 128, 1024, 0);
          WG_FENCE();
#pragma unroll
          for (int kk = 0; kk < 8; kk++) {
            if (kk == 0) wg24_ss_bf16_tt_i(p0, da, db);
            else wg24_ss_bf16_tt(p0, da + kk * 16, db + (kk & 3) * 16 + (kk >> 2) * 384, 1);
          }
          WG_COMMIT();
          WG_WAIT(0);
          pin(p0);
          mbar_arrive_if(lane == 0 && wg < 2, bar + 8 * (B_LINK + wg));
          bar_sync(1 + wg, 128);
          const uint32_t ks = kb + ((w * 16 + g) * 24 + 2 * t) * 4;
#pragma unroll
          for (int j = 0; j < 3; j++) {
            if (w < 3) asm volatile("st.shared.v2.f32 [%0], {%1, %2};" ::"r"(ks + 32 * j), "f"(p0[4 * j]), "f"(p0[4 * j + 1]) : "memory");
            if (w < 2) asm volatile("st.shared.v2.f32 [%0], {%1, %2};" ::"r"(ks + 768 + 32 * j), "f"(p0[4 * j + 2]), "f"(p0[4 * j + 3]) : "memory");
          }
          PROXY_FENCE();
          bar_sync(1 + wg, 128);
          bulk_addf_if(wt == 0, g_kv + h * 960, kb, 3840);
          BULK_COMMIT();
          TS_MARK(8);
        }
        if (i == 12 + wg) { BULK_WAIT(); signal_if(wt == 0, &g_cnt[C_KV + h]); }
        if (i == 17 && wg == 1) {
          mbar_wait(bar + 8 * (B_FREE + 1), 0);
          mbar_expect_if(wt == 0, bar + 8 * B_QB, P1_STB);
          tma5d_if(wt == 0, sb + P1_STB, &maps.qld, c0, 0, 16 + qt * 4, bar + 8 * B_QB);
        }
        if (i == 17 && wg == 0) {
          wait_count(&g_cnt[C_KV + h], epoch * 16);
          float v[8];
#pragma unroll
          for (int u = 0; u < 8; u++) v[u] = (u < 7 || wt < 64) ? __ldcg(&g_kv[h * 960 + u * 128 + wt]) : 0.f;
#pragma unroll
          for (int u = 0; u < 9; u++) {
            const int e = u * 128 + wt, f = e / 24, d = e % 24;
            sts16(sb + SM_KVB + (f >> 3) * 384 + d * 16 + (f & 7) * 2, u < 8 ? __bfloat16_as_ushort(__float2bfloat16(v[u < 8 ? u : 0])) : (uint16_t)0);
          }
          PROXY_FENCE();
          mbar_arrive(bar + 8 * B_KVB);
        }
        if (i == 19 + wg) {
          TS_MARK(9);
          float gt[4];
#pragma unroll
          for (int u = 0; u < 4; u++) gt[u] = 1.f - __ldcg(&g_gate[rb * 128 + (u >> 1) * 64 + w * 16 + g + (u & 1) * 8]);
          mbar_wait(bar + 8 * B_QB, 0);
          float p0[12], p1[12];
          phi_proj(p0, p1, sb + P1_STB + wg * 12288, dw);
          const uint64_t dkv = mkdesc(sb + SM_KVB, 384, 128, 0);
          auto readout = [&](float (&p)[12], float g0, float g1, uint32_t a) {
            uint32_t phi[10];
            feature_map(phi, p);
            WG_FENCE();
            wg24_rs_bf16_i(p, phi[0], phi[5], phi[1], phi[6], dkv);
            wg24_rs_bf16(p, phi[2], phi[7], phi[3], phi[8], dkv + 48, 1);
            wg24_rs_bf16(p, phi[4], phi[9], 0u, 0u, dkv + 96, 1);
            WG_COMMIT();
            WG_WAIT(0);
            pin(p);
            const float l0 = __shfl_sync(0xffffffffu, odd ? p[0] : p[8], lsrc), l1 = __shfl_sync(0xffffffffu, odd ? p[2] : p[10], lsrc);
            stage_o(p, __fdividef(g0, l0 + 1e-6f), __fdividef(g1, l1 + 1e-6f), a, v0, v2);
          };
          mbar_wait(bar + 8 * B_KVB, 0);
          readout(p0, gt[0], gt[1], ostg + orow);
          readout(p1, gt[2], gt[3], ostg + orow + 1024);
          PROXY_FENCE();
          bar_sync(1 + wg, 128);
          flush_o(wt == 0, g_o + rb * ORB + (80 + c0) * 2048, ostg, odd);
          TS_MARK(10);
        }
        if (i == 21 + wg) { BULK_WAIT(); signal_if(wt == 0, &g_cnt[C_OB + rb * 2 + (h >> 4)]); }
        if (i == 25 && wg == 2) {
          mbar_wait(bar + 8 * (B_FREE + 2), 0);
#pragma unroll
          for (int j = 0; j < 3; j++) p3_load_w(wt == 0, j);
        }
        if (i == 28) {
          wait_count(&g_cnt[C_OB + rb1 * 2 + kh], epoch * 16);
#pragma unroll
          for (int j = 0; j < 3; j++) p3_load_a(wt == 0, j);
        }
        if ((i & 7) == 0) mbar_wait(bar + 8 * (B_READY + (i >> 3)), 0);
      }
      if (!(i & 1)) TS_MARK(40 + (i >> 1));
#pragma unroll
      for (int m = 0; m < 2; m++) {
        float s[32];
        uint32_t p[16];
        WG_FENCE();
        wg64_rs_bf16_i(s, q[m][0], q[m][1], q[m][2], q[m][3], desc_lohi(dk0, 8));
        wg64_rs_bf16(s, q[m][4], q[m][5], qc[2 * m], qc[2 * m + 1], desc_lohi(dk1, 8), 1);
        WG_COMMIT();
        WG_WAIT(0);
        constexpr int A = 2 * NMB, B = 16 - A;
#pragma unroll
        for (int j = 0; j < B; j++) {
          if ((j * A) % B < A) { const int a = j * A / B; p[a] = exp2_pair_mufu(s[2 * a], s[2 * a + 1]); }
          p[A + j] = exp2_pair(s[2 * (A + j)], s[2 * (A + j) + 1]);
        }
        WG_FENCE();
#pragma unroll
        for (int kk = 0; kk < 4; kk++) wg24_rs_f16_t(o[m], p[4 * kk], p[4 * kk + 1], p[4 * kk + 2], p[4 * kk + 3], desc_lohi(dv + kk * 16, 64), 1);
        WG_COMMIT();
      }
      dk0 += 384; dk1 += 384u - (384u << 16); dv += 384;
    }
  }
  {
    COORDS();
    float gt[4];
#pragma unroll
    for (int u = 0; u < 4; u++) gt[u] = __ldcg(&g_gate[rb * 128 + (u >> 1) * 64 + w * 16 + g + (u & 1) * 8]);
    WG_WAIT(0);
    pin(o[0]); pin(o[1]);
    TS_MARK(11);
    int big = 0;
#pragma unroll
    for (int m = 0; m < 2; m++) {
      const float l0 = __shfl_sync(0xffffffffu, odd ? o[m][0] : o[m][8], lsrc), l1 = __shfl_sync(0xffffffffu, odd ? o[m][2] : o[m][10], lsrc);
      const float r0 = rcp(l0), r1 = rcp(l1);
      float chk = 0.f, mx0 = 0.f, mx1 = 0.f;
#pragma unroll
      for (int i = 0; i < 12; i++) chk = fmaf(o[m][i], 0.f, chk);
#pragma unroll
      for (int i = 4; i < 6; i++) { mx0 = fmaxf(mx0, fabsf(o[m][i])); mx1 = fmaxf(mx1, fabsf(o[m][i + 2])); }
      bad |= !(chk == 0.f) || !(l0 >= 32.f) || !(l1 >= 32.f);
      big |= fmaxf(mx0 * r0, mx1 * r1) >= 1.220703125e-4f;
      stage_o(o[m], r0 * gt[2 * m], r1 * gt[2 * m + 1], ostg + orow + m * 1024, v0, v2);
    }
    PROXY_FENCE();
    const int anybad = __syncthreads_or(bad), anybig = __syncthreads_or(big);
    if (anybad || !anybig) attn_exact(x, wqkv, h, qt, sb + SM_X);
  }
  TS_MARK(12);

  COORDS();
  if (wg == 3) {
    flush_o(lane == 0, g_o + (qt * 4 + w) * ORB + c0 * 2048, sb + SM_X + w * 6144, odd);
    BULK_WAIT();
    TS_MARK(17);
    signal_if(lane == 0, &g_cnt[C_OA + (qt * 4 + w) * 2 + (h >> 4)]);
    TS_MARK(18);
    if (wt == 0) atomicAdd(&g_cnt[C_EPOCH], 1);
  } else if (wg == 2) {
    if (w == 0) {
      const bool p = lane == 0;
      p3_load_w(p, 3); p3_load_a(p, 3);
      mbar_wait(bar + 8 * (B_P3EMPTY + 0), 0);
      p3_load_w(p, 4); p3_load_a(p, 4);
      for (int j = 5; j < 8; j++) { mbar_wait(bar + 8 * (B_P3EMPTY + (j & 3)), 0); p3_load_w(p, j); }
      wait_count(&g_cnt[C_OA + rb1 * 2 + kh], epoch * 16);
      TS_MARK(16);
      for (int j = 5; j < 8; j++) p3_load_a(p, j);
      for (int j = 8; j < 10; j++) { mbar_wait(bar + 8 * (B_P3EMPTY + (j & 3)), 1); p3_load_w(p, j); p3_load_a(p, j); }
    }
  } else {
    float acc[96];
    const bool wide = (cg & 1) == wg;
    const int skip = (!wide && (cg & 1)) ? 1 : 0;
    if (wide) {
#pragma unroll 1
      for (int j = 0; j < 10; j++) {
        mbar_wait(bar + 8 * (B_P3FULL + (j & 3)), (j >> 2) & 1);
        if (j == 5) TS_MARK(13);
        const uint32_t dst = sb + (j & 3) * P3_STB;
        const uint64_t da = mkdesc(dst + wg * 1024, 2048, 128, 0), db = mkdesc(dst + 16384, 8192, 1024, 1);
        WG_FENCE();
#pragma unroll
        for (int k = 0; k < 4; k++) wg192_ss(acc, da + k * 256, db + k * 128, (j | k) != 0);
        WG_COMMIT();
        WG_WAIT(1);
        mbar_arrive_if(j > 0 && wt == 0, bar + 8 * (B_P3EMPTY + ((j - 1) & 3)));
      }
      WG_WAIT(0);
    } else {
#pragma unroll 1
      for (int j = 0; j < 10; j++) {
        mbar_wait(bar + 8 * (B_P3FULL + (j & 3)), (j >> 2) & 1);
        if (j == 5) TS_MARK(13);
        const uint32_t dst = sb + (j & 3) * P3_STB;
        const uint64_t da = mkdesc(dst + wg * 1024, 2048, 128, 0), db = mkdesc(dst + 16384 + skip * 8192, 8192, 1024, 1);
        WG_FENCE();
#pragma unroll
        for (int k = 0; k < 4; k++) wg128_ss_of96(acc, da + k * 256, db + k * 128, (j | k) != 0);
        WG_COMMIT();
        WG_WAIT(1);
        mbar_arrive_if(j > 0 && wt == 0, bar + 8 * (B_P3EMPTY + ((j - 1) & 3)));
      }
      WG_WAIT(0);
    }
    pin(acc);
    TS_MARK(14);
    if (!wide) mbar_wait(bar + 8 * (B_P3EMPTY + 2), 1);
    const uint32_t stg = sb + (wide ? 4 : 2) * P3_STB;
    const int r = w * 16 + (lane & 15);
#pragma unroll
    for (int i = 0; i < 24; i += 2)
      if (i < 16 || wide) {
        const int ch = (i & 7) + (lane >> 4);
        stsm4(stg + (i >> 3) * 8192 + r * 128 + ((ch ^ (r & 7)) << 4), pack_bf16(acc[4 * i], acc[4 * i + 1]), pack_bf16(acc[4 * i + 2], acc[4 * i + 3]),
              pack_bf16(acc[4 * i + 4], acc[4 * i + 5]), pack_bf16(acc[4 * i + 6], acc[4 * i + 7]));
      }
    PROXY_FENCE();
    bar_sync(1 + wg, 128);
    if (wt < (wide ? 3 : 2)) {
      PROXY_FENCE_G();
      asm volatile("cp.reduce.async.bulk.tensor.2d.global.shared::cta.add.bulk_group [%0, {%2, %3}], [%1];" ::"l"(&maps.out), "r"(stg + wt * 8192),
                   "r"((atom3 + skip + wt) * 64), "r"(rb1 * 128 + wg * 64) : "memory");
      asm volatile("cp.async.bulk.commit_group;" ::: "memory");
      asm volatile("cp.async.bulk.wait_group 0;" ::: "memory");
    }
    TS_MARK(15);
  }
}

typedef CUresult (*EncodeFn)(CUtensorMap*, CUtensorMapDataType, cuuint32_t, void*, const cuuint64_t*, const cuuint64_t*, const cuuint32_t*, const cuuint32_t*,
                             CUtensorMapInterleave, CUtensorMapSwizzle, CUtensorMapL2promotion, CUtensorMapFloatOOBfill);
void encode(EncodeFn enc, CUtensorMap* m, void* p, int rank, const cuuint64_t* gd, const cuuint64_t* gs, const cuuint32_t* bd) {
  const cuuint32_t es[3] = {1, 1, 1};
  enc(m, CU_TENSOR_MAP_DATA_TYPE_BFLOAT16, rank, p, gd, gs, bd, es, CU_TENSOR_MAP_INTERLEAVE_NONE, CU_TENSOR_MAP_SWIZZLE_128B,
      CU_TENSOR_MAP_L2_PROMOTION_L2_128B, CU_TENSOR_MAP_FLOAT_OOB_FILL_NONE);
}

}

extern "C" void kernel_launch(void* const* d_in, const int* in_sizes, int n_in, void* d_out, int out_size) {
  static EncodeFn enc = nullptr;
  if (!enc) {
    cudaDriverEntryPointQueryResult qr;
    cudaGetDriverEntryPoint("cuTensorMapEncodeTiled", (void**)&enc, cudaEnableDefault, &qr);
    cudaFuncSetAttribute(gated_mix_kernel, cudaFuncAttributeMaxDynamicSharedMemorySize, SMEM_BYTES);
  }
  Maps m;
  {
    const cuuint64_t gd[2] = {640, 2048}, gs[1] = {1280};
    const cuuint32_t bx[2] = {64, 128}, bo[2] = {64, 64};
    encode(enc, &m.x, d_in[0], 2, gd, gs, bx);
    encode(enc, &m.out, d_out, 2, gd, gs, bo);
  }
  for (int b = 0; b < 2; b++) {
    const cuuint64_t gd[3] = {64, 640, 30}, gs[2] = {3840, 128}, gd3[3] = {64, 640, 10}, gs3[2] = {1280, 128};
    const cuuint32_t bd[3] = {64, 64, 4}, bd3[3] = {64, 64, 3};
    encode(enc, &m.w[b], d_in[b ? 4 : 1], 3, gd, gs, bd);
    encode(enc, &m.wo[b], d_in[b ? 6 : 2], 3, gd3, gs3, bd3);
  }
  {
    void* qp = nullptr;
    cudaGetSymbolAddress(&qp, g_qkv);
    const cuuint64_t gd[5] = {128, 80, 3, 2, 32}, gs[4] = {2048, QTY, 1024, QRB};
    const cuuint32_t bl[5] = {128, 3, 2, 2, 4}, bs[5] = {128, 8, 1, 1, 1}, es[5] = {1, 1, 1, 1, 1};
    enc(&m.qld, CU_TENSOR_MAP_DATA_TYPE_UINT64, 5, qp, gd, gs, bl, es, CU_TENSOR_MAP_INTERLEAVE_NONE, CU_TENSOR_MAP_SWIZZLE_NONE, CU_TENSOR_MAP_L2_PROMOTION_L2_128B, CU_TENSOR_MAP_FLOAT_OOB_FILL_NONE);
    enc(&m.qst, CU_TENSOR_MAP_DATA_TYPE_UINT64, 5, qp, gd, gs, bs, es, CU_TENSOR_MAP_INTERLEAVE_NONE, CU_TENSOR_MAP_SWIZZLE_NONE, CU_TENSOR_MAP_L2_PROMOTION_NONE, CU_TENSOR_MAP_FLOAT_OOB_FILL_NONE);
  }
  gated_mix_kernel<<<128, 512, SMEM_BYTES, cudaStreamPerThread>>>(m, (const __nv_bfloat16*)d_in[0], (const __nv_bfloat16*)d_in[1], (const __nv_bfloat16*)d_in[5],
                                                                 (const __nv_bfloat16*)d_in[7], d_in[4], d_in[2], d_in[6], (uint4*)d_out);
}
```

```cpp
#include <cuda_runtime.h>
#include <cuda.h>
#include <cuda_bf16.h>
#include <cuda_fp16.h>
#include <stdint.h>
#pragma nv_diag_suppress 550

namespace {

constexpr int QRB = 240 * 2048;
constexpr int QBR = 16 * QRB;
constexpr int QTY = 80 * 2048;
constexpr int ORB = 160 * 2048;
constexpr int NMB = 3;

__device__ __align__(1024) uint8_t g_qkv[2 * QBR];
__device__ __align__(1024) uint8_t g_o[16 * ORB];
__device__ float g_gate[2048];
__device__ __align__(16) float g_kv[32 * 960];
__device__ uint32_t g_kbad;
__device__ uint32_t g_fb[128 * 2048 * 20];
__device__ uint32_t g_cnt[192];
constexpr int C_EPOCH = 0, C_TA = 32, C_TB = 64, C_KV = 96, C_OB = 128, C_OA = 160;

#define TS_MARK(i)

__device__ __forceinline__ uint64_t mkdesc(uint32_t addr, uint32_t lbo, uint32_t sbo, int mode) {
  return (uint64_t)((addr & 0x3FFFF) >> 4) | ((uint64_t)(lbo >> 4) << 16) | ((uint64_t)(sbo >> 4) << 32) | ((uint64_t)mode << 62);
}
__device__ __forceinline__ uint64_t desc_lohi(uint32_t lo, uint32_t hi) { return ((uint64_t)hi << 32) | lo; }
#define WG_FENCE() asm volatile("wgmma.fence.sync.aligned;" ::: "memory")
#define WG_COMMIT() asm volatile("wgmma.commit_group.sync.aligned;" ::: "memory")
#define WG_WAIT(n) asm volatile("wgmma.wait_group.sync.aligned %0;" ::"n"(n) : "memory")
#define PROXY_FENCE() asm volatile("fence.proxy.async.shared::cta;" ::: "memory")
#define PROXY_FENCE_G() asm volatile("fence.proxy.async.global;" ::: "memory")
__device__ __forceinline__ void bar_sync(int id, int n) { asm volatile("bar.sync %0, %1;" ::"r"(id), "r"(n) : "memory"); }
__device__ __forceinline__ void mbar_init(uint32_t a, int c) { asm volatile("mbarrier.init.shared::cta.b64 [%0], %1;" ::"r"(a), "r"(c)); }
__device__ __forceinline__ uint32_t mbar_try(uint32_t a, int par) {
  uint32_t ok;
  asm volatile("{.reg .pred p; mbarrier.try_wait.parity.shared::cta.b64 p, [%1], %2; selp.b32 %0, 1, 0, p;}" : "=r"(ok) : "r"(a), "r"(par) : "memory");
  return ok;
}
__device__ __forceinline__ void mbar_wait(uint32_t a, int par) {
  for (int i = 0; !mbar_try(a, par); i++)
    if (i > (1 << 22)) break;
}
__device__ __forceinline__ void mbar_arrive(uint32_t a) { asm volatile("mbarrier.arrive.shared::cta.b64 _, [%0];" ::"r"(a) : "memory"); }
__device__ __forceinline__ void mbar_arrive_if(bool p, uint32_t a) {
  asm volatile("{.reg .pred p; setp.ne.b32 p, %0, 0; @p mbarrier.arrive.shared::cta.b64 _, [%1];}" ::"r"((int)p), "r"(a) : "memory");
}
__device__ __forceinline__ void mbar_expect_if(bool p, uint32_t a, int bytes) {
  asm volatile("{.reg .pred p; setp.ne.b32 p, %0, 0; @p mbarrier.arrive.expect_tx.shared::cta.b64 _, [%1], %2;}" ::"r"((int)p), "r"(a), "r"(bytes) : "memory");
}
__device__ __forceinline__ void tma2d_if(bool p, uint32_t dst, const CUtensorMap* m, int c0, int c1, uint32_t bar) {
  asm volatile("{.reg .pred p; setp.ne.b32 p, %0, 0; @p cp.async.bulk.tensor.2d.shared::cluster.global.mbarrier::complete_tx::bytes [%1], [%2, {%4, %5}], [%3];}"
               ::"r"((int)p), "r"(dst), "l"(m), "r"(bar), "r"(c0), "r"(c1) : "memory");
}
__device__ __forceinline__ void tma3d_if(bool p, uint32_t dst, const CUtensorMap* m, int c1, int c2, uint32_t bar) {
  asm volatile("{.reg .pred p; setp.ne.b32 p, %0, 0; @p cp.async.bulk.tensor.3d.shared::cluster.global.mbarrier::complete_tx::bytes [%1], [%2, {%6, %4, %5}], [%3];}"
               ::"r"((int)p), "r"(dst), "l"(m), "r"(bar), "r"(c1), "r"(c2), "r"(0) : "memory");
}
__device__ __forceinline__ void bulk_g2s_if(bool p, uint32_t dst, const void* src, int bytes, uint32_t bar) {
  asm volatile("{.reg .pred p; setp.ne.b32 p, %0, 0; @p cp.async.bulk.shared::cluster.global.mbarrier::complete_tx::bytes [%1], [%2], %3, [%4];}"
               ::"r"((int)p), "r"(dst), "l"(src), "r"(bytes), "r"(bar) : "memory");
}
__device__ __forceinline__ void tma5d_if(bool p, uint32_t dst, const CUtensorMap* m, int c1, int c2, int c4, uint32_t bar) {
  asm volatile("{.reg .pred p; setp.ne.b32 p, %0, 0; @p cp.async.bulk.tensor.5d.shared::cluster.global.mbarrier::complete_tx::bytes [%1], [%2, {%7, %4, %5, %7, %6}], [%3];}"
               ::"r"((int)p), "r"(dst), "l"(m), "r"(bar), "r"(c1), "r"(c2), "r"(c4), "r"(0) : "memory");
}
__device__ __forceinline__ void tma5d_store_if(bool p, const CUtensorMap* m, uint32_t src, int c1, int c2, int c3, int c4) {
  asm volatile("{.reg .pred p; setp.ne.b32 p, %0, 0; @p cp.async.bulk.tensor.5d.global.shared::cta.bulk_group [%1, {%7, %3, %4, %5, %6}], [%2];}"
               ::"r"((int)p), "l"(m), "r"(src), "r"(c1), "r"(c2), "r"(c3), "r"(c4), "r"(0) : "memory");
}
__device__ __forceinline__ void bulk_s2g_if(bool p, void* dst, uint32_t src, int bytes) {
  asm volatile("{.reg .pred p; setp.ne.b32 p, %0, 0; @p cp.async.bulk.global.shared::cta.bulk_group [%1], [%2], %3;}" ::"r"((int)p), "l"(dst), "r"(src), "r"(bytes) : "memory");
}
__device__ __forceinline__ void bulk_or_if(bool p, void* dst, uint32_t src, int bytes) {
  asm volatile("{.reg .pred p; setp.ne.b32 p, %0, 0; @p cp.reduce.async.bulk.global.shared::cta.bulk_group.or.b32 [%1], [%2], %3;}" ::"r"((int)p), "l"(dst), "r"(src), "r"(bytes) : "memory");
}
__device__ __forceinline__ void bulk_addf_if(bool p, void* dst, uint32_t src, int bytes) {
  asm volatile("{.reg .pred p; setp.ne.b32 p, %0, 0; @p cp.reduce.async.bulk.global.shared::cta.bulk_group.add.f32 [%1], [%2], %3;}" ::"r"((int)p), "l"(dst), "r"(src), "r"(bytes) : "memory");
}
#define BULK_COMMIT() asm volatile("cp.async.bulk.commit_group;" ::: "memory")
#define BULK_WAIT() asm volatile("cp.async.bulk.wait_group 0;" ::: "memory")
#define BULK_WAIT_READ() asm volatile("cp.async.bulk.wait_group.read 0;" ::: "memory")
__device__ __forceinline__ void signal_fence_if(bool p, uint32_t* c) {
  asm volatile("{.reg .pred p; setp.ne.b32 p, %0, 0; @p fence.acq_rel.gpu; @p red.relaxed.gpu.global.add.u32 [%1], 1;}" ::"r"((int)p), "l"(c) : "memory");
}
__device__ __forceinline__ void signal_bulk_if(bool p, uint32_t* c) {
  asm volatile("{.reg .pred p; setp.ne.b32 p, %0, 0; cp.async.bulk.wait_group 0; @p red.relaxed.gpu.global.add.u32 [%1], 1;}" ::"r"((int)p), "l"(c) : "memory");
}
__device__ __forceinline__ void wait_count(const uint32_t* c, uint32_t target) {
  for (int i = 0;; i++) {
    uint32_t v;
    asm volatile("ld.relaxed.gpu.global.u32 %0, [%1];" : "=r"(v) : "l"(c) : "memory");
    if ((int)(v - target) >= 0) break;
    if (i > (1 << 20)) break;
  }
  PROXY_FENCE_G();
}
__device__ __forceinline__ uint32_t pack_bf16(float lo, float hi) { uint32_t r; asm("cvt.rn.bf16x2.f32 %0, %1, %2;" : "=r"(r) : "f"(hi), "f"(lo)); return r; }
__device__ __forceinline__ uint32_t pack_f16(float lo, float hi) { uint32_t r; asm("cvt.rn.f16x2.f32 %0, %1, %2;" : "=r"(r) : "f"(hi), "f"(lo)); return r; }
__device__ __forceinline__ float ex2(float a) { float r; asm("ex2.approx.ftz.f32 %0, %1;" : "=f"(r) : "f"(a)); return r; }
__device__ __forceinline__ float rcp(float a) { float r; asm("rcp.approx.ftz.f32 %0, %1;" : "=f"(r) : "f"(a)); return r; }
__device__ __forceinline__ uint32_t maxabs_bf16x2(uint32_t a, uint32_t b) { uint32_t r; asm("max.NaN.xorsign.abs.bf16x2 %0, %1, %2;" : "=r"(r) : "r"(a), "r"(b)); return r; }
__device__ __forceinline__ uint32_t ldg32(const void* p) { return __ldg(reinterpret_cast<const uint32_t*>(p)); }
__device__ __forceinline__ uint32_t ldcg32(const void* p) { uint32_t v; asm volatile("ld.global.cg.u32 %0, [%1];" : "=r"(v) : "l"(p) : "memory"); return v; }
__device__ __forceinline__ void sts32(uint32_t a, uint32_t v) { asm volatile("st.shared.b32 [%0], %1;" ::"r"(a), "r"(v) : "memory"); }
__device__ __forceinline__ void sts16(uint32_t a, uint16_t v) { asm volatile("st.shared.b16 [%0], %1;" ::"r"(a), "h"(v) : "memory"); }
__device__ __forceinline__ void stsm4(uint32_t a, uint32_t r0, uint32_t r1, uint32_t r2, uint32_t r3) {
  asm volatile("stmatrix.sync.aligned.m8n8.x4.shared.b16 [%0], {%1, %2, %3, %4};" ::"r"(a), "r"(r0), "r"(r1), "r"(r2), "r"(r3) : "memory");
}
template <int N> __device__ __forceinline__ void pin(float (&d)[N]) {
#pragma unroll
  for (int i = 0; i < N; i++) asm volatile("" : "+f"(d[i])::"memory");
}

__device__ __forceinline__ void wg128_ss(float (&d)[64], uint64_t da, uint64_t db, int scale_d) {
  asm volatile("{\n.reg .pred p;\nsetp.ne.b32 p, %66, 0;\n"
    "wgmma.mma_async.sync.aligned.m64n128k16.f32.bf16.bf16 "
    "{%0, %1, %2, %3, %4, %5, %6, %7, %8, %9, %10, %11, %12, %13, %14, %15,"
    "%16, %17, %18, %19, %20, %21, %22, %23, %24, %25, %26, %27, %28, %29, %30, %31,"
    "%32, %33, %34, %35, %36, %37, %38, %39, %40, %41, %42, %43, %44, %45, %46, %47,"
    "%48, %49, %50, %51, %52, %53, %54, %55, %56, %57, %58, %59, %60, %61, %62, %63}, "
    "%64, %65, p, 1, 1, 0, 1;\n}\n"
    : "+f"(d[0]), "+f"(d[1]), "+f"(d[2]), "+f"(d[3]), "+f"(d[4]), "+f"(d[5]), "+f"(d[6]), "+f"(d[7]),
      "+f"(d[8]), "+f"(d[9]), "+f"(d[10]), "+f"(d[11]), "+f"(d[12]), "+f"(d[13]), "+f"(d[14]), "+f"(d[15]),
      "+f"(d[16]), "+f"(d[17]), "+f"(d[18]), "+f"(d[19]), "+f"(d[20]), "+f"(d[21]), "+f"(d[22]), "+f"(d[23]),
      "+f"(d[24]), "+f"(d[25]), "+f"(d[26]), "+f"(d[27]), "+f"(d[28]), "+f"(d[29]), "+f"(d[30]), "+f"(d[31]),
      "+f"(d[32]), "+f"(d[33]), "+f"(d[34]), "+f"(d[35]), "+f"(d[36]), "+f"(d[37]), "+f"(d[38]), "+f"(d[39]),
      "+f"(d[40]), "+f"(d[41]), "+f"(d[42]), "+f"(d[43]), "+f"(d[44]), "+f"(d[45]), "+f"(d[46]), "+f"(d[47]),
      "+f"(d[48]), "+f"(d[49]), "+f"(d[50]), "+f"(d[51]), "+f"(d[52]), "+f"(d[53]), "+f"(d[54]), "+f"(d[55]),
      "+f"(d[56]), "+f"(d[57]), "+f"(d[58]), "+f"(d[59]), "+f"(d[60]), "+f"(d[61]), "+f"(d[62]), "+f"(d[63])
    : "l"(da), "l"(db), "r"(scale_d));
}

__device__ __forceinline__ void wg64_ss_of64(float (&d)[64], uint64_t da, uint64_t db, int scale_d) {
  asm volatile("{\n.reg .pred p;\nsetp.ne.b32 p, %34, 0;\n"
    "wgmma.mma_async.sync.aligned.m64n64k16.f32.bf16.bf16 "
    "{%0, %1, %2, %3, %4, %5, %6, %7, %8, %9, %10, %11, %12, %13, %14, %15,"
    "%16, %17, %18, %19, %20, %21, %22, %23, %24, %25, %26, %27, %28, %29, %30, %31}, "
    "%32, %33, p, 1, 1, 0, 1;\n}\n"
    : "+f"(d[0]), "+f"(d[1]), "+f"(d[2]), "+f"(d[3]), "+f"(d[4]), "+f"(d[5]), "+f"(d[6]), "+f"(d[7]),
      "+f"(d[8]), "+f"(d[9]), "+f"(d[10]), "+f"(d[11]), "+f"(d[12]), "+f"(d[13]), "+f"(d[14]), "+f"(d[15]),
      "+f"(d[16]), "+f"(d[17]), "+f"(d[18]), "+f"(d[19]), "+f"(d[20]), "+f"(d[21]), "+f"(d[22]), "+f"(d[23]),
      "+f"(d[24]), "+f"(d[25]), "+f"(d[26]), "+f"(d[27]), "+f"(d[28]), "+f"(d[29]), "+f"(d[30]), "+f"(d[31])
    : "l"(da), "l"(db), "r"(scale_d));
}

__device__ __forceinline__ void wg192_ss(float (&d)[96], uint64_t da, uint64_t db, int scale_d) {
  asm volatile("{\n.reg .pred p;\nsetp.ne.b32 p, %98, 0;\n"
    "wgmma.mma_async.sync.aligned.m64n192k16.f32.bf16.bf16 "
    "{%0, %1, %2, %3, %4, %5, %6, %7, %8, %9, %10, %11, %12, %13, %14, %15,"
    "%16, %17, %18, %19, %20, %21, %22, %23, %24, %25, %26, %27, %28, %29, %30, %31,"
    "%32, %33, %34, %35, %36, %37, %38, %39, %40, %41, %42, %43, %44, %45, %46, %47,"
    "%48, %49, %50, %51, %52, %53, %54, %55, %56, %57, %58, %59, %60, %61, %62, %63,"
    "%64, %65, %66, %67, %68, %69, %70, %71, %72, %73, %74, %75, %76, %77, %78, %79,"
    "%80, %81, %82, %83, %84, %85, %86, %87, %88, %89, %90, %91, %92, %93, %94, %95}, "
    "%96, %97, p, 1, 1, 0, 1;\n}\n"
    : "+f"(d[0]), "+f"(d[1]), "+f"(d[2]), "+f"(d[3]), "+f"(d[4]), "+f"(d[5]), "+f"(d[6]), "+f"(d[7]),
      "+f"(d[8]), "+f"(d[9]), "+f"(d[10]), "+f"(d[11]), "+f"(d[12]), "+f"(d[13]), "+f"(d[14]), "+f"(d[15]),
      "+f"(d[16]), "+f"(d[17]), "+f"(d[18]), "+f"(d[19]), "+f"(d[20]), "+f"(d[21]), "+f"(d[22]), "+f"(d[23]),
      "+f"(d[24]), "+f"(d[25]), "+f"(d[26]), "+f"(d[27]), "+f"(d[28]), "+f"(d[29]), "+f"(d[30]), "+f"(d[31]),
      "+f"(d[32]), "+f"(d[33]), "+f"(d[34]), "+f"(d[35]), "+f"(d[36]), "+f"(d[37]), "+f"(d[38]), "+f"(d[39]),
      "+f"(d[40]), "+f"(d[41]), "+f"(d[42]), "+f"(d[43]), "+f"(d[44]), "+f"(d[45]), "+f"(d[46]), "+f"(d[47]),
      "+f"(d[48]), "+f"(d[49]), "+f"(d[50]), "+f"(d[51]), "+f"(d[52]), "+f"(d[53]), "+f"(d[54]), "+f"(d[55]),
      "+f"(d[56]), "+f"(d[57]), "+f"(d[58]), "+f"(d[59]), "+f"(d[60]), "+f"(d[61]), "+f"(d[62]), "+f"(d[63]),
      "+f"(d[64]), "+f"(d[65]), "+f"(d[66]), "+f"(d[67]), "+f"(d[68]), "+f"(d[69]), "+f"(d[70]), "+f"(d[71]),
      "+f"(d[72]), "+f"(d[73]), "+f"(d[74]), "+f"(d[75]), "+f"(d[76]), "+f"(d[77]), "+f"(d[78]), "+f"(d[79]),
      "+f"(d[80]), "+f"(d[81]), "+f"(d[82]), "+f"(d[83]), "+f"(d[84]), "+f"(d[85]), "+f"(d[86]), "+f"(d[87]),
      "+f"(d[88]), "+f"(d[89]), "+f"(d[90]), "+f"(d[91]), "+f"(d[92]), "+f"(d[93]), "+f"(d[94]), "+f"(d[95])
    : "l"(da), "l"(db), "r"(scale_d));
}

__device__ __forceinline__ void wg128_ss_of96(float (&d)[96], uint64_t da, uint64_t db, int scale_d) {
  asm volatile("{\n.reg .pred p;\nsetp.ne.b32 p, %66, 0;\n"
    "wgmma.mma_async.sync.aligned.m64n128k16.f32.bf16.bf16 "
    "{%0, %1, %2, %3, %4, %5, %6, %7, %8, %9, %10, %11, %12, %13, %14, %15,"
    "%16, %17, %18, %19, %20, %21, %22, %23, %24, %25, %26, %27, %28, %29, %30, %31,"
    "%32, %33, %34, %35, %36, %37, %38, %39, %40, %41, %42, %43, %44, %45, %46, %47,"
    "%48, %49, %50, %51, %52, %53, %54, %55, %56, %57, %58, %59, %60, %61, %62, %63}, "
    "%64, %65, p, 1, 1, 0, 1;\n}\n"
    : "+f"(d[0]), "+f"(d[1]), "+f"(d[2]), "+f"(d[3]), "+f"(d[4]), "+f"(d[5]), "+f"(d[6]), "+f"(d[7]),
      "+f"(d[8]), "+f"(d[9]), "+f"(d[10]), "+f"(d[11]), "+f"(d[12]), "+f"(d[13]), "+f"(d[14]), "+f"(d[15]),
      "+f"(d[16]), "+f"(d[17]), "+f"(d[18]), "+f"(d[19]), "+f"(d[20]), "+f"(d[21]), "+f"(d[22]), "+f"(d[23]),
      "+f"(d[24]), "+f"(d[25]), "+f"(d[26]), "+f"(d[27]), "+f"(d[28]), "+f"(d[29]), "+f"(d[30]), "+f"(d[31]),
      "+f"(d[32]), "+f"(d[33]), "+f"(d[34]), "+f"(d[35]), "+f"(d[36]), "+f"(d[37]), "+f"(d[38]), "+f"(d[39]),
      "+f"(d[40]), "+f"(d[41]), "+f"(d[42]), "+f"(d[43]), "+f"(d[44]), "+f"(d[45]), "+f"(d[46]), "+f"(d[47]),
      "+f"(d[48]), "+f"(d[49]), "+f"(d[50]), "+f"(d[51]), "+f"(d[52]), "+f"(d[53]), "+f"(d[54]), "+f"(d[55]),
      "+f"(d[56]), "+f"(d[57]), "+f"(d[58]), "+f"(d[59]), "+f"(d[60]), "+f"(d[61]), "+f"(d[62]), "+f"(d[63])
    : "l"(da), "l"(db), "r"(scale_d));
}

__device__ __forceinline__ void wg64_rs_bf16(float (&d)[32], uint32_t a0, uint32_t a1, uint32_t a2, uint32_t a3, uint64_t db, int scale_d) {
  asm volatile("{\n.reg .pred p;\nsetp.ne.b32 p, %37, 0;\n"
    "wgmma.mma_async.sync.aligned.m64n64k16.f32.bf16.bf16 "
    "{%0, %1, %2, %3, %4, %5, %6, %7, %8, %9, %10, %11, %12, %13, %14, %15,"
    "%16, %17, %18, %19, %20, %21, %22, %23, %24, %25, %26, %27, %28, %29, %30, %31}, "
    "{%32, %33, %34, %35}, %36, p, 1, 1, 0;\n}\n"
    : "+f"(d[0]), "+f"(d[1]), "+f"(d[2]), "+f"(d[3]), "+f"(d[4]), "+f"(d[5]), "+f"(d[6]), "+f"(d[7]),
      "+f"(d[8]), "+f"(d[9]), "+f"(d[10]), "+f"(d[11]), "+f"(d[12]), "+f"(d[13]), "+f"(d[14]), "+f"(d[15]),
      "+f"(d[16]), "+f"(d[17]), "+f"(d[18]), "+f"(d[19]), "+f"(d[20]), "+f"(d[21]), "+f"(d[22]), "+f"(d[23]),
      "+f"(d[24]), "+f"(d[25]), "+f"(d[26]), "+f"(d[27]), "+f"(d[28]), "+f"(d[29]), "+f"(d[30]), "+f"(d[31])
    : "r"(a0), "r"(a1), "r"(a2), "r"(a3), "l"(db), "r"(scale_d));
}

__device__ __forceinline__ void wg24_rs_f16_t(float (&d)[12], uint32_t a0, uint32_t a1, uint32_t a2, uint32_t a3, uint64_t db, int scale_d) {
  asm volatile("{\n.reg .pred p;\nsetp.ne.b32 p, %17, 0;\n"
    "wgmma.mma_async.sync.aligned.m64n24k16.f32.f16.f16 "
    "{%0, %1, %2, %3, %4, %5, %6, %7, %8, %9, %10, %11}, "
    "{%12, %13, %14, %15}, %16, p, 1, 1, 1;\n}\n"
    : "+f"(d[0]), "+f"(d[1]), "+f"(d[2]), "+f"(d[3]), "+f"(d[4]), "+f"(d[5]), "+f"(d[6]), "+f"(d[7]),
      "+f"(d[8]), "+f"(d[9]), "+f"(d[10]), "+f"(d[11])
    : "r"(a0), "r"(a1), "r"(a2), "r"(a3), "l"(db), "r"(scale_d));
}

__device__ __forceinline__ void wg24_rs_bf16(float (&d)[12], uint32_t a0, uint32_t a1, uint32_t a2, uint32_t a3, uint64_t db, int scale_d) {
  asm volatile("{\n.reg .pred p;\nsetp.ne.b32 p, %17, 0;\n"
    "wgmma.mma_async.sync.aligned.m64n24k16.f32.bf16.bf16 "
    "{%0, %1, %2, %3, %4, %5, %6, %7, %8, %9, %10, %11}, "
    "{%12, %13, %14, %15}, %16, p, 1, 1, 0;\n}\n"
    : "+f"(d[0]), "+f"(d[1]), "+f"(d[2]), "+f"(d[3]), "+f"(d[4]), "+f"(d[5]), "+f"(d[6]), "+f"(d[7]),
      "+f"(d[8]), "+f"(d[9]), "+f"(d[10]), "+f"(d[11])
    : "r"(a0), "r"(a1), "r"(a2), "r"(a3), "l"(db), "r"(scale_d));
}

__device__ __forceinline__ void wg24_ss_bf16_tt(float (&d)[12], uint64_t da, uint64_t db, int scale_d) {
  asm volatile("{\n.reg .pred p;\nsetp.ne.b32 p, %14, 0;\n"
    "wgmma.mma_async.sync.aligned.m64n24k16.f32.bf16.bf16 "
    "{%0, %1, %2, %3, %4, %5, %6, %7, %8, %9, %10, %11}, "
    "%12, %13, p, 1, 1, 1, 1;\n}\n"
    : "+f"(d[0]), "+f"(d[1]), "+f"(d[2]), "+f"(d[3]), "+f"(d[4]), "+f"(d[5]), "+f"(d[6]), "+f"(d[7]),
      "+f"(d[8]), "+f"(d[9]), "+f"(d[10]), "+f"(d[11])
    : "l"(da), "l"(db), "r"(scale_d));
}

__device__ __forceinline__ void wg64_rs_bf16_i(float (&d)[32], uint32_t a0, uint32_t a1, uint32_t a2, uint32_t a3, uint64_t db) {
  asm volatile("{\n.reg .pred p;\nsetp.ne.b32 p, 0, 0;\n"
    "wgmma.mma_async.sync.aligned.m64n64k16.f32.bf16.bf16 "
    "{%0, %1, %2, %3, %4, %5, %6, %7, %8, %9, %10, %11, %12, %13, %14, %15,"
    "%16, %17, %18, %19, %20, %21, %22, %23, %24, %25, %26, %27, %28, %29, %30, %31}, "
    "{%32, %33, %34, %35}, %36, p, 1, 1, 0;\n}\n"
    : "=f"(d[0]), "=f"(d[1]), "=f"(d[2]), "=f"(d[3]), "=f"(d[4]), "=f"(d[5]), "=f"(d[6]), "=f"(d[7]),
      "=f"(d[8]), "=f"(d[9]), "=f"(d[10]), "=f"(d[11]), "=f"(d[12]), "=f"(d[13]), "=f"(d[14]), "=f"(d[15]),
      "=f"(d[16]), "=f"(d[17]), "=f"(d[18]), "=f"(d[19]), "=f"(d[20]), "=f"(d[21]), "=f"(d[22]), "=f"(d[23]),
      "=f"(d[24]), "=f"(d[25]), "=f"(d[26]), "=f"(d[27]), "=f"(d[28]), "=f"(d[29]), "=f"(d[30]), "=f"(d[31])
    : "r"(a0), "r"(a1), "r"(a2), "r"(a3), "l"(db));
}

__device__ __forceinline__ void wg24_rs_bf16_i(float (&d)[12], uint32_t a0, uint32_t a1, uint32_t a2, uint32_t a3, uint64_t db) {
  asm volatile("{\n.reg .pred p;\nsetp.ne.b32 p, 0, 0;\n"
    "wgmma.mma_async.sync.aligned.m64n24k16.f32.bf16.bf16 "
    "{%0, %1, %2, %3, %4, %5, %6, %7, %8, %9, %10, %11}, "
    "{%12, %13, %14, %15}, %16, p, 1, 1, 0;\n}\n"
    : "=f"(d[0]), "=f"(d[1]), "=f"(d[2]), "=f"(d[3]), "=f"(d[4]), "=f"(d[5]), "=f"(d[6]), "=f"(d[7]),
      "=f"(d[8]), "=f"(d[9]), "=f"(d[10]), "=f"(d[11])
    : "r"(a0), "r"(a1), "r"(a2), "r"(a3), "l"(db));
}

__device__ __forceinline__ void wg24_ss_bf16_tt_i(float (&d)[12], uint64_t da, uint64_t db) {
  asm volatile("{\n.reg .pred p;\nsetp.ne.b32 p, 0, 0;\n"
    "wgmma.mma_async.sync.aligned.m64n24k16.f32.bf16.bf16 "
    "{%0, %1, %2, %3, %4, %5, %6, %7, %8, %9, %10, %11}, "
    "%12, %13, p, 1, 1, 1, 1;\n}\n"
    : "=f"(d[0]), "=f"(d[1]), "=f"(d[2]), "=f"(d[3]), "=f"(d[4]), "=f"(d[5]), "=f"(d[6]), "=f"(d[7]),
      "=f"(d[8]), "=f"(d[9]), "=f"(d[10]), "=f"(d[11])
    : "l"(da), "l"(db));
}

__device__ __forceinline__ void wg24_ss_bf16(float (&d)[12], uint64_t da, uint64_t db, int scale_d) {
  asm volatile("{\n.reg .pred p;\nsetp.ne.b32 p, %14, 0;\n"
    "wgmma.mma_async.sync.aligned.m64n24k16.f32.bf16.bf16 "
    "{%0, %1, %2, %3, %4, %5, %6, %7, %8, %9, %10, %11}, "
    "%12, %13, p, 1, 1, 0, 0;\n}\n"
    : "+f"(d[0]), "+f"(d[1]), "+f"(d[2]), "+f"(d[3]), "+f"(d[4]), "+f"(d[5]), "+f"(d[6]), "+f"(d[7]),
      "+f"(d[8]), "+f"(d[9]), "+f"(d[10]), "+f"(d[11])
    : "l"(da), "l"(db), "r"(scale_d));
}

__device__ __forceinline__ void wg24_ss_bf16_i(float (&d)[12], uint64_t da, uint64_t db) {
  asm volatile("{\n.reg .pred p;\nsetp.ne.b32 p, 0, 0;\n"
    "wgmma.mma_async.sync.aligned.m64n24k16.f32.bf16.bf16 "
    "{%0, %1, %2, %3, %4, %5, %6, %7, %8, %9, %10, %11}, "
    "%12, %13, p, 1, 1, 0, 0;\n}\n"
    : "=f"(d[0]), "=f"(d[1]), "=f"(d[2]), "=f"(d[3]), "=f"(d[4]), "=f"(d[5]), "=f"(d[6]), "=f"(d[7]),
      "=f"(d[8]), "=f"(d[9]), "=f"(d[10]), "=f"(d[11])
    : "l"(da), "l"(db));
}

constexpr int P1_STB = 49152, P3_STB = 40960;
constexpr int SM_X = 196608;
constexpr int SM_KVB = SM_X + 24576;
constexpr int SM_CONST = SM_X + 32768, SM_WPHI = SM_CONST + 1024, SM_BAR = SM_WPHI + 1536;
constexpr int SMEM_BYTES = SM_BAR + 512;
constexpr int B_FULL = 0, B_EMPTY = 4, B_STG2 = 9, B_KB = 10, B_QB = 11, B_LINK = 12, B_KVB = 14, B_FREE = 15, B_KVFULL = 18, B_READY = 22, B_P3FULL = 26, B_P3EMPTY = 30;

template <int V> struct Int { static constexpr int value = V; };
struct Maps { CUtensorMap x, w[2], wo[2], out, qld, qst; };

__device__ __forceinline__ int tile_atom(int t) { return (t >> 2) * 15 + ((0xB740 >> ((t & 3) * 4)) & 15); }

template <int MODE, int A>
__device__ __forceinline__ void pack_atom(const float (&acc)[64], uint32_t (&r)[32], float s0, float s1, uint32_t& m0, uint32_t& m1) {
#pragma unroll
  for (int e = A * 16; e < A * 16 + 16; e++) {
    const float s = (e & 1) ? s1 : s0;
    if (MODE == 0) r[e] = pack_bf16(acc[2 * e], acc[2 * e + 1]);
    else if (MODE == 3) r[e] = pack_f16(acc[2 * e], acc[2 * e + 1]);
    else r[e] = pack_bf16(acc[2 * e] * s, acc[2 * e + 1] * s);
    if (MODE == 2) { if (e & 1) m1 = maxabs_bf16x2(m1, r[e]); else m0 = maxabs_bf16x2(m0, r[e]); }
  }
}
template <int A>
__device__ __forceinline__ void pack_atom_a(const float (&acc)[64], uint32_t (&r)[32], int ga, float sk0, float sk1, uint32_t& m0, uint32_t& m1) {
  if (ga < 10) { const float cq = __uint_as_float(463809372u); pack_atom<1, A>(acc, r, cq, cq, m0, m1); }
  else if (ga < 20) pack_atom<2, A>(acc, r, sk0, sk1, m0, m1);
  else pack_atom<3, A>(acc, r, 0.f, 0.f, m0, m1);
}

__device__ __forceinline__ uint32_t exp2_pair(float a, float b) {
  uint32_t z, w, h;
  asm volatile("cvt.pack.sat.s16.s32 %0, %2, %1;" : "=r"(z) : "r"(__float_as_uint(a)), "r"(__float_as_uint(b)));
  asm volatile("lop3.b32 %0, %1, 0x03ff03ff, 0x34003400, 0xEA;" : "=r"(w) : "r"(z));
  asm volatile("fma.rn.f16x2 %0, %1, %1, %2;" : "=r"(h) : "r"(w), "r"(0x36203620));
  asm volatile("fma.rn.f16x2 %0, %0, %1, %2;" : "+r"(h) : "r"(w), "r"(0x2e012e01));
  return h + z - w;
}
__device__ __forceinline__ uint32_t exp2_pair_mufu(float a, float b) {
  float x, y; uint32_t r;
  asm volatile("ex2.approx.ftz.f32 %0, %1;" : "=f"(x) : "f"(a));
  asm volatile("ex2.approx.ftz.f32 %0, %1;" : "=f"(y) : "f"(b));
  asm volatile("cvt.rn.f16x2.f32 %0, %1, %2;" : "=r"(r) : "f"(y), "f"(x));
  return r;
}
__device__ __forceinline__ void load_frag(uint32_t (&a)[6], const uint8_t* p) {
  a[0] = ldcg32(p); a[1] = ldcg32(p + 128); a[2] = ldcg32(p + 2048); a[3] = ldcg32(p + 2048 + 128); a[4] = ldcg32(p + 4096); a[5] = ldcg32(p + 4096 + 128);
}
__device__ __forceinline__ void feature_map(uint32_t (&phi)[10], const float (&p)[12]) {
  const float L = 1.4426950408889634f;
#pragma unroll
  for (int r = 0; r < 2; r++) {
    const float v[5] = {p[2 * r], p[2 * r + 1], p[4 + 2 * r], p[5 + 2 * r], p[8 + 2 * r]};
    float mx = fmaxf(fmaxf(fmaxf(v[0], v[1]), fmaxf(v[2], v[3])), v[4]);
    float mn = fminf(fminf(fminf(v[0], v[1]), fminf(v[2], v[3])), v[4]);
    mx = fmaxf(mx, __shfl_xor_sync(0xffffffffu, mx, 1)); mn = fminf(mn, __shfl_xor_sync(0xffffffffu, mn, 1));
    mx = fmaxf(mx, __shfl_xor_sync(0xffffffffu, mx, 2)); mn = fminf(mn, __shfl_xor_sync(0xffffffffu, mn, 2));
    const float mxl = -mx * L, mnl = mn * L;
    float ep[5], en[5];
#pragma unroll
    for (int i = 0; i < 5; i++) { ep[i] = ex2(fmaf(v[i], L, mxl)); en[i] = ex2(fmaf(v[i], -L, mnl)); }
    float sp = (ep[0] + ep[1]) + (ep[2] + ep[3]) + ep[4], sn = (en[0] + en[1]) + (en[2] + en[3]) + en[4];
    sp += __shfl_xor_sync(0xffffffffu, sp, 1); sn += __shfl_xor_sync(0xffffffffu, sn, 1);
    sp += __shfl_xor_sync(0xffffffffu, sp, 2); sn += __shfl_xor_sync(0xffffffffu, sn, 2);
    const float rp = rcp(sp), rn = rcp(sn);
#pragma unroll
    for (int i = 0; i < 5; i++) phi[5 * r + i] = pack_bf16(ep[i] * rp, en[i] * rn);
  }
}
__device__ __forceinline__ void phi_proj(float (&p0)[12], float (&p1)[12], uint32_t a, uint64_t dw) {
  const uint64_t da = mkdesc(a, 1024, 128, 0), db = mkdesc(a + 2048, 0, 128, 0);
  WG_FENCE();
  wg24_ss_bf16_i(p0, da, dw);
  wg24_ss_bf16(p0, db, dw + 48, 1);
  wg24_ss_bf16_i(p1, da + 384, dw);
  wg24_ss_bf16(p1, db + 384, dw + 48, 1);
  WG_COMMIT();
  WG_WAIT(0);
  pin(p0); pin(p1);
}
__device__ __forceinline__ void stage_o(const float (&o)[12], float s0, float s1, uint32_t a, bool v0, bool v2) {
#pragma unroll
  for (int j = 0; j < 3; j++) {
    const bool v = j == 1 || (j == 0 ? v0 : v2);
    sts32(a + j * 2048, v ? pack_bf16(o[4 * j] * s0, o[4 * j + 1] * s0) : 0u);
    sts32(a + j * 2048 + 128, v ? pack_bf16(o[4 * j + 2] * s1, o[4 * j + 3] * s1) : 0u);
  }
}
__device__ __forceinline__ void flush_o(bool p, uint8_t* dst, uint32_t src, bool odd) {
  bulk_s2g_if(p, dst + (odd ? 2048 : 0), src + (odd ? 2048 : 0), 4096);
  bulk_or_if(p, dst + (odd ? 0 : 4096), src + (odd ? 0 : 4096), 2048);
  BULK_COMMIT();
}

__device__ __forceinline__ void proj20(float (&acc)[20], const __nv_bfloat16* __restrict__ xr, const __nv_bfloat16* __restrict__ wc) {
#pragma unroll
  for (int d = 0; d < 20; d++) acc[d] = 0.f;
#pragma unroll 2
  for (int k = 0; k < 640; k++) {
    const float xv = __bfloat162float(xr[k]);
#pragma unroll
    for (int d = 0; d < 10; d++) {
      const uint32_t u = ldg32(wc + k * 1920 + 2 * d);
      acc[2 * d] = fmaf(xv, __uint_as_float(u << 16), acc[2 * d]);
      acc[2 * d + 1] = fmaf(xv, __uint_as_float(u & 0xffff0000u), acc[2 * d + 1]);
    }
  }
}
__device__ __noinline__ void attn_exact(const __nv_bfloat16* __restrict__ x, const __nv_bfloat16* __restrict__ wqkv, int h, int qt, uint32_t stg) {
  const int tid = threadIdx.x;
  uint32_t* kvs = g_fb + blockIdx.x * (2048 * 20);
  float a[20];
  for (int i = 0; i < 8; i++) {
    const int key = (i >> 1) * 512 + tid, ty = 1 + (i & 1);
    proj20(a, x + key * 640, wqkv + ty * 640 + h * 20);
#pragma unroll
    for (int d = 0; d < 10; d++) kvs[key * 20 + (i & 1) * 10 + d] = pack_bf16(a[2 * d], a[2 * d + 1]);
  }
  const int row = qt * 512 + tid;
  proj20(a, x + row * 640, wqkv + h * 20);
#pragma unroll
  for (int d = 0; d < 20; d++) a[d] = __bfloat162float(__float2bfloat16(a[d]));
  __syncthreads();
  float o[20], m = -INFINITY, l = 0.f;
#pragma unroll
  for (int d = 0; d < 20; d++) o[d] = 0.f;
  for (int key = 0; key < 2048; key++) {
    uint32_t u[20];
#pragma unroll
    for (int d = 0; d < 5; d++) {
      const uint4 t4 = *reinterpret_cast<const uint4*>(kvs + key * 20 + 4 * d);
      u[4 * d] = t4.x; u[4 * d + 1] = t4.y; u[4 * d + 2] = t4.z; u[4 * d + 3] = t4.w;
    }
    float s = 0.f;
#pragma unroll
    for (int d = 0; d < 10; d++) {
      s = fmaf(a[2 * d], __uint_as_float(u[d] << 16), s);
      s = fmaf(a[2 * d + 1], __uint_as_float(u[d] & 0xffff0000u), s);
    }
    s *= 0.22360679774997896f;
    const float mn = fmaxf(m, s), cr = __expf(m - mn), p = __expf(s - mn);
    m = mn;
    l = l * cr + p;
#pragma unroll
    for (int d = 0; d < 10; d++) {
      o[2 * d] = fmaf(p, __uint_as_float(u[10 + d] << 16), o[2 * d] * cr);
      o[2 * d + 1] = fmaf(p, __uint_as_float(u[10 + d] & 0xffff0000u), o[2 * d + 1] * cr);
    }
  }
  const float sc = __ldcg(&g_gate[row]) / l;
#pragma unroll
  for (int d = 0; d < 10; d++) {
    const int col = (h & 1) * 4 + 2 * d;
    sts32(stg + (tid >> 7) * 6144 + (col >> 3) * 2048 + (tid & 127) * 16 + (col & 7) * 2, pack_bf16(o[2 * d] * sc, o[2 * d + 1] * sc));
  }
  PROXY_FENCE();
  __syncthreads();
}

#define COORDS()                                                                                                        \
  int tid, bid;                                                                                                         \
  asm volatile("mov.u32 %0, %%tid.x;" : "=r"(tid));                                                                     \
  asm volatile("mov.u32 %0, %%ctaid.x;" : "=r"(bid));                                                                   \
  const int wg = __shfl_sync(0xffffffffu, tid >> 7, 0);                                                                 \
  const int lane = tid & 31, w = (tid >> 5) & 3, g = lane >> 2, t = lane & 3, wt = tid & 127;                           \
  const int rb1 = bid >> 3, c1 = bid & 7;                                       \
  const int h = bid >> 2, qt = bid & 3, rb = qt * 4 + wg;                    \
  const bool odd = h & 1;                                                                                               \
  const int c0 = (h * 5) >> 1;                                               \
  const int lsrc = (lane & ~3) | (odd ? 0 : 2);                                                                         \
  const bool v0 = !odd || t >= 2, v2 = odd || t < 2;                                                                    \
  const uint32_t ostg = sb + SM_X + wg * 6144, orow = (w * 16 + g) * 16 + t * 4;                                        \
  const int kh = bid & 1, cg = (bid >> 1) & 3, atom3 = (cg >> 1) * 5 + (cg & 1) * 2;                                    \
  auto p3_load_w = [&](bool p, int j) {                                                                                 \
    const uint32_t fb = bar + 8 * (B_P3FULL + (j & 3));                                                                 \
    mbar_expect_if(p, fb, P3_STB);                                                                                      \
    tma3d_if(p, sb + (j & 3) * P3_STB + 16384, &maps.wo[j < 5], (kh * 5 + (j < 5 ? j : j - 5)) * 64, atom3, fb);       \
  };                                                                                                                    \
  auto p3_load_a = [&](bool p, int j) {                                                                                 \
    bulk_g2s_if(p, sb + (j & 3) * P3_STB, g_o + rb1 * ORB + ((j < 5 ? 10 + j : j - 5) + kh * 5) * 16384, 16384,         \
                bar + 8 * (B_P3FULL + (j & 3)));                                                                        \
  };                                                                                                                    \
  (void)g; (void)t; (void)wt; (void)rb1; (void)c1; (void)rb; (void)c0; (void)lsrc; (void)v0; (void)v2; (void)ostg;      \
  (void)orow; (void)atom3; (void)p3_load_w; (void)p3_load_a

__global__ void __launch_bounds__(512, 1)
gated_mix_kernel(const __grid_constant__ Maps maps, const __nv_bfloat16* __restrict__ x, const __nv_bfloat16* __restrict__ wqkv, const __nv_bfloat16* __restrict__ w_phi,
                 const __nv_bfloat16* __restrict__ gate_w, const void* wqkv_b, const void* wo_a, const void* wo_b, uint4* __restrict__ out) {
  extern __shared__ __align__(1024) uint8_t smem_raw[];
  const uint32_t sb = (uint32_t)__cvta_generic_to_shared(smem_raw);
  const uint32_t bar = sb + SM_BAR;
  uint32_t q[2][6], qc[4], epoch, events;
  int bad;
  {
  COORDS();
  TS_MARK(0);

  auto p1_load = [&](bool p, int it) {
    const int st = it & 3, br = it >= 10, ks = it - br * 10;
    const uint32_t dst = sb + st * P1_STB, fb = bar + 8 * (B_FULL + st);
    mbar_expect_if(p, fb, P1_STB);
    tma2d_if(p, dst, &maps.x, ks * 64, rb1 * 128, fb);
    tma3d_if(p, dst + 16384, &maps.w[br], ks * 64, tile_atom(c1 ^ br), fb);
  };
  if (tid == 0) {
    if (sb & 1023) __trap();
    for (int i = 0; i < 4; i++) { mbar_init(bar + 8 * (B_FULL + i), 1); mbar_init(bar + 8 * (B_EMPTY + i), 4); }
    asm volatile("fence.mbarrier_init.release.cluster;" ::: "memory");
    for (int i = 0; i < 4; i++) p1_load(true, i);
  }
  if (tid == 32) {
    mbar_init(bar + 8 * B_STG2, 4); mbar_init(bar + 8 * B_KB, 1); mbar_init(bar + 8 * B_QB, 1);
    mbar_init(bar + 8 * B_LINK, 4); mbar_init(bar + 8 * (B_LINK + 1), 4); mbar_init(bar + 8 * B_KVB, 128);
    for (int i = 0; i < 3; i++) mbar_init(bar + 8 * (B_FREE + i), 4);
    for (int i = 0; i < 4; i++) {
      mbar_init(bar + 8 * (B_KVFULL + i), 1); mbar_init(bar + 8 * (B_READY + i), 512);
      mbar_init(bar + 8 * (B_P3FULL + i), 1); mbar_init(bar + 8 * (B_P3EMPTY + i), 2);
    }
    asm volatile("fence.mbarrier_init.release.cluster;" ::: "memory");
  }
  epoch = ldcg32(&g_cnt[C_EPOCH]);
  uint2 xa[5], ga[5];
  uint16_t wv[2];
#pragma unroll
  for (int i = 0; i < 5; i++) {
    xa[i] = __ldg(reinterpret_cast<const uint2*>(x + (rb1 * 128 + c1 * 16 + (tid >> 5)) * 640 + i * 128 + lane * 4));
    ga[i] = __ldg(reinterpret_cast<const uint2*>(gate_w + i * 128 + lane * 4));
  }
#pragma unroll
  for (int u = 0; u < 2; u++) {
    const int i = tid + u * 512, k = i / 24, n = i % 24, ii = 2 * (n >> 3) + (n & 1), f = 4 * ii + ((n & 7) >> 1), d = k - (odd ? 4 : 0);
    wv[u] = (d >= 0 && d < 20 && ii < 5) ? __ldg(reinterpret_cast<const uint16_t*>(w_phi) + h * 400 + d * 20 + f) : (uint16_t)0;
  }
  __syncthreads();

  {
    float acc[64];
    const int r = wg & 1, ch = wg >> 1;
    const bool mufu0 = 2 * w < NMB, mufu1 = 2 * w + 1 < NMB;
    uint32_t pk[32];
    uint8_t* gdst;
    auto duties = [&](auto BR, int it) {
      constexpr int br = decltype(BR)::value;
      if (wg == (it & 3) && it >= 1 && it <= 16) {
        mbar_wait(bar + 8 * (B_EMPTY + ((it - 1) & 3)), ((it - 1) >> 2) & 1);
        p1_load(wt == 0, it + 3);
      }
      if (br == 0 && it == 1) {
        asm volatile("" : "+r"(epoch));
        epoch = (epoch >> 7) + 1;
        float s = 0.f;
#pragma unroll
        for (int i = 0; i < 5; i++) {
          s += __uint_as_float(xa[i].x << 16) * __uint_as_float(ga[i].x << 16) + __uint_as_float(xa[i].x & 0xffff0000u) * __uint_as_float(ga[i].x & 0xffff0000u);
          s += __uint_as_float(xa[i].y << 16) * __uint_as_float(ga[i].y << 16) + __uint_as_float(xa[i].y & 0xffff0000u) * __uint_as_float(ga[i].y & 0xffff0000u);
        }
#pragma unroll
        for (int o = 16; o; o >>= 1) s += __shfl_xor_sync(0xffffffffu, s, o);
        if (lane == 0) g_gate[rb1 * 128 + c1 * 16 + (tid >> 5)] = 1.f / (1.f + __expf(-s));
#pragma unroll
        for (int u = 0; u < 2; u++) {
          const int i = tid + u * 512, k = i / 24, n = i % 24;
          if (i < 768) sts16(sb + SM_WPHI + (k >> 3) * 384 + n * 16 + (k & 7) * 2, wv[u]);
        }
        if (tid < 256) sts32(sb + SM_CONST + tid * 4, (tid & 3) ? 0u : ((tid >> 5) < NMB ? 0xdd02e192u : 0x00001ef0u));
        PROXY_FENCE();
      }
      if (br == 0 && it == 2) {
        const uint4 z4 = make_uint4(0u, 0u, 0u, 0u);
        out[bid * 1280 + tid] = z4; out[bid * 1280 + 512 + tid] = z4;
        if (tid < 256) out[bid * 1280 + 1024 + tid] = z4;
        *reinterpret_cast<uint4*>(g_o + rb1 * ORB + ((c1 * 4 + wg) * 5 + 2) * 2048 + wt * 16) = z4;
        if (tid < 240) g_kv[bid * 240 + tid] = 0.f;
      }
      if (br == 0 && it == 3 && wg == 0 && wt < 3) {
        const int bytes = wt == 0 ? 19200 : 6400;
        const uint8_t* p = reinterpret_cast<const uint8_t*>(wt == 0 ? wqkv_b : wt == 1 ? wo_a : wo_b) + bid * bytes;
        asm volatile("cp.async.bulk.prefetch.L2.global [%0], %1;" ::"l"(p), "r"(bytes) : "memory");
      }
      const bool narrow_a = ((c1 & 3) == 1 && wg == 3) || ((c1 & 3) == 2 && wg == 0);
#pragma unroll
      for (int u = 0; u < 4; u++)
        if (br == 1 && it == 10 + u && (u < 2 || !narrow_a)) {
#pragma unroll
          for (int e = u * 8; e < u * 8 + 8; e++) *reinterpret_cast<uint32_t*>(gdst + (e >> 1) * 2048 + (e & 1) * 128) = pk[e];
        }
      if (br == 1 && it == 14 + (wg >> 1)) { bar_sync(1 + wg, 128); signal_fence_if(wt == 0, &g_cnt[C_TA]); }
      if (br == 1 && it >= 17 && it <= 18 && wg == (it & 3)) {
        if (it == 17) wait_count(&g_cnt[C_TA], epoch * 512);
        else mbar_wait(bar + 8 * (B_KVFULL + 0), 0);
        mbar_wait(bar + 8 * (B_EMPTY + (it - 17)), 0);
        mbar_expect_if(wt == 0, bar + 8 * (B_KVFULL + it - 17), P1_STB);
        tma5d_if(wt == 0, sb + (it - 17) * P1_STB, &maps.qld, c0, 1, (it - 17) * 4, bar + 8 * (B_KVFULL + it - 17));
      }
    };
    auto tile = [&](auto BR) {
      constexpr int br = decltype(BR)::value;
      const int tl = c1 ^ br, k4 = tl & 3;
      const bool narrow = (k4 == 1 && wg == 3) || (k4 == 2 && wg == 0);
      const int a0 = 2 * ch + ((k4 == 2 && wg == 0) ? 1 : 0);
      if (!narrow) {
#pragma unroll 1
        for (int ks = 0; ks < 10; ks++) {
          const int it = br * 10 + ks, st = it & 3;
          mbar_wait(bar + 8 * (B_FULL + st), (it >> 2) & 1);
          TS_MARK(20 + it);
          const uint32_t dst = sb + st * P1_STB;
          const uint64_t da = mkdesc(dst + r * 8192, 16, 1024, 1), db = mkdesc(dst + 16384 + a0 * 8192, 8192, 1024, 1);
          WG_FENCE();
#pragma unroll
          for (int k = 0; k < 4; k++) wg128_ss(acc, da + k * 2, db + k * 128, (ks | k) != 0);
          WG_COMMIT();
          WG_WAIT(1);
          mbar_arrive_if(ks > 0 && wt == 0, bar + 8 * (B_EMPTY + ((it - 1) & 3)));
          duties(BR, it);
        }
        WG_WAIT(0);
      } else {
#pragma unroll 1
        for (int ks = 0; ks < 10; ks++) {
          const int it = br * 10 + ks, st = it & 3;
          mbar_wait(bar + 8 * (B_FULL + st), (it >> 2) & 1);
          TS_MARK(20 + it);
          const uint32_t dst = sb + st * P1_STB;
          const uint64_t da = mkdesc(dst + r * 8192, 16, 1024, 1), db = mkdesc(dst + 16384 + a0 * 8192, 8192, 1024, 1);
          WG_FENCE();
#pragma unroll
          for (int k = 0; k < 4; k++) wg64_ss_of64(acc, da + k * 2, db + k * 128, (ks | k) != 0);
          WG_COMMIT();
          WG_WAIT(1);
          mbar_arrive_if(ks > 0 && wt == 0, bar + 8 * (B_EMPTY + ((it - 1) & 3)));
          duties(BR, it);
        }
        WG_WAIT(0);
      }
      pin(acc);
      TS_MARK(2 + 2 * br);
      mbar_arrive_if(wt == 0, bar + 8 * (B_EMPTY + ((br * 10 + 9) & 3)));
      const int ga0 = tile_atom(tl) + a0;
      uint32_t m0 = 0, m1 = 0;
      if (br == 0) {
        const float sk0 = __uint_as_float(mufu0 ? (127u + 70u) << 23 : (127u - 69u) << 23);
        const float sk1 = __uint_as_float(mufu1 ? (127u + 70u) << 23 : (127u - 69u) << 23);
        pack_atom_a<0>(acc, pk, ga0, sk0, sk1, m0, m1);
        if (!narrow) pack_atom_a<1>(acc, pk, ga0 + 1, sk0, sk1, m0, m1);
        gdst = g_qkv + rb1 * QRB + ga0 * 16384 + (r * 64 + w * 16 + g) * 16 + t * 4;
        const uint32_t lim0 = (mufu0 ? 127u + 110u : 127u - 29u) << 7, lim1 = (mufu1 ? 127u + 110u : 127u - 29u) << 7;
        if ((m0 & 0x7fffu) >= lim0 || ((m0 >> 16) & 0x7fffu) >= lim0 || (m1 & 0x7fffu) >= lim1 || ((m1 >> 16) & 0x7fffu) >= lim1) g_kbad = epoch;
      } else {
        mbar_wait(bar + 8 * (B_KVFULL + 0), 0);
        const uint8_t* qp = g_qkv + rb * QRB + c0 * 2048 + (w * 16 + g) * 16 + t * 4;
        load_frag(q[0], qp);
        load_frag(q[1], qp + 1024);
        bad = ldcg32(&g_kbad) == epoch;
        sts16(sb + wg * 12288 + (wt >> 6) * 6144 + 3072 + (odd ? 0 : 2048 + 8) + (wt & 63) * 16, 0x3c00);
        PROXY_FENCE();
        mbar_arrive(bar + 8 * (B_READY + 0));
        pack_atom<0, 0>(acc, pk, 0.f, 0.f, m0, m1);
        pack_atom<0, 1>(acc, pk, 0.f, 0.f, m0, m1);
        mbar_wait(bar + 8 * (B_EMPTY + 2 + ch), 0);
        const uint32_t stg = sb + (2 + ch) * P1_STB + r * 16384;
#pragma unroll
        for (int e = 0; e < 32; e += 4) stsm4(stg + (w * 16 + (lane & 15)) * 16 + (lane >> 4) * 1024 + e * 512, pk[e], pk[e + 1], pk[e + 2], pk[e + 3]);
        PROXY_FENCE();
        bar_sync(1 + wg, 128);
        tma5d_store_if(wt == 0, &maps.qst, stg, (ga0 % 10) * 8, ga0 / 10, r, 16 + rb1);
        tma5d_store_if(wt == 0 && !narrow, &maps.qst, stg + 8192, ((ga0 + 1) % 10) * 8, (ga0 + 1) / 10, r, 16 + rb1);
        BULK_COMMIT();
      }
      TS_MARK(3 + 2 * br);
    };
    tile(Int<0>{});
    tile(Int<1>{});
  }

  if (odd ? t < 2 : t >= 2) {
    if (odd) { q[0][0] = 0; q[0][1] = 0; q[1][0] = 0; q[1][1] = 0; }
    else { q[0][4] = 0; q[0][5] = 0; q[1][4] = 0; q[1][5] = 0; }
  }
  {
    uint32_t m = 0;
#pragma unroll
    for (int i = 0; i < 6; i++) m = maxabs_bf16x2(m, maxabs_bf16x2(q[0][i], q[1][i]));
    bad |= (m & 0x7fffu) >= ((127u - 50u) << 7) || ((m >> 16) & 0x7fffu) >= ((127u - 50u) << 7);
  }
#pragma unroll
  for (int i = 0; i < 4; i++) { qc[i] = t == 0 ? 0x1c801c80u : 0u; asm volatile("" : "+r"(qc[i])); }
  events = 0x01038105u | (0x281810u << wg) | (wg == 2 ? 0x2000200u : wg == 1 ? 0x10000000u : 0u);
  }
  float o[2][12];
#pragma unroll
  for (int i = 0; i < 12; i++) { o[0][i] = 0.f; o[1][i] = 0.f; }
  {
    uint32_t dk0 = (uint32_t)mkdesc(sb, 1024, 0, 0), dk1 = (uint32_t)mkdesc(sb + 2048, SM_CONST - 2048, 0, 0), dv = (uint32_t)mkdesc(sb + 3072, 128, 0, 0);
    TS_MARK(6);
#pragma unroll 1
    for (int i = 0; i < 32; i++) {
      if ((events >> i) & 1) {
        WG_WAIT(0);
        COORDS();
        const uint64_t dw = mkdesc(sb + SM_WPHI, 384, 128, 0);
        const uint32_t onepos = (wt >> 6) * 6144 + 3072 + (odd ? 0 : 2048 + 8) + (wt & 63) * 16;
        if ((i & 7) == 0 && i > 0) mbar_arrive_if(wt == 0, bar + 8 * (B_FREE + (i >> 3) - 1));
        if (i == 4 + wg) {
          signal_bulk_if(wt == 0, &g_cnt[C_TB]);
          mbar_arrive_if(wt == 0, bar + 8 * B_STG2);
        }
        if (i == 8 && wg == 3) {
          mbar_wait(bar + 8 * B_STG2, 0);
#pragma unroll
          for (int u = 2; u < 4; u++) {
            mbar_expect_if(wt == 0, bar + 8 * (B_KVFULL + u), P1_STB);
            tma5d_if(wt == 0, sb + u * P1_STB, &maps.qld, c0, 1, u * 4, bar + 8 * (B_KVFULL + u));
          }
        }
        if (i == 9 && wg == 2) {
          mbar_wait(bar + 8 * (B_FREE + 0), 0);
          wait_count(&g_cnt[C_TB], epoch * 512);
          mbar_expect_if(wt == 0, bar + 8 * B_KB, P1_STB);
          tma5d_if(wt == 0, sb, &maps.qld, c0, 1, 16 + qt * 4, bar + 8 * B_KB);
        }
        if (i == 2 || i == 15 || i == 17) {
          const int u = i == 2 ? 1 : i == 15 ? 2 : 3;
          mbar_wait(bar + 8 * (B_KVFULL + u), 0);
          sts16(sb + u * P1_STB + wg * 12288 + onepos, 0x3c00);
          PROXY_FENCE();
          mbar_arrive(bar + 8 * (B_READY + u));
        }
        if (i == 11 + wg) {
          TS_MARK(7);
          const uint32_t kb = sb + wg * 12288, ph = sb + SM_X + (wg & 1) * 10240;
          mbar_wait(bar + 8 * B_KB, 0);
          sts16(kb + onepos, 0x3f80);
          float p0[12], p1[12];
          phi_proj(p0, p1, kb, dw);
          if (wg >= 2) mbar_wait(bar + 8 * (B_LINK + (wg & 1)), 0);
          uint32_t phi[10];
          feature_map(phi, p0);
#pragma unroll
          for (int u = 0; u < 10; u++) sts32(ph + (u % 5) * 2048 + orow + (u / 5) * 128, phi[u]);
          feature_map(phi, p1);
#pragma unroll
          for (int u = 0; u < 10; u++) sts32(ph + (u % 5) * 2048 + orow + (u / 5) * 128 + 1024, phi[u]);
          PROXY_FENCE();
          bar_sync(1 + wg, 128);
          const uint64_t da = mkdesc(ph, 128, 2048, 0), db = mkdesc(kb + 3072, 128, 1024, 0);
          WG_FENCE();
#pragma unroll
          for (int kk = 0; kk < 8; kk++) {
            if (kk == 0) wg24_ss_bf16_tt_i(p0, da, db);
            else wg24_ss_bf16_tt(p0, da + kk * 16, db + (kk & 3) * 16 + (kk >> 2) * 384, 1);
          }
          WG_COMMIT();
          WG_WAIT(0);
          pin(p0);
          mbar_arrive_if(lane == 0 && wg < 2, bar + 8 * (B_LINK + wg));
          bar_sync(1 + wg, 128);
          const uint32_t ks = kb + ((w * 16 + g) * 24 + 2 * t) * 4;
#pragma unroll
          for (int j = 0; j < 3; j++) {
            if (w < 3) asm volatile("st.shared.v2.f32 [%0], {%1, %2};" ::"r"(ks + 32 * j), "f"(p0[4 * j]), "f"(p0[4 * j + 1]) : "memory");
            if (w < 2) asm volatile("st.shared.v2.f32 [%0], {%1, %2};" ::"r"(ks + 768 + 32 * j), "f"(p0[4 * j + 2]), "f"(p0[4 * j + 3]) : "memory");
          }
          PROXY_FENCE();
          bar_sync(1 + wg, 128);
          bulk_addf_if(wt == 0, g_kv + h * 960, kb, 3840);
          BULK_COMMIT();
          TS_MARK(8);
        }
        if (i == 12 + wg) signal_bulk_if(wt == 0, &g_cnt[C_KV + h]);
        if (i == 17 && wg == 1) {
          mbar_wait(bar + 8 * (B_FREE + 1), 0);
          mbar_expect_if(wt == 0, bar + 8 * B_QB, P1_STB);
          tma5d_if(wt == 0, sb + P1_STB, &maps.qld, c0, 0, 16 + qt * 4, bar + 8 * B_QB);
        }
        if (i == 17 && wg == 0) {
          wait_count(&g_cnt[C_KV + h], epoch * 16);
          float v[8];
#pragma unroll
          for (int u = 0; u < 8; u++) v[u] = (u < 7 || wt < 64) ? __ldcg(&g_kv[h * 960 + u * 128 + wt]) : 0.f;
#pragma unroll
          for (int u = 0; u < 9; u++) {
            const int e = u * 128 + wt, f = e / 24, d = e % 24;
            sts16(sb + SM_KVB + (f >> 3) * 384 + d * 16 + (f & 7) * 2, u < 8 ? __bfloat16_as_ushort(__float2bfloat16(v[u < 8 ? u : 0])) : (uint16_t)0);
          }
          PROXY_FENCE();
          mbar_arrive(bar + 8 * B_KVB);
        }
        if (i == 19 + wg) {
          TS_MARK(9);
          float gt[4];
#pragma unroll
          for (int u = 0; u < 4; u++) gt[u] = 1.f - __ldcg(&g_gate[rb * 128 + (u >> 1) * 64 + w * 16 + g + (u & 1) * 8]);
          mbar_wait(bar + 8 * B_QB, 0);
          float p0[12], p1[12];
          phi_proj(p0, p1, sb + P1_STB + wg * 12288, dw);
          const uint64_t dkv = mkdesc(sb + SM_KVB, 384, 128, 0);
          auto readout = [&](float (&p)[12], float g0, float g1, uint32_t a) {
            uint32_t phi[10];
            feature_map(phi, p);
            WG_FENCE();
            wg24_rs_bf16_i(p, phi[0], phi[5], phi[1], phi[6], dkv);
            wg24_rs_bf16(p, phi[2], phi[7], phi[3], phi[8], dkv + 48, 1);
            wg24_rs_bf16(p, phi[4], phi[9], 0u, 0u, dkv + 96, 1);
            WG_COMMIT();
            WG_WAIT(0);
            pin(p);
            const float l0 = __shfl_sync(0xffffffffu, odd ? p[0] : p[8], lsrc), l1 = __shfl_sync(0xffffffffu, odd ? p[2] : p[10], lsrc);
            stage_o(p, __fdividef(g0, l0 + 1e-6f), __fdividef(g1, l1 + 1e-6f), a, v0, v2);
          };
          mbar_wait(bar + 8 * B_KVB, 0);
          readout(p0, gt[0], gt[1], ostg + orow);
          readout(p1, gt[2], gt[3], ostg + orow + 1024);
          PROXY_FENCE();
          bar_sync(1 + wg, 128);
          flush_o(wt == 0, g_o + rb * ORB + (80 + c0) * 2048, ostg, odd);
          TS_MARK(10);
        }
        if (i == 21 + wg) signal_bulk_if(wt == 0, &g_cnt[C_OB + rb * 2 + (h >> 4)]);
        if (i == 25 && wg == 2) {
          mbar_wait(bar + 8 * (B_FREE + 2), 0);
#pragma unroll
          for (int j = 0; j < 3; j++) p3_load_w(wt == 0, j);
        }
        if (i == 28) {
          wait_count(&g_cnt[C_OB + rb1 * 2 + kh], epoch * 16);
#pragma unroll
          for (int j = 0; j < 3; j++) p3_load_a(wt == 0, j);
        }
        if ((i & 7) == 0) mbar_wait(bar + 8 * (B_READY + (i >> 3)), 0);
      }
      if (!(i & 1)) TS_MARK(40 + (i >> 1));
#pragma unroll
      for (int m = 0; m < 2; m++) {
        float s[32];
        uint32_t p[16];
        WG_FENCE();
        wg64_rs_bf16_i(s, q[m][0], q[m][1], q[m][2], q[m][3], desc_lohi(dk0, 8));
        wg64_rs_bf16(s, q[m][4], q[m][5], qc[2 * m], qc[2 * m + 1], desc_lohi(dk1, 8), 1);
        WG_COMMIT();
        WG_WAIT(0);
        constexpr int A = 2 * NMB, B = 16 - A;
#pragma unroll
        for (int j = 0; j < B; j++) {
          if ((j * A) % B < A) { const int a = j * A / B; p[a] = exp2_pair_mufu(s[2 * a], s[2 * a + 1]); }
          p[A + j] = exp2_pair(s[2 * (A + j)], s[2 * (A + j) + 1]);
        }
        WG_FENCE();
#pragma unroll
        for (int kk = 0; kk < 4; kk++) wg24_rs_f16_t(o[m], p[4 * kk], p[4 * kk + 1], p[4 * kk + 2], p[4 * kk + 3], desc_lohi(dv + kk * 16, 64), 1);
        WG_COMMIT();
      }
      dk0 += 384; dk1 += 384u - (384u << 16); dv += 384;
    }
  }
  {
    COORDS();
    float gt[4];
#pragma unroll
    for (int u = 0; u < 4; u++) gt[u] = __ldcg(&g_gate[rb * 128 + (u >> 1) * 64 + w * 16 + g + (u & 1) * 8]);
    WG_WAIT(0);
    pin(o[0]); pin(o[1]);
    TS_MARK(11);
    int big = 0;
#pragma unroll
    for (int m = 0; m < 2; m++) {
      const float l0 = __shfl_sync(0xffffffffu, odd ? o[m][0] : o[m][8], lsrc), l1 = __shfl_sync(0xffffffffu, odd ? o[m][2] : o[m][10], lsrc);
      const float r0 = rcp(l0), r1 = rcp(l1);
      float chk = 0.f, mx0 = 0.f, mx1 = 0.f;
#pragma unroll
      for (int i = 0; i < 12; i++) chk = fmaf(o[m][i], 0.f, chk);
#pragma unroll
      for (int i = 4; i < 6; i++) { mx0 = fmaxf(mx0, fabsf(o[m][i])); mx1 = fmaxf(mx1, fabsf(o[m][i + 2])); }
      bad |= !(chk == 0.f) || !(l0 >= 32.f) || !(l1 >= 32.f);
      big |= fmaxf(mx0 * r0, mx1 * r1) >= 1.220703125e-4f;
      stage_o(o[m], r0 * gt[2 * m], r1 * gt[2 * m + 1], ostg + orow + m * 1024, v0, v2);
    }
    PROXY_FENCE();
    const int anybad = __syncthreads_or(bad), anybig = __syncthreads_or(big);
    if (anybad || !anybig) attn_exact(x, wqkv, h, qt, sb + SM_X);
  }
  TS_MARK(12);

  COORDS();
  if (wg == 3) {
    flush_o(lane == 0, g_o + (qt * 4 + w) * ORB + c0 * 2048, sb + SM_X + w * 6144, odd);
    signal_bulk_if(lane == 0, &g_cnt[C_OA + (qt * 4 + w) * 2 + (h >> 4)]);
    TS_MARK(18);
    if (wt == 0) atomicAdd(&g_cnt[C_EPOCH], 1);
  } else if (wg == 2) {
    if (w == 0) {
      const bool p = lane == 0;
      p3_load_w(p, 3); p3_load_a(p, 3);
      mbar_wait(bar + 8 * (B_P3EMPTY + 0), 0);
      p3_load_w(p, 4); p3_load_a(p, 4);
      for (int j = 5; j < 8; j++) { mbar_wait(bar + 8 * (B_P3EMPTY + (j & 3)), 0); p3_load_w(p, j); }
      wait_count(&g_cnt[C_OA + rb1 * 2 + kh], epoch * 16);
      TS_MARK(16);
      for (int j = 5; j < 8; j++) p3_load_a(p, j);
      for (int j = 8; j < 10; j++) { mbar_wait(bar + 8 * (B_P3EMPTY + (j & 3)), 1); p3_load_w(p, j); p3_load_a(p, j); }
    }
  } else {
    float acc[96];
    const bool wide = (cg & 1) == wg;
    const int skip = (!wide && (cg & 1)) ? 1 : 0;
    if (wide) {
#pragma unroll 1
      for (int j = 0; j < 10; j++) {
        mbar_wait(bar + 8 * (B_P3FULL + (j & 3)), (j >> 2) & 1);
        if (j == 5) TS_MARK(13);
        const uint32_t dst = sb + (j & 3) * P3_STB;
        const uint64_t da = mkdesc(dst + wg * 1024, 2048, 128, 0), db = mkdesc(dst + 16384, 8192, 1024, 1);
        WG_FENCE();
#pragma unroll
        for (int k = 0; k < 4; k++) wg192_ss(acc, da + k * 256, db + k * 128, (j | k) != 0);
        WG_COMMIT();
        WG_WAIT(1);
        mbar_arrive_if(j > 0 && wt == 0, bar + 8 * (B_P3EMPTY + ((j - 1) & 3)));
      }
      WG_WAIT(0);
    } else {
#pragma unroll 1
      for (int j = 0; j < 10; j++) {
        mbar_wait(bar + 8 * (B_P3FULL + (j & 3)), (j >> 2) & 1);
        if (j == 5) TS_MARK(13);
        const uint32_t dst = sb + (j & 3) * P3_STB;
        const uint64_t da = mkdesc(dst + wg * 1024, 2048, 128, 0), db = mkdesc(dst + 16384 + skip * 8192, 8192, 1024, 1);
        WG_FENCE();
#pragma unroll
        for (int k = 0; k < 4; k++) wg128_ss_of96(acc, da + k * 256, db + k * 128, (j | k) != 0);
        WG_COMMIT();
        WG_WAIT(1);
        mbar_arrive_if(j > 0 && wt == 0, bar + 8 * (B_P3EMPTY + ((j - 1) & 3)));
      }
      WG_WAIT(0);
    }
    pin(acc);
    TS_MARK(14);
    if (!wide) mbar_wait(bar + 8 * (B_P3EMPTY + 2), 1);
    const uint32_t stg = sb + (wide ? 4 : 2) * P3_STB;
    const int r = w * 16 + (lane & 15);
#pragma unroll
    for (int i = 0; i < 24; i += 2)
      if (i < 16 || wide) {
        const int ch = (i & 7) + (lane >> 4);
        stsm4(stg + (i >> 3) * 8192 + r * 128 + ((ch ^ (r & 7)) << 4), pack_bf16(acc[4 * i], acc[4 * i + 1]), pack_bf16(acc[4 * i + 2], acc[4 * i + 3]),
              pack_bf16(acc[4 * i + 4], acc[4 * i + 5]), pack_bf16(acc[4 * i + 6], acc[4 * i + 7]));
      }
    PROXY_FENCE();
    bar_sync(1 + wg, 128);
    if (wt < (wide ? 3 : 2)) {
      PROXY_FENCE_G();
      asm volatile("cp.reduce.async.bulk.tensor.2d.global.shared::cta.add.bulk_group [%0, {%2, %3}], [%1];" ::"l"(&maps.out), "r"(stg + wt * 8192),
                   "r"((atom3 + skip + wt) * 64), "r"(rb1 * 128 + wg * 64) : "memory");
      asm volatile("cp.async.bulk.commit_group;" ::: "memory");
      asm volatile("cp.async.bulk.wait_group 0;" ::: "memory");
    }
    TS_MARK(15);
  }
}

typedef CUresult (*EncodeFn)(CUtensorMap*, CUtensorMapDataType, cuuint32_t, void*, const cuuint64_t*, const cuuint64_t*, const cuuint32_t*, const cuuint32_t*,
                             CUtensorMapInterleave, CUtensorMapSwizzle, CUtensorMapL2promotion, CUtensorMapFloatOOBfill);
void encode(EncodeFn enc, CUtensorMap* m, void* p, int rank, const cuuint64_t* gd, const cuuint64_t* gs, const cuuint32_t* bd) {
  const cuuint32_t es[3] = {1, 1, 1};
  enc(m, CU_TENSOR_MAP_DATA_TYPE_BFLOAT16, rank, p, gd, gs, bd, es, CU_TENSOR_MAP_INTERLEAVE_NONE, CU_TENSOR_MAP_SWIZZLE_128B,
      CU_TENSOR_MAP_L2_PROMOTION_L2_128B, CU_TENSOR_MAP_FLOAT_OOB_FILL_NONE);
}

}

extern "C" void kernel_launch(void* const* d_in, const int* in_sizes, int n_in, void* d_out, int out_size) {
  static EncodeFn enc = nullptr;
  if (!enc) {
    cudaDriverEntryPointQueryResult qr;
    cudaGetDriverEntryPoint("cuTensorMapEncodeTiled", (void**)&enc, cudaEnableDefault, &qr);
    cudaFuncSetAttribute(gated_mix_kernel, cudaFuncAttributeMaxDynamicSharedMemorySize, SMEM_BYTES);
  }
  Maps m;
  {
    const cuuint64_t gd[2] = {640, 2048}, gs[1] = {1280};
    const cuuint32_t bx[2] = {64, 128}, bo[2] = {64, 64};
    encode(enc, &m.x, d_in[0], 2, gd, gs, bx);
    encode(enc, &m.out, d_out, 2, gd, gs, bo);
  }
  for (int b = 0; b < 2; b++) {
    const cuuint64_t gd[3] = {64, 640, 30}, gs[2] = {3840, 128}, gd3[3] = {64, 640, 10}, gs3[2] = {1280, 128};
    const cuuint32_t bd[3] = {64, 64, 4}, bd3[3] = {64, 64, 3};
    encode(enc, &m.w[b], d_in[b ? 4 : 1], 3, gd, gs, bd);
    encode(enc, &m.wo[b], d_in[b ? 6 : 2], 3, gd3, gs3, bd3);
  }
  {
    void* qp = nullptr;
    cudaGetSymbolAddress(&qp, g_qkv);
    const cuuint64_t gd[5] = {128, 80, 3, 2, 32}, gs[4] = {2048, QTY, 1024, QRB};
    const cuuint32_t bl[5] = {128, 3, 2, 2, 4}, bs[5] = {128, 8, 1, 1, 1}, es[5] = {1, 1, 1, 1, 1};
    enc(&m.qld, CU_TENSOR_MAP_DATA_TYPE_UINT64, 5, qp, gd, gs, bl, es, CU_TENSOR_MAP_INTERLEAVE_NONE, CU_TENSOR_MAP_SWIZZLE_NONE, CU_TENSOR_MAP_L2_PROMOTION_L2_128B, CU_TENSOR_MAP_FLOAT_OOB_FILL_NONE);
    enc(&m.qst, CU_TENSOR_MAP_DATA_TYPE_UINT64, 5, qp, gd, gs, bs, es, CU_TENSOR_MAP_INTERLEAVE_NONE, CU_TENSOR_MAP_SWIZZLE_NONE, CU_TENSOR_MAP_L2_PROMOTION_NONE, CU_TENSOR_MAP_FLOAT_OOB_FILL_NONE);
  }
  gated_mix_kernel<<<128, 512, SMEM_BYTES, cudaStreamPerThread>>>(m, (const __nv_bfloat16*)d_in[0], (const __nv_bfloat16*)d_in[1], (const __nv_bfloat16*)d_in[5],
                                                                 (const __nv_bfloat16*)d_in[7], d_in[4], d_in[2], d_in[6], (uint4*)d_out);
}
```

```cpp
#include <cuda_runtime.h>
#include <cuda.h>
#include <cuda_bf16.h>
#include <cuda_fp16.h>
#include <stdint.h>
#pragma nv_diag_suppress 550

namespace {

constexpr int QRB = 240 * 2048;
constexpr int QBR = 16 * QRB;
constexpr int QTY = 80 * 2048;
constexpr int ORB = 160 * 2048;
constexpr int NMB = 3;

__device__ __align__(1024) uint8_t g_qkv[2 * QBR];
__device__ __align__(1024) uint8_t g_o[16 * ORB];
__device__ float g_gate[2048];
__device__ __align__(16) float g_kv[32 * 960];
__device__ uint32_t g_kbad;
__device__ uint32_t g_fb[128 * 2048 * 20];
__device__ uint32_t g_cnt[192];
constexpr int C_EPOCH = 0, C_TA = 32, C_TB = 64, C_KV = 96, C_OB = 128, C_OA = 160;

#define TS_MARK(i)
#define TS_INIT()
#define TS_FIRST()
#define TS_DUMP()

__device__ __forceinline__ uint64_t mkdesc(uint32_t addr, uint32_t lbo, uint32_t sbo, int mode) {
  return (uint64_t)((addr & 0x3FFFF) >> 4) | ((uint64_t)(lbo >> 4) << 16) | ((uint64_t)(sbo >> 4) << 32) | ((uint64_t)mode << 62);
}
__device__ __forceinline__ uint64_t desc_lohi(uint32_t lo, uint32_t hi) { return ((uint64_t)hi << 32) | lo; }
#define WG_FENCE() asm volatile("wgmma.fence.sync.aligned;" ::: "memory")
#define WG_COMMIT() asm volatile("wgmma.commit_group.sync.aligned;" ::: "memory")
#define WG_WAIT(n) asm volatile("wgmma.wait_group.sync.aligned %0;" ::"n"(n) : "memory")
#define PROXY_FENCE() asm volatile("fence.proxy.async.shared::cta;" ::: "memory")
#define PROXY_FENCE_G() asm volatile("fence.proxy.async.global;" ::: "memory")
__device__ __forceinline__ void bar_sync(int id, int n) { asm volatile("bar.sync %0, %1;" ::"r"(id), "r"(n) : "memory"); }
__device__ __forceinline__ void mbar_init(uint32_t a, int c) { asm volatile("mbarrier.init.shared::cta.b64 [%0], %1;" ::"r"(a), "r"(c)); }
__device__ __forceinline__ uint32_t mbar_try(uint32_t a, int par) {
  uint32_t ok;
  asm volatile("{.reg .pred p; mbarrier.try_wait.parity.shared::cta.b64 p, [%1], %2; selp.b32 %0, 1, 0, p;}" : "=r"(ok) : "r"(a), "r"(par) : "memory");
  return ok;
}
__device__ __forceinline__ void mbar_wait(uint32_t a, int par) {
  for (int i = 0; !mbar_try(a, par); i++)
    if (i > (1 << 22)) break;
}
__device__ __forceinline__ void mbar_arrive(uint32_t a) { asm volatile("mbarrier.arrive.shared::cta.b64 _, [%0];" ::"r"(a) : "memory"); }
__device__ __forceinline__ void mbar_arrive_if(bool p, uint32_t a) {
  asm volatile("{.reg .pred p; setp.ne.b32 p, %0, 0; @p mbarrier.arrive.shared::cta.b64 _, [%1];}" ::"r"((int)p), "r"(a) : "memory");
}
__device__ __forceinline__ void mbar_expect_if(bool p, uint32_t a, int bytes) {
  asm volatile("{.reg .pred p; setp.ne.b32 p, %0, 0; @p mbarrier.arrive.expect_tx.shared::cta.b64 _, [%1], %2;}" ::"r"((int)p), "r"(a), "r"(bytes) : "memory");
}
__device__ __forceinline__ void tma2d_if(bool p, uint32_t dst, const CUtensorMap* m, int c0, int c1, uint32_t bar) {
  asm volatile("{.reg .pred p; setp.ne.b32 p, %0, 0; @p cp.async.bulk.tensor.2d.shared::cluster.global.mbarrier::complete_tx::bytes [%1], [%2, {%4, %5}], [%3];}"
               ::"r"((int)p), "r"(dst), "l"(m), "r"(bar), "r"(c0), "r"(c1) : "memory");
}
__device__ __forceinline__ void tma3d_if(bool p, uint32_t dst, const CUtensorMap* m, int c1, int c2, uint32_t bar) {
  asm volatile("{.reg .pred p; setp.ne.b32 p, %0, 0; @p cp.async.bulk.tensor.3d.shared::cluster.global.mbarrier::complete_tx::bytes [%1], [%2, {%6, %4, %5}], [%3];}"
               ::"r"((int)p), "r"(dst), "l"(m), "r"(bar), "r"(c1), "r"(c2), "r"(0) : "memory");
}
__device__ __forceinline__ void bulk_g2s_if(bool p, uint32_t dst, const void* src, int bytes, uint32_t bar) {
  asm volatile("{.reg .pred p; setp.ne.b32 p, %0, 0; @p cp.async.bulk.shared::cluster.global.mbarrier::complete_tx::bytes [%1], [%2], %3, [%4];}"
               ::"r"((int)p), "r"(dst), "l"(src), "r"(bytes), "r"(bar) : "memory");
}
__device__ __forceinline__ void tma5d_if(bool p, uint32_t dst, const CUtensorMap* m, int c1, int c2, int c4, uint32_t bar) {
  asm volatile("{.reg .pred p; setp.ne.b32 p, %0, 0; @p cp.async.bulk.tensor.5d.shared::cluster.global.mbarrier::complete_tx::bytes [%1], [%2, {%7, %4, %5, %7, %6}], [%3];}"
               ::"r"((int)p), "r"(dst), "l"(m), "r"(bar), "r"(c1), "r"(c2), "r"(c4), "r"(0) : "memory");
}
__device__ __forceinline__ void tma5d_store_if(bool p, const CUtensorMap* m, uint32_t src, int c1, int c2, int c3, int c4) {
  asm volatile("{.reg .pred p; setp.ne.b32 p, %0, 0; @p cp.async.bulk.tensor.5d.global.shared::cta.bulk_group [%1, {%7, %3, %4, %5, %6}], [%2];}"
               ::"r"((int)p), "l"(m), "r"(src), "r"(c1), "r"(c2), "r"(c3), "r"(c4), "r"(0) : "memory");
}
__device__ __forceinline__ void bulk_s2g_if(bool p, void* dst, uint32_t src, int bytes) {
  asm volatile("{.reg .pred p; setp.ne.b32 p, %0, 0; @p cp.async.bulk.global.shared::cta.bulk_group [%1], [%2], %3;}" ::"r"((int)p), "l"(dst), "r"(src), "r"(bytes) : "memory");
}
__device__ __forceinline__ void bulk_or_if(bool p, void* dst, uint32_t src, int bytes) {
  asm volatile("{.reg .pred p; setp.ne.b32 p, %0, 0; @p cp.reduce.async.bulk.global.shared::cta.bulk_group.or.b32 [%1], [%2], %3;}" ::"r"((int)p), "l"(dst), "r"(src), "r"(bytes) : "memory");
}
__device__ __forceinline__ void bulk_addf_if(bool p, void* dst, uint32_t src, int bytes) {
  asm volatile("{.reg .pred p; setp.ne.b32 p, %0, 0; @p cp.reduce.async.bulk.global.shared::cta.bulk_group.add.f32 [%1], [%2], %3;}" ::"r"((int)p), "l"(dst), "r"(src), "r"(bytes) : "memory");
}
#define BULK_COMMIT() asm volatile("cp.async.bulk.commit_group;" ::: "memory")
#define BULK_WAIT() asm volatile("cp.async.bulk.wait_group 0;" ::: "memory")
#define BULK_WAIT_READ() asm volatile("cp.async.bulk.wait_group.read 0;" ::: "memory")
__device__ __forceinline__ void signal_bulk_if(bool p, uint32_t* c) {
  asm volatile("{.reg .pred p; setp.ne.b32 p, %0, 0; cp.async.bulk.wait_group 0; @p red.relaxed.gpu.global.add.u32 [%1], 1;}" ::"r"((int)p), "l"(c) : "memory");
}
__device__ __forceinline__ void wait_count(const uint32_t* c, uint32_t target) {
  for (int i = 0;; i++) {
    uint32_t v;
    asm volatile("ld.relaxed.gpu.global.u32 %0, [%1];" : "=r"(v) : "l"(c) : "memory");
    if ((int)(v - target) >= 0) break;
    if (i > (1 << 20)) break;
  }
  PROXY_FENCE_G();
}
__device__ __forceinline__ uint32_t pack_bf16(float lo, float hi) { uint32_t r; asm("cvt.rn.bf16x2.f32 %0, %1, %2;" : "=r"(r) : "f"(hi), "f"(lo)); return r; }
__device__ __forceinline__ uint32_t pack_f16(float lo, float hi) { uint32_t r; asm("cvt.rn.f16x2.f32 %0, %1, %2;" : "=r"(r) : "f"(hi), "f"(lo)); return r; }
__device__ __forceinline__ float ex2(float a) { float r; asm("ex2.approx.ftz.f32 %0, %1;" : "=f"(r) : "f"(a)); return r; }
__device__ __forceinline__ float rcp(float a) { float r; asm("rcp.approx.ftz.f32 %0, %1;" : "=f"(r) : "f"(a)); return r; }
__device__ __forceinline__ uint32_t maxabs_bf16x2(uint32_t a, uint32_t b) { uint32_t r; asm("max.NaN.xorsign.abs.bf16x2 %0, %1, %2;" : "=r"(r) : "r"(a), "r"(b)); return r; }
__device__ __forceinline__ uint32_t ldg32(const void* p) { return __ldg(reinterpret_cast<const uint32_t*>(p)); }
__device__ __forceinline__ uint32_t ldcg32(const void* p) { uint32_t v; asm volatile("ld.global.cg.u32 %0, [%1];" : "=r"(v) : "l"(p) : "memory"); return v; }
__device__ __forceinline__ uint32_t lds32(uint32_t a) { uint32_t v; asm volatile("ld.shared.b32 %0, [%1];" : "=r"(v) : "r"(a) : "memory"); return v; }
__device__ __forceinline__ void sts32(uint32_t a, uint32_t v) { asm volatile("st.shared.b32 [%0], %1;" ::"r"(a), "r"(v) : "memory"); }
__device__ __forceinline__ void sts16(uint32_t a, uint16_t v) { asm volatile("st.shared.b16 [%0], %1;" ::"r"(a), "h"(v) : "memory"); }
__device__ __forceinline__ void stsm4(uint32_t a, uint32_t r0, uint32_t r1, uint32_t r2, uint32_t r3) {
  asm volatile("stmatrix.sync.aligned.m8n8.x4.shared.b16 [%0], {%1, %2, %3, %4};" ::"r"(a), "r"(r0), "r"(r1), "r"(r2), "r"(r3) : "memory");
}
template <int N> __device__ __forceinline__ void pin(float (&d)[N]) {
#pragma unroll
  for (int i = 0; i < N; i++) asm volatile("" : "+f"(d[i])::"memory");
}

__device__ __forceinline__ void wg128_ss(float (&d)[64], uint64_t da, uint64_t db, int scale_d) {
  asm volatile("{\n.reg .pred p;\nsetp.ne.b32 p, %66, 0;\n"
    "wgmma.mma_async.sync.aligned.m64n128k16.f32.bf16.bf16 "
    "{%0, %1, %2, %3, %4, %5, %6, %7, %8, %9, %10, %11, %12, %13, %14, %15,"
    "%16, %17, %18, %19, %20, %21, %22, %23, %24, %25, %26, %27, %28, %29, %30, %31,"
    "%32, %33, %34, %35, %36, %37, %38, %39, %40, %41, %42, %43, %44, %45, %46, %47,"
    "%48, %49, %50, %51, %52, %53, %54, %55, %56, %57, %58, %59, %60, %61, %62, %63}, "
    "%64, %65, p, 1, 1, 0, 1;\n}\n"
    : "+f"(d[0]), "+f"(d[1]), "+f"(d[2]), "+f"(d[3]), "+f"(d[4]), "+f"(d[5]), "+f"(d[6]), "+f"(d[7]),
      "+f"(d[8]), "+f"(d[9]), "+f"(d[10]), "+f"(d[11]), "+f"(d[12]), "+f"(d[13]), "+f"(d[14]), "+f"(d[15]),
      "+f"(d[16]), "+f"(d[17]), "+f"(d[18]), "+f"(d[19]), "+f"(d[20]), "+f"(d[21]), "+f"(d[22]), "+f"(d[23]),
      "+f"(d[24]), "+f"(d[25]), "+f"(d[26]), "+f"(d[27]), "+f"(d[28]), "+f"(d[29]), "+f"(d[30]), "+f"(d[31]),
      "+f"(d[32]), "+f"(d[33]), "+f"(d[34]), "+f"(d[35]), "+f"(d[36]), "+f"(d[37]), "+f"(d[38]), "+f"(d[39]),
      "+f"(d[40]), "+f"(d[41]), "+f"(d[42]), "+f"(d[43]), "+f"(d[44]), "+f"(d[45]), "+f"(d[46]), "+f"(d[47]),
      "+f"(d[48]), "+f"(d[49]), "+f"(d[50]), "+f"(d[51]), "+f"(d[52]), "+f"(d[53]), "+f"(d[54]), "+f"(d[55]),
      "+f"(d[56]), "+f"(d[57]), "+f"(d[58]), "+f"(d[59]), "+f"(d[60]), "+f"(d[61]), "+f"(d[62]), "+f"(d[63])
    : "l"(da), "l"(db), "r"(scale_d));
}

__device__ __forceinline__ void wg64_ss_of64(float (&d)[64], uint64_t da, uint64_t db, int scale_d) {
  asm volatile("{\n.reg .pred p;\nsetp.ne.b32 p, %34, 0;\n"
    "wgmma.mma_async.sync.aligned.m64n64k16.f32.bf16.bf16 "
    "{%0, %1, %2, %3, %4, %5, %6, %7, %8, %9, %10, %11, %12, %13, %14, %15,"
    "%16, %17, %18, %19, %20, %21, %22, %23, %24, %25, %26, %27, %28, %29, %30, %31}, "
    "%32, %33, p, 1, 1, 0, 1;\n}\n"
    : "+f"(d[0]), "+f"(d[1]), "+f"(d[2]), "+f"(d[3]), "+f"(d[4]), "+f"(d[5]), "+f"(d[6]), "+f"(d[7]),
      "+f"(d[8]), "+f"(d[9]), "+f"(d[10]), "+f"(d[11]), "+f"(d[12]), "+f"(d[13]), "+f"(d[14]), "+f"(d[15]),
      "+f"(d[16]), "+f"(d[17]), "+f"(d[18]), "+f"(d[19]), "+f"(d[20]), "+f"(d[21]), "+f"(d[22]), "+f"(d[23]),
      "+f"(d[24]), "+f"(d[25]), "+f"(d[26]), "+f"(d[27]), "+f"(d[28]), "+f"(d[29]), "+f"(d[30]), "+f"(d[31])
    : "l"(da), "l"(db), "r"(scale_d));
}

__device__ __forceinline__ void wg192_ss(float (&d)[96], uint64_t da, uint64_t db, int scale_d) {
  asm volatile("{\n.reg .pred p;\nsetp.ne.b32 p, %98, 0;\n"
    "wgmma.mma_async.sync.aligned.m64n192k16.f32.bf16.bf16 "
    "{%0, %1, %2, %3, %4, %5, %6, %7, %8, %9, %10, %11, %12, %13, %14, %15,"
    "%16, %17, %18, %19, %20, %21, %22, %23, %24, %25, %26, %27, %28, %29, %30, %31,"
    "%32, %33, %34, %35, %36, %37, %38, %39, %40, %41, %42, %43, %44, %45, %46, %47,"
    "%48, %49, %50, %51, %52, %53, %54, %55, %56, %57, %58, %59, %60, %61, %62, %63,"
    "%64, %65, %66, %67, %68, %69, %70, %71, %72, %73, %74, %75, %76, %77, %78, %79,"
    "%80, %81, %82, %83, %84, %85, %86, %87, %88, %89, %90, %91, %92, %93, %94, %95}, "
    "%96, %97, p, 1, 1, 0, 1;\n}\n"
    : "+f"(d[0]), "+f"(d[1]), "+f"(d[2]), "+f"(d[3]), "+f"(d[4]), "+f"(d[5]), "+f"(d[6]), "+f"(d[7]),
      "+f"(d[8]), "+f"(d[9]), "+f"(d[10]), "+f"(d[11]), "+f"(d[12]), "+f"(d[13]), "+f"(d[14]), "+f"(d[15]),
      "+f"(d[16]), "+f"(d[17]), "+f"(d[18]), "+f"(d[19]), "+f"(d[20]), "+f"(d[21]), "+f"(d[22]), "+f"(d[23]),
      "+f"(d[24]), "+f"(d[25]), "+f"(d[26]), "+f"(d[27]), "+f"(d[28]), "+f"(d[29]), "+f"(d[30]), "+f"(d[31]),
      "+f"(d[32]), "+f"(d[33]), "+f"(d[34]), "+f"(d[35]), "+f"(d[36]), "+f"(d[37]), "+f"(d[38]), "+f"(d[39]),
      "+f"(d[40]), "+f"(d[41]), "+f"(d[42]), "+f"(d[43]), "+f"(d[44]), "+f"(d[45]), "+f"(d[46]), "+f"(d[47]),
      "+f"(d[48]), "+f"(d[49]), "+f"(d[50]), "+f"(d[51]), "+f"(d[52]), "+f"(d[53]), "+f"(d[54]), "+f"(d[55]),
      "+f"(d[56]), "+f"(d[57]), "+f"(d[58]), "+f"(d[59]), "+f"(d[60]), "+f"(d[61]), "+f"(d[62]), "+f"(d[63]),
      "+f"(d[64]), "+f"(d[65]), "+f"(d[66]), "+f"(d[67]), "+f"(d[68]), "+f"(d[69]), "+f"(d[70]), "+f"(d[71]),
      "+f"(d[72]), "+f"(d[73]), "+f"(d[74]), "+f"(d[75]), "+f"(d[76]), "+f"(d[77]), "+f"(d[78]), "+f"(d[79]),
      "+f"(d[80]), "+f"(d[81]), "+f"(d[82]), "+f"(d[83]), "+f"(d[84]), "+f"(d[85]), "+f"(d[86]), "+f"(d[87]),
      "+f"(d[88]), "+f"(d[89]), "+f"(d[90]), "+f"(d[91]), "+f"(d[92]), "+f"(d[93]), "+f"(d[94]), "+f"(d[95])
    : "l"(da), "l"(db), "r"(scale_d));
}

__device__ __forceinline__ void wg128_ss_of96(float (&d)[96], uint64_t da, uint64_t db, int scale_d) {
  asm volatile("{\n.reg .pred p;\nsetp.ne.b32 p, %66, 0;\n"
    "wgmma.mma_async.sync.aligned.m64n128k16.f32.bf16.bf16 "
    "{%0, %1, %2, %3, %4, %5, %6, %7, %8, %9, %10, %11, %12, %13, %14, %15,"
    "%16, %17, %18, %19, %20, %21, %22, %23, %24, %25, %26, %27, %28, %29, %30, %31,"
    "%32, %33, %34, %35, %36, %37, %38, %39, %40, %41, %42, %43, %44, %45, %46, %47,"
    "%48, %49, %50, %51, %52, %53, %54, %55, %56, %57, %58, %59, %60, %61, %62, %63}, "
    "%64, %65, p, 1, 1, 0, 1;\n}\n"
    : "+f"(d[0]), "+f"(d[1]), "+f"(d[2]), "+f"(d[3]), "+f"(d[4]), "+f"(d[5]), "+f"(d[6]), "+f"(d[7]),
      "+f"(d[8]), "+f"(d[9]), "+f"(d[10]), "+f"(d[11]), "+f"(d[12]), "+f"(d[13]), "+f"(d[14]), "+f"(d[15]),
      "+f"(d[16]), "+f"(d[17]), "+f"(d[18]), "+f"(d[19]), "+f"(d[20]), "+f"(d[21]), "+f"(d[22]), "+f"(d[23]),
      "+f"(d[24]), "+f"(d[25]), "+f"(d[26]), "+f"(d[27]), "+f"(d[28]), "+f"(d[29]), "+f"(d[30]), "+f"(d[31]),
      "+f"(d[32]), "+f"(d[33]), "+f"(d[34]), "+f"(d[35]), "+f"(d[36]), "+f"(d[37]), "+f"(d[38]), "+f"(d[39]),
      "+f"(d[40]), "+f"(d[41]), "+f"(d[42]), "+f"(d[43]), "+f"(d[44]), "+f"(d[45]), "+f"(d[46]), "+f"(d[47]),
      "+f"(d[48]), "+f"(d[49]), "+f"(d[50]), "+f"(d[51]), "+f"(d[52]), "+f"(d[53]), "+f"(d[54]), "+f"(d[55]),
      "+f"(d[56]), "+f"(d[57]), "+f"(d[58]), "+f"(d[59]), "+f"(d[60]), "+f"(d[61]), "+f"(d[62]), "+f"(d[63])
    : "l"(da), "l"(db), "r"(scale_d));
}

__device__ __forceinline__ void wg64_rs_bf16(float (&d)[32], uint32_t a0, uint32_t a1, uint32_t a2, uint32_t a3, uint64_t db, int scale_d) {
  asm volatile("{\n.reg .pred p;\nsetp.ne.b32 p, %37, 0;\n"
    "wgmma.mma_async.sync.aligned.m64n64k16.f32.bf16.bf16 "
    "{%0, %1, %2, %3, %4, %5, %6, %7, %8, %9, %10, %11, %12, %13, %14, %15,"
    "%16, %17, %18, %19, %20, %21, %22, %23, %24, %25, %26, %27, %28, %29, %30, %31}, "
    "{%32, %33, %34, %35}, %36, p, 1, 1, 0;\n}\n"
    : "+f"(d[0]), "+f"(d[1]), "+f"(d[2]), "+f"(d[3]), "+f"(d[4]), "+f"(d[5]), "+f"(d[6]), "+f"(d[7]),
      "+f"(d[8]), "+f"(d[9]), "+f"(d[10]), "+f"(d[11]), "+f"(d[12]), "+f"(d[13]), "+f"(d[14]), "+f"(d[15]),
      "+f"(d[16]), "+f"(d[17]), "+f"(d[18]), "+f"(d[19]), "+f"(d[20]), "+f"(d[21]), "+f"(d[22]), "+f"(d[23]),
      "+f"(d[24]), "+f"(d[25]), "+f"(d[26]), "+f"(d[27]), "+f"(d[28]), "+f"(d[29]), "+f"(d[30]), "+f"(d[31])
    : "r"(a0), "r"(a1), "r"(a2), "r"(a3), "l"(db), "r"(scale_d));
}

__device__ __forceinline__ void wg24_rs_f16_t(float (&d)[12], uint32_t a0, uint32_t a1, uint32_t a2, uint32_t a3, uint64_t db, int scale_d) {
  asm volatile("{\n.reg .pred p;\nsetp.ne.b32 p, %17, 0;\n"
    "wgmma.mma_async.sync.aligned.m64n24k16.f32.f16.f16 "
    "{%0, %1, %2, %3, %4, %5, %6, %7, %8, %9, %10, %11}, "
    "{%12, %13, %14, %15}, %16, p, 1, 1, 1;\n}\n"
    : "+f"(d[0]), "+f"(d[1]), "+f"(d[2]), "+f"(d[3]), "+f"(d[4]), "+f"(d[5]), "+f"(d[6]), "+f"(d[7]),
      "+f"(d[8]), "+f"(d[9]), "+f"(d[10]), "+f"(d[11])
    : "r"(a0), "r"(a1), "r"(a2), "r"(a3), "l"(db), "r"(scale_d));
}

__device__ __forceinline__ void wg24_rs_bf16(float (&d)[12], uint32_t a0, uint32_t a1, uint32_t a2, uint32_t a3, uint64_t db, int scale_d) {
  asm volatile("{\n.reg .pred p;\nsetp.ne.b32 p, %17, 0;\n"
    "wgmma.mma_async.sync.aligned.m64n24k16.f32.bf16.bf16 "
    "{%0, %1, %2, %3, %4, %5, %6, %7, %8, %9, %10, %11}, "
    "{%12, %13, %14, %15}, %16, p, 1, 1, 0;\n}\n"
    : "+f"(d[0]), "+f"(d[1]), "+f"(d[2]), "+f"(d[3]), "+f"(d[4]), "+f"(d[5]), "+f"(d[6]), "+f"(d[7]),
      "+f"(d[8]), "+f"(d[9]), "+f"(d[10]), "+f"(d[11])
    : "r"(a0), "r"(a1), "r"(a2), "r"(a3), "l"(db), "r"(scale_d));
}

__device__ __forceinline__ void wg24_ss_bf16_tt(float (&d)[12], uint64_t da, uint64_t db, int scale_d) {
  asm volatile("{\n.reg .pred p;\nsetp.ne.b32 p, %14, 0;\n"
    "wgmma.mma_async.sync.aligned.m64n24k16.f32.bf16.bf16 "
    "{%0, %1, %2, %3, %4, %5, %6, %7, %8, %9, %10, %11}, "
    "%12, %13, p, 1, 1, 1, 1;\n}\n"
    : "+f"(d[0]), "+f"(d[1]), "+f"(d[2]), "+f"(d[3]), "+f"(d[4]), "+f"(d[5]), "+f"(d[6]), "+f"(d[7]),
      "+f"(d[8]), "+f"(d[9]), "+f"(d[10]), "+f"(d[11])
    : "l"(da), "l"(db), "r"(scale_d));
}

__device__ __forceinline__ void wg64_rs_bf16_i(float (&d)[32], uint32_t a0, uint32_t a1, uint32_t a2, uint32_t a3, uint64_t db) {
  asm volatile("{\n.reg .pred p;\nsetp.ne.b32 p, 0, 0;\n"
    "wgmma.mma_async.sync.aligned.m64n64k16.f32.bf16.bf16 "
    "{%0, %1, %2, %3, %4, %5, %6, %7, %8, %9, %10, %11, %12, %13, %14, %15,"
    "%16, %17, %18, %19, %20, %21, %22, %23, %24, %25, %26, %27, %28, %29, %30, %31}, "
    "{%32, %33, %34, %35}, %36, p, 1, 1, 0;\n}\n"
    : "=f"(d[0]), "=f"(d[1]), "=f"(d[2]), "=f"(d[3]), "=f"(d[4]), "=f"(d[5]), "=f"(d[6]), "=f"(d[7]),
      "=f"(d[8]), "=f"(d[9]), "=f"(d[10]), "=f"(d[11]), "=f"(d[12]), "=f"(d[13]), "=f"(d[14]), "=f"(d[15]),
      "=f"(d[16]), "=f"(d[17]), "=f"(d[18]), "=f"(d[19]), "=f"(d[20]), "=f"(d[21]), "=f"(d[22]), "=f"(d[23]),
      "=f"(d[24]), "=f"(d[25]), "=f"(d[26]), "=f"(d[27]), "=f"(d[28]), "=f"(d[29]), "=f"(d[30]), "=f"(d[31])
    : "r"(a0), "r"(a1), "r"(a2), "r"(a3), "l"(db));
}

__device__ __forceinline__ void wg24_rs_bf16_i(float (&d)[12], uint32_t a0, uint32_t a1, uint32_t a2, uint32_t a3, uint64_t db) {
  asm volatile("{\n.reg .pred p;\nsetp.ne.b32 p, 0, 0;\n"
    "wgmma.mma_async.sync.aligned.m64n24k16.f32.bf16.bf16 "
    "{%0, %1, %2, %3, %4, %5, %6, %7, %8, %9, %10, %11}, "
    "{%12, %13, %14, %15}, %16, p, 1, 1, 0;\n}\n"
    : "=f"(d[0]), "=f"(d[1]), "=f"(d[2]), "=f"(d[3]), "=f"(d[4]), "=f"(d[5]), "=f"(d[6]), "=f"(d[7]),
      "=f"(d[8]), "=f"(d[9]), "=f"(d[10]), "=f"(d[11])
    : "r"(a0), "r"(a1), "r"(a2), "r"(a3), "l"(db));
}

__device__ __forceinline__ void wg24_ss_bf16_tt_i(float (&d)[12], uint64_t da, uint64_t db) {
  asm volatile("{\n.reg .pred p;\nsetp.ne.b32 p, 0, 0;\n"
    "wgmma.mma_async.sync.aligned.m64n24k16.f32.bf16.bf16 "
    "{%0, %1, %2, %3, %4, %5, %6, %7, %8, %9, %10, %11}, "
    "%12, %13, p, 1, 1, 1, 1;\n}\n"
    : "=f"(d[0]), "=f"(d[1]), "=f"(d[2]), "=f"(d[3]), "=f"(d[4]), "=f"(d[5]), "=f"(d[6]), "=f"(d[7]),
      "=f"(d[8]), "=f"(d[9]), "=f"(d[10]), "=f"(d[11])
    : "l"(da), "l"(db));
}

__device__ __forceinline__ void wg24_ss_bf16(float (&d)[12], uint64_t da, uint64_t db, int scale_d) {
  asm volatile("{\n.reg .pred p;\nsetp.ne.b32 p, %14, 0;\n"
    "wgmma.mma_async.sync.aligned.m64n24k16.f32.bf16.bf16 "
    "{%0, %1, %2, %3, %4, %5, %6, %7, %8, %9, %10, %11}, "
    "%12, %13, p, 1, 1, 0, 0;\n}\n"
    : "+f"(d[0]), "+f"(d[1]), "+f"(d[2]), "+f"(d[3]), "+f"(d[4]), "+f"(d[5]), "+f"(d[6]), "+f"(d[7]),
      "+f"(d[8]), "+f"(d[9]), "+f"(d[10]), "+f"(d[11])
    : "l"(da), "l"(db), "r"(scale_d));
}

__device__ __forceinline__ void wg24_ss_bf16_i(float (&d)[12], uint64_t da, uint64_t db) {
  asm volatile("{\n.reg .pred p;\nsetp.ne.b32 p, 0, 0;\n"
    "wgmma.mma_async.sync.aligned.m64n24k16.f32.bf16.bf16 "
    "{%0, %1, %2, %3, %4, %5, %6, %7, %8, %9, %10, %11}, "
    "%12, %13, p, 1, 1, 0, 0;\n}\n"
    : "=f"(d[0]), "=f"(d[1]), "=f"(d[2]), "=f"(d[3]), "=f"(d[4]), "=f"(d[5]), "=f"(d[6]), "=f"(d[7]),
      "=f"(d[8]), "=f"(d[9]), "=f"(d[10]), "=f"(d[11])
    : "l"(da), "l"(db));
}

constexpr int P1_STB = 49152, P3_STB = 40960;
constexpr int SM_X = 196608;
constexpr int SM_KVB = SM_X + 24576;
constexpr int SM_GW = SM_X + 8192, SM_WRAW = SM_GW + 1280, SM_EP = SM_WRAW + 800;
constexpr int SM_CONST = SM_X + 32768, SM_WPHI = SM_CONST + 1024, SM_BAR = SM_WPHI + 1536;
constexpr int SMEM_BYTES = SM_BAR + 512;
constexpr int B_FULL = 0, B_EMPTY = 4, B_AUX = 8, B_ZERO = 9, B_KB = 10, B_QB = 11, B_LINK = 12, B_KVB = 14, B_FREE = 15, B_KVFULL = 18, B_READY = 22, B_P3FULL = 26, B_P3EMPTY = 30;

template <int V> struct Int { static constexpr int value = V; };
struct Maps { CUtensorMap x, w[2], wo[2], out, qld, qst; };

__device__ __forceinline__ int tile_atom(int t) { return (t >> 2) * 15 + ((0xB740 >> ((t & 3) * 4)) & 15); }

template <int MODE, int A>
__device__ __forceinline__ void pack_atom(const float (&acc)[64], uint32_t (&r)[32], float s0, float s1, uint32_t& m0, uint32_t& m1) {
#pragma unroll
  for (int e = A * 16; e < A * 16 + 16; e++) {
    const float s = (e & 1) ? s1 : s0;
    if (MODE == 0) r[e] = pack_bf16(acc[2 * e], acc[2 * e + 1]);
    else if (MODE == 3) r[e] = pack_f16(acc[2 * e], acc[2 * e + 1]);
    else r[e] = pack_bf16(acc[2 * e] * s, acc[2 * e + 1] * s);
    if (MODE == 2) { if (e & 1) m1 = maxabs_bf16x2(m1, r[e]); else m0 = maxabs_bf16x2(m0, r[e]); }
  }
}
template <int A>
__device__ __forceinline__ void pack_atom_a(const float (&acc)[64], uint32_t (&r)[32], int ga, float sk0, float sk1, uint32_t& m0, uint32_t& m1) {
  if (ga < 10) { const float cq = __uint_as_float(463809372u); pack_atom<1, A>(acc, r, cq, cq, m0, m1); }
  else if (ga < 20) pack_atom<2, A>(acc, r, sk0, sk1, m0, m1);
  else pack_atom<3, A>(acc, r, 0.f, 0.f, m0, m1);
}

__device__ __forceinline__ uint32_t exp2_pair(float a, float b) {
  uint32_t z, w, h;
  asm volatile("cvt.pack.sat.s16.s32 %0, %2, %1;" : "=r"(z) : "r"(__float_as_uint(a)), "r"(__float_as_uint(b)));
  asm volatile("lop3.b32 %0, %1, 0x03ff03ff, 0x34003400, 0xEA;" : "=r"(w) : "r"(z));
  asm volatile("fma.rn.f16x2 %0, %1, %1, %2;" : "=r"(h) : "r"(w), "r"(0x36203620));
  asm volatile("fma.rn.f16x2 %0, %0, %1, %2;" : "+r"(h) : "r"(w), "r"(0x2e012e01));
  return h + z - w;
}
__device__ __forceinline__ uint32_t exp2_pair_mufu(float a, float b) {
  float x, y; uint32_t r;
  asm volatile("ex2.approx.ftz.f32 %0, %1;" : "=f"(x) : "f"(a));
  asm volatile("ex2.approx.ftz.f32 %0, %1;" : "=f"(y) : "f"(b));
  asm volatile("cvt.rn.f16x2.f32 %0, %1, %2;" : "=r"(r) : "f"(y), "f"(x));
  return r;
}
__device__ __forceinline__ void load_frag(uint32_t (&a)[6], const uint8_t* p) {
  a[0] = ldcg32(p); a[1] = ldcg32(p + 128); a[2] = ldcg32(p + 2048); a[3] = ldcg32(p + 2048 + 128); a[4] = ldcg32(p + 4096); a[5] = ldcg32(p + 4096 + 128);
}
__device__ __forceinline__ void feature_map(uint32_t (&phi)[10], const float (&p)[12]) {
  const float L = 1.4426950408889634f;
#pragma unroll
  for (int r = 0; r < 2; r++) {
    const float v[5] = {p[2 * r], p[2 * r + 1], p[4 + 2 * r], p[5 + 2 * r], p[8 + 2 * r]};
    float mx = fmaxf(fmaxf(fmaxf(v[0], v[1]), fmaxf(v[2], v[3])), v[4]);
    float mn = fminf(fminf(fminf(v[0], v[1]), fminf(v[2], v[3])), v[4]);
    mx = fmaxf(mx, __shfl_xor_sync(0xffffffffu, mx, 1)); mn = fminf(mn, __shfl_xor_sync(0xffffffffu, mn, 1));
    mx = fmaxf(mx, __shfl_xor_sync(0xffffffffu, mx, 2)); mn = fminf(mn, __shfl_xor_sync(0xffffffffu, mn, 2));
    const float mxl = -mx * L, mnl = mn * L;
    float ep[5], en[5];
#pragma unroll
    for (int i = 0; i < 5; i++) { ep[i] = ex2(fmaf(v[i], L, mxl)); en[i] = ex2(fmaf(v[i], -L, mnl)); }
    float sp = (ep[0] + ep[1]) + (ep[2] + ep[3]) + ep[4], sn = (en[0] + en[1]) + (en[2] + en[3]) + en[4];
    sp += __shfl_xor_sync(0xffffffffu, sp, 1); sn += __shfl_xor_sync(0xffffffffu, sn, 1);
    sp += __shfl_xor_sync(0xffffffffu, sp, 2); sn += __shfl_xor_sync(0xffffffffu, sn, 2);
    const float rp = rcp(sp), rn = rcp(sn);
#pragma unroll
    for (int i = 0; i < 5; i++) phi[5 * r + i] = pack_bf16(ep[i] * rp, en[i] * rn);
  }
}
__device__ __forceinline__ void phi_proj(float (&p0)[12], float (&p1)[12], uint32_t a, uint64_t dw) {
  const uint64_t da = mkdesc(a, 1024, 128, 0), db = mkdesc(a + 2048, 0, 128, 0);
  WG_FENCE();
  wg24_ss_bf16_i(p0, da, dw);
  wg24_ss_bf16(p0, db, dw + 48, 1);
  wg24_ss_bf16_i(p1, da + 384, dw);
  wg24_ss_bf16(p1, db + 384, dw + 48, 1);
  WG_COMMIT();
  WG_WAIT(0);
  pin(p0); pin(p1);
}
__device__ __forceinline__ void stage_o(const float (&o)[12], float s0, float s1, uint32_t a, bool v0, bool v2) {
#pragma unroll
  for (int j = 0; j < 3; j++) {
    const bool v = j == 1 || (j == 0 ? v0 : v2);
    sts32(a + j * 2048, v ? pack_bf16(o[4 * j] * s0, o[4 * j + 1] * s0) : 0u);
    sts32(a + j * 2048 + 128, v ? pack_bf16(o[4 * j + 2] * s1, o[4 * j + 3] * s1) : 0u);
  }
}
__device__ __forceinline__ void flush_o(bool p, uint8_t* dst, uint32_t src, bool odd) {
  bulk_s2g_if(p, dst + (odd ? 2048 : 0), src + (odd ? 2048 : 0), 4096);
  bulk_or_if(p, dst + (odd ? 0 : 4096), src + (odd ? 0 : 4096), 2048);
  BULK_COMMIT();
}

__device__ __forceinline__ void proj20(float (&acc)[20], const __nv_bfloat16* __restrict__ xr, const __nv_bfloat16* __restrict__ wc) {
#pragma unroll
  for (int d = 0; d < 20; d++) acc[d] = 0.f;
#pragma unroll 2
  for (int k = 0; k < 640; k++) {
    const float xv = __bfloat162float(xr[k]);
#pragma unroll
    for (int d = 0; d < 10; d++) {
      const uint32_t u = ldg32(wc + k * 1920 + 2 * d);
      acc[2 * d] = fmaf(xv, __uint_as_float(u << 16), acc[2 * d]);
      acc[2 * d + 1] = fmaf(xv, __uint_as_float(u & 0xffff0000u), acc[2 * d + 1]);
    }
  }
}
__device__ __noinline__ void attn_exact(const __nv_bfloat16* __restrict__ x, const __nv_bfloat16* __restrict__ wqkv, int h, int qt, uint32_t stg) {
  const int tid = threadIdx.x;
  uint32_t* kvs = g_fb + blockIdx.x * (2048 * 20);
  float a[20];
  for (int i = 0; i < 8; i++) {
    const int key = (i >> 1) * 512 + tid, ty = 1 + (i & 1);
    proj20(a, x + key * 640, wqkv + ty * 640 + h * 20);
#pragma unroll
    for (int d = 0; d < 10; d++) kvs[key * 20 + (i & 1) * 10 + d] = pack_bf16(a[2 * d], a[2 * d + 1]);
  }
  const int row = qt * 512 + tid;
  proj20(a, x + row * 640, wqkv + h * 20);
#pragma unroll
  for (int d = 0; d < 20; d++) a[d] = __bfloat162float(__float2bfloat16(a[d]));
  __syncthreads();
  float o[20], m = -INFINITY, l = 0.f;
#pragma unroll
  for (int d = 0; d < 20; d++) o[d] = 0.f;
  for (int key = 0; key < 2048; key++) {
    uint32_t u[20];
#pragma unroll
    for (int d = 0; d < 5; d++) {
      const uint4 t4 = *reinterpret_cast<const uint4*>(kvs + key * 20 + 4 * d);
      u[4 * d] = t4.x; u[4 * d + 1] = t4.y; u[4 * d + 2] = t4.z; u[4 * d + 3] = t4.w;
    }
    float s = 0.f;
#pragma unroll
    for (int d = 0; d < 10; d++) {
      s = fmaf(a[2 * d], __uint_as_float(u[d] << 16), s);
      s = fmaf(a[2 * d + 1], __uint_as_float(u[d] & 0xffff0000u), s);
    }
    s *= 0.22360679774997896f;
    const float mn = fmaxf(m, s), cr = __expf(m - mn), p = __expf(s - mn);
    m = mn;
    l = l * cr + p;
#pragma unroll
    for (int d = 0; d < 10; d++) {
      o[2 * d] = fmaf(p, __uint_as_float(u[10 + d] << 16), o[2 * d] * cr);
      o[2 * d + 1] = fmaf(p, __uint_as_float(u[10 + d] & 0xffff0000u), o[2 * d + 1] * cr);
    }
  }
  const float sc = __ldcg(&g_gate[row]) / l;
#pragma unroll
  for (int d = 0; d < 10; d++) {
    const int col = (h & 1) * 4 + 2 * d;
    sts32(stg + (tid >> 7) * 6144 + (col >> 3) * 2048 + (tid & 127) * 16 + (col & 7) * 2, pack_bf16(o[2 * d] * sc, o[2 * d + 1] * sc));
  }
  PROXY_FENCE();
  __syncthreads();
}

#define COORDS()                                                                                                        \
  int tid, bid;                                                                                                         \
  asm volatile("mov.u32 %0, %%tid.x;" : "=r"(tid));                                                                     \
  asm volatile("mov.u32 %0, %%ctaid.x;" : "=r"(bid));                                                                   \
  const int wg = __shfl_sync(0xffffffffu, tid >> 7, 0);                                                                 \
  const int lane = tid & 31, w = (tid >> 5) & 3, g = lane >> 2, t = lane & 3, wt = tid & 127;                           \
  const int rb1 = bid >> 3, c1 = bid & 7;                                       \
  const int h = bid >> 2, qt = bid & 3, rb = qt * 4 + wg;                    \
  const bool odd = h & 1;                                                                                               \
  const int c0 = (h * 5) >> 1;                                               \
  const int lsrc = (lane & ~3) | (odd ? 0 : 2);                                                                         \
  const bool v0 = !odd || t >= 2, v2 = odd || t < 2;                                                                    \
  const uint32_t ostg = sb + SM_X + wg * 6144, orow = (w * 16 + g) * 16 + t * 4;                                        \
  const int kh = bid & 1, cg = (bid >> 1) & 3, atom3 = (cg >> 1) * 5 + (cg & 1) * 2;                                    \
  auto p3_load_w = [&](bool p, int j) {                                                                                 \
    const uint32_t fb = bar + 8 * (B_P3FULL + (j & 3));                                                                 \
    mbar_expect_if(p, fb, P3_STB);                                                                                      \
    tma3d_if(p, sb + (j & 3) * P3_STB + 16384, &maps.wo[j < 5], (kh * 5 + (j < 5 ? j : j - 5)) * 64, atom3, fb);       \
  };                                                                                                                    \
  auto p3_load_a = [&](bool p, int j) {                                                                                 \
    bulk_g2s_if(p, sb + (j & 3) * P3_STB, g_o + rb1 * ORB + ((j < 5 ? 10 + j : j - 5) + kh * 5) * 16384, 16384,         \
                bar + 8 * (B_P3FULL + (j & 3)));                                                                        \
  };                                                                                                                    \
  (void)g; (void)t; (void)wt; (void)rb1; (void)c1; (void)rb; (void)c0; (void)lsrc; (void)v0; (void)v2; (void)ostg;      \
  (void)orow; (void)atom3; (void)p3_load_w; (void)p3_load_a

__global__ void __launch_bounds__(512, 1)
gated_mix_kernel(const __grid_constant__ Maps maps, const __nv_bfloat16* __restrict__ x, const __nv_bfloat16* __restrict__ wqkv, const __nv_bfloat16* __restrict__ w_phi,
                 const __nv_bfloat16* __restrict__ gate_w, const void* wqkv_b, const void* wo_a, const void* wo_b, uint4* __restrict__ out) {
  extern __shared__ __align__(1024) uint8_t smem_raw[];
  const uint32_t sb = (uint32_t)__cvta_generic_to_shared(smem_raw);
  const uint32_t bar = sb + SM_BAR;
  uint32_t q[2][6], qc[4], epoch, events;
  int bad;
  {
  COORDS();
  TS_INIT();

  auto p1_load = [&](bool p, int it) {
    const int st = it & 3, br = it >= 10, ks = it - br * 10;
    const uint32_t dst = sb + st * P1_STB, fb = bar + 8 * (B_FULL + st);
    mbar_expect_if(p, fb, P1_STB);
    tma2d_if(p, dst, &maps.x, ks * 64, rb1 * 128, fb);
    tma3d_if(p, dst + 16384, &maps.w[br], ks * 64, tile_atom(c1 ^ br), fb);
  };
  if (tid == 0) {
    if (sb & 1023) __trap();
    for (int i = 0; i < 4; i++) { mbar_init(bar + 8 * (B_FULL + i), 1); mbar_init(bar + 8 * (B_EMPTY + i), 4); }
    asm volatile("fence.mbarrier_init.release.cluster;" ::: "memory");
    for (int i = 0; i < 4; i++) p1_load(true, i);
  }
  if (tid == 32) {
    mbar_init(bar + 8 * B_AUX, 1); mbar_init(bar + 8 * B_ZERO, 16); mbar_init(bar + 8 * B_KB, 1); mbar_init(bar + 8 * B_QB, 1);
    mbar_init(bar + 8 * B_LINK, 4); mbar_init(bar + 8 * (B_LINK + 1), 4); mbar_init(bar + 8 * B_KVB, 128);
    for (int i = 0; i < 3; i++) mbar_init(bar + 8 * (B_FREE + i), 4);
    for (int i = 0; i < 4; i++) {
      mbar_init(bar + 8 * (B_KVFULL + i), 1); mbar_init(bar + 8 * (B_READY + i), i < 2 ? 512 : 128);
      mbar_init(bar + 8 * (B_P3FULL + i), 1); mbar_init(bar + 8 * (B_P3EMPTY + i), 2);
    }
    asm volatile("fence.mbarrier_init.release.cluster;" ::: "memory");
    mbar_expect_if(true, bar + 8 * B_AUX, 1280 + 800 + 16);
    bulk_g2s_if(true, sb + SM_GW, gate_w, 1280, bar + 8 * B_AUX);
    bulk_g2s_if(true, sb + SM_WRAW, w_phi + h * 400, 800, bar + 8 * B_AUX);
    bulk_g2s_if(true, sb + SM_EP, &g_cnt[C_EPOCH], 16, bar + 8 * B_AUX);
  }
  asm volatile("st.shared.v4.b32 [%0], {%1, %1, %1, %1};" ::"r"(sb + SM_X + tid * 16), "r"(0) : "memory");
  if (tid < 256) sts32(sb + SM_CONST + tid * 4, (tid & 3) ? 0u : ((tid >> 5) < NMB ? 0xdd02e192u : 0x00001ef0u));
  PROXY_FENCE();
  __syncthreads();
  TS_FIRST();
  TS_MARK(1);

  {
    float acc[64];
    const int r = wg & 1, ch = wg >> 1;
    const bool mufu0 = 2 * w < NMB, mufu1 = 2 * w + 1 < NMB;
    uint32_t pk[32];
    float gs = 0.f;
    const int grow = c1 * 16 + (tid >> 5);
    auto stage = [&](uint32_t stg, int e0) {
#pragma unroll
      for (int e = 0; e < 16; e += 4) stsm4(stg + (w * 16 + (lane & 15)) * 16 + (lane >> 4) * 1024 + e * 512, pk[e0 + e], pk[e0 + e + 1], pk[e0 + e + 2], pk[e0 + e + 3]);
    };
    auto duties = [&](auto BR, int it, int ga0, bool narrow_a) {
      constexpr int br = decltype(BR)::value;
      if (wg == (it & 3) && it >= 1 && it <= 16) {
        mbar_wait(bar + 8 * (B_EMPTY + ((it - 1) & 3)), ((it - 1) >> 2) & 1);
        p1_load(wt == 0, it + 3);
      }
      if (br == 0 && wg == 0 && it >= 1 && it <= 4) {
        const bool p = wt == 0;
        if (it < 4) bulk_s2g_if(p, reinterpret_cast<uint8_t*>(out) + bid * 20480 + (it - 1) * 8192, sb + SM_X, it == 3 ? 4096 : 8192);
        else bulk_s2g_if(p, g_kv + bid * 240, sb + SM_X, 960);
        bulk_s2g_if(p, g_o + rb1 * ORB + ((c1 * 4 + it - 1) * 5 + 2) * 2048, sb + SM_X, 2048);
        BULK_COMMIT();
      }
      if (br == 0 && it == 2 && wg == 1 && wt < 3) {
        const int bytes = wt == 0 ? 19200 : 6400;
        const uint8_t* p = reinterpret_cast<const uint8_t*>(wt == 0 ? wqkv_b : wt == 1 ? wo_a : wo_b) + bid * bytes;
        asm volatile("cp.async.bulk.prefetch.L2.global [%0], %1;" ::"l"(p), "r"(bytes) : "memory");
      }
      if (br == 0 && it == 3) {
        epoch = (lds32(sb + SM_EP) >> 7) + 1;
#pragma unroll
        for (int u = 0; u < 2; u++) {
          const int i = tid + u * 512, k = i / 24, n = i % 24, ii = 2 * (n >> 3) + (n & 1), f = 4 * ii + ((n & 7) >> 1), d = k - (odd ? 4 : 0);
          uint16_t v = 0;
          if (d >= 0 && d < 20 && ii < 5) asm volatile("ld.shared.u16 %0, [%1];" : "=h"(v) : "r"(sb + SM_WRAW + (d * 20 + f) * 2) : "memory");
          if (i < 768) sts16(sb + SM_WPHI + (k >> 3) * 384 + n * 16 + (k & 7) * 2, v);
        }
      }
      if (br == 0 && it == 6 && wg == 0) BULK_WAIT_READ();
      if (br == 1 && it == 12) {
        BULK_WAIT_READ();
        bar_sync(1 + wg, 128);
        if (!narrow_a) {
          stage(sb + SM_X + wg * 8192, 16);
          PROXY_FENCE();
          bar_sync(1 + wg, 128);
          tma5d_store_if(wt == 0, &maps.qst, sb + SM_X + wg * 8192, ((ga0 + 1) % 10) * 8, (ga0 + 1) / 10, wg & 1, rb1);
          BULK_COMMIT();
        }
      }
      if (br == 1 && it == 15) signal_bulk_if(wt == 0, &g_cnt[C_TA]);
      if (br == 1 && it >= 17 && it <= 18 && wg == (it & 3)) {
        if (it == 17) wait_count(&g_cnt[C_TA], epoch * 512);
        else mbar_wait(bar + 8 * (B_KVFULL + 0), 0);
        mbar_wait(bar + 8 * (B_EMPTY + (it - 17)), 0);
        mbar_expect_if(wt == 0, bar + 8 * (B_KVFULL + it - 17), P1_STB);
        tma5d_if(wt == 0, sb + (it - 17) * P1_STB, &maps.qld, c0, 1, (it - 17) * 4, bar + 8 * (B_KVFULL + it - 17));
      }
    };
    const int ga_a = tile_atom(c1) + 2 * ch + (((c1 & 3) == 2 && wg == 0) ? 1 : 0);
    const bool narrow_a = ((c1 & 3) == 1 && wg == 3) || ((c1 & 3) == 2 && wg == 0);
    auto gate_step = [&](uint32_t dst, int ks) {
      if (ks == 0) mbar_wait(bar + 8 * B_AUX, 0);
      const uint32_t a = lds32(dst + grow * 128 + (((lane >> 2) ^ (grow & 7)) << 4) + t * 4), b = lds32(sb + SM_GW + ks * 128 + lane * 4);
      gs = fmaf(__uint_as_float(a << 16), __uint_as_float(b << 16), gs);
      gs = fmaf(__uint_as_float(a & 0xffff0000u), __uint_as_float(b & 0xffff0000u), gs);
      __syncwarp();
      mbar_arrive_if(ks == 9 && lane == 0, bar + 8 * B_ZERO);
    };
    auto tile = [&](auto BR) {
      constexpr int br = decltype(BR)::value;
      const int tl = c1 ^ br, k4 = tl & 3;
      const bool narrow = (k4 == 1 && wg == 3) || (k4 == 2 && wg == 0);
      const int a0 = 2 * ch + ((k4 == 2 && wg == 0) ? 1 : 0);
      if (!narrow) {
#pragma unroll 1
        for (int ks = 0; ks < 10; ks++) {
          const int it = br * 10 + ks, st = it & 3;
          mbar_wait(bar + 8 * (B_FULL + st), (it >> 2) & 1);
          TS_MARK(20 + it);
          const uint32_t dst = sb + st * P1_STB;
          const uint64_t da = mkdesc(dst + r * 8192, 16, 1024, 1), db = mkdesc(dst + 16384 + a0 * 8192, 8192, 1024, 1);
          WG_FENCE();
#pragma unroll
          for (int k = 0; k < 4; k++) wg128_ss(acc, da + k * 2, db + k * 128, (ks | k) != 0);
          WG_COMMIT();
          if (br == 0) gate_step(dst, ks);
          WG_WAIT(1);
          mbar_arrive_if(ks > 0 && wt == 0, bar + 8 * (B_EMPTY + ((it - 1) & 3)));
          duties(BR, it, ga_a, narrow_a);
        }
        WG_WAIT(0);
      } else {
#pragma unroll 1
        for (int ks = 0; ks < 10; ks++) {
          const int it = br * 10 + ks, st = it & 3;
          mbar_wait(bar + 8 * (B_FULL + st), (it >> 2) & 1);
          TS_MARK(20 + it);
          const uint32_t dst = sb + st * P1_STB;
          const uint64_t da = mkdesc(dst + r * 8192, 16, 1024, 1), db = mkdesc(dst + 16384 + a0 * 8192, 8192, 1024, 1);
          WG_FENCE();
#pragma unroll
          for (int k = 0; k < 4; k++) wg64_ss_of64(acc, da + k * 2, db + k * 128, (ks | k) != 0);
          WG_COMMIT();
          if (br == 0) gate_step(dst, ks);
          WG_WAIT(1);
          mbar_arrive_if(ks > 0 && wt == 0, bar + 8 * (B_EMPTY + ((it - 1) & 3)));
          duties(BR, it, ga_a, narrow_a);
        }
        WG_WAIT(0);
      }
      pin(acc);
      TS_MARK(2 + 2 * br);
      mbar_arrive_if(wt == 0, bar + 8 * (B_EMPTY + ((br * 10 + 9) & 3)));
      const int ga0 = tile_atom(tl) + a0;
      uint32_t m0 = 0, m1 = 0;
      if (br == 0) {
        const float sk0 = __uint_as_float(mufu0 ? (127u + 70u) << 23 : (127u - 69u) << 23);
        const float sk1 = __uint_as_float(mufu1 ? (127u + 70u) << 23 : (127u - 69u) << 23);
        pack_atom_a<0>(acc, pk, ga0, sk0, sk1, m0, m1);
        if (!narrow) pack_atom_a<1>(acc, pk, ga0 + 1, sk0, sk1, m0, m1);
        const uint32_t lim0 = (mufu0 ? 127u + 110u : 127u - 29u) << 7, lim1 = (mufu1 ? 127u + 110u : 127u - 29u) << 7;
        if ((m0 & 0x7fffu) >= lim0 || ((m0 >> 16) & 0x7fffu) >= lim0 || (m1 & 0x7fffu) >= lim1 || ((m1 >> 16) & 0x7fffu) >= lim1) { g_kbad = epoch; __threadfence(); }
#pragma unroll
        for (int o = 16; o; o >>= 1) gs += __shfl_xor_sync(0xffffffffu, gs, o);
        mbar_wait(bar + 8 * B_ZERO, 0);
        stage(sb + SM_X + wg * 8192, 0);
        if (lane == 0) sts32(sb + SM_BAR + 448 + (tid >> 5) * 4, __float_as_uint(1.f / (1.f + __expf(-gs))));
        PROXY_FENCE();
        bar_sync(1 + wg, 128);
        tma5d_store_if(wt == 0, &maps.qst, sb + SM_X + wg * 8192, (ga0 % 10) * 8, ga0 / 10, r, rb1);
        bulk_s2g_if(wt == 0, g_gate + rb1 * 128 + c1 * 16 + wg * 4, sb + SM_BAR + 448 + wg * 16, 16);
        BULK_COMMIT();
      } else {
        mbar_wait(bar + 8 * (B_KVFULL + 0), 0);
        const uint8_t* qp = g_qkv + rb * QRB + c0 * 2048 + (w * 16 + g) * 16 + t * 4;
        load_frag(q[0], qp);
        load_frag(q[1], qp + 1024);
        bad = ldcg32(&g_kbad) == epoch;
        const uint32_t onepos = sb + wg * 12288 + (wt >> 6) * 6144 + 3072 + (odd ? 0 : 2048 + 8) + (wt & 63) * 16;
        sts16(onepos, 0x3c00);
        PROXY_FENCE();
        mbar_arrive(bar + 8 * (B_READY + 0));
        pack_atom<0, 0>(acc, pk, 0.f, 0.f, m0, m1);
        pack_atom<0, 1>(acc, pk, 0.f, 0.f, m0, m1);
        mbar_wait(bar + 8 * (B_EMPTY + 2 + ch), 0);
        const uint32_t stg = sb + (2 + ch) * P1_STB + r * 16384;
        stage(stg, 0);
        stage(stg + 8192, 16);
        mbar_wait(bar + 8 * (B_KVFULL + 1), 0);
        sts16(onepos + P1_STB, 0x3c00);
        PROXY_FENCE();
        mbar_arrive(bar + 8 * (B_READY + 1));
        bar_sync(1 + wg, 128);
        tma5d_store_if(wt == 0, &maps.qst, stg, (ga0 % 10) * 8, ga0 / 10, r, 16 + rb1);
        tma5d_store_if(wt == 0 && !narrow, &maps.qst, stg + 8192, ((ga0 + 1) % 10) * 8, (ga0 + 1) / 10, r, 16 + rb1);
        BULK_COMMIT();
      }
      TS_MARK(3 + 2 * br);
    };
    tile(Int<0>{});
    tile(Int<1>{});
  }

  if (odd ? t < 2 : t >= 2) {
    if (odd) { q[0][0] = 0; q[0][1] = 0; q[1][0] = 0; q[1][1] = 0; }
    else { q[0][4] = 0; q[0][5] = 0; q[1][4] = 0; q[1][5] = 0; }
  }
  {
    uint32_t m = 0;
#pragma unroll
    for (int i = 0; i < 6; i++) m = maxabs_bf16x2(m, maxabs_bf16x2(q[0][i], q[1][i]));
    bad |= (m & 0x7fffu) >= ((127u - 50u) << 7) || ((m >> 16) & 0x7fffu) >= ((127u - 50u) << 7);
  }
#pragma unroll
  for (int i = 0; i < 4; i++) { qc[i] = t == 0 ? 0x1c801c80u : 0u; asm volatile("" : "+r"(qc[i])); }
  events = 0x01010100u | (0x81000u << wg) | (wg == 0 ? 0x40000u : wg == 1 ? 0x4020000u : wg == 2 ? 0x400u : 0xa00u);
  mbar_wait(bar + 8 * (B_READY + 0), 0);
  }
  float o[2][12];
#pragma unroll
  for (int i = 0; i < 12; i++) { o[0][i] = 0.f; o[1][i] = 0.f; }
  {
    uint32_t dk0 = (uint32_t)mkdesc(sb, 1024, 0, 0), dk1 = (uint32_t)mkdesc(sb + 2048, SM_CONST - 2048, 0, 0), dv = (uint32_t)mkdesc(sb + 3072, 128, 0, 0);
    TS_MARK(6);
#pragma unroll 1
    for (int i = 0; i < 32; i++) {
      if ((events >> i) & 1) {
        if ((i & 7) == 0) {
          COORDS();
          const bool p = wt == 0;
          signal_bulk_if(p, &g_cnt[i == 8 ? C_TB : i == 16 ? C_KV + h : C_OB + rb * 2 + (h >> 4)]);
          WG_WAIT(0);
          mbar_arrive_if(p, bar + 8 * (B_FREE - 1) + i);
          mbar_wait(bar + 8 * B_READY + i, 0);
        } else if (i < 12 || i == 17 || i == 26) {
          COORDS();
          if (i == 9) {
            mbar_wait(bar + 8 * (B_FREE + 0), 0);
#pragma unroll
            for (int u = 2; u < 4; u++) {
              mbar_expect_if(wt == 0, bar + 8 * (B_KVFULL + u), P1_STB);
              tma5d_if(wt == 0, sb + u * P1_STB, &maps.qld, c0, 1, u * 4, bar + 8 * (B_KVFULL + u));
            }
          } else if (i == 11) {
            const uint32_t onepos = sb + 2 * P1_STB + (wt >> 6) * 6144 + 3072 + (odd ? 0 : 2048 + 8) + (wt & 63) * 16;
            mbar_wait(bar + 8 * (B_KVFULL + 2), 0);
            mbar_wait(bar + 8 * (B_KVFULL + 3), 0);
#pragma unroll
            for (int u = 0; u < 8; u++) sts16(onepos + u * 12288, 0x3c00);
            PROXY_FENCE();
            mbar_arrive(bar + 8 * (B_READY + 2));
            mbar_arrive(bar + 8 * (B_READY + 3));
          } else if (i == 26) {
            mbar_wait(bar + 8 * (B_FREE + 2), 0);
#pragma unroll
            for (int j = 0; j < 3; j++) p3_load_w(wt == 0, j);
            wait_count(&g_cnt[C_OB + rb1 * 2 + kh], epoch * 16);
#pragma unroll
            for (int j = 0; j < 3; j++) p3_load_a(wt == 0, j);
          } else {
            const int u = i == 17;
            mbar_wait(bar + 8 * (B_FREE + u), 0);
            if (!u) wait_count(&g_cnt[C_TB], epoch * 512);
            mbar_expect_if(wt == 0, bar + 8 * (B_KB + u), P1_STB);
            tma5d_if(wt == 0, sb + u * P1_STB, &maps.qld, c0, 1 - u, 16 + qt * 4, bar + 8 * (B_KB + u));
          }
        } else if (i < 16) {
          WG_WAIT(0);
          COORDS();
          const uint64_t dw = mkdesc(sb + SM_WPHI, 384, 128, 0);
          const uint32_t onepos = (wt >> 6) * 6144 + 3072 + (odd ? 0 : 2048 + 8) + (wt & 63) * 16;
          TS_MARK(7);
          const uint32_t kb = sb + wg * 12288, ph = sb + SM_X + (wg & 1) * 10240;
          mbar_wait(bar + 8 * B_KB, 0);
          sts16(kb + onepos, 0x3f80);
          float p0[12], p1[12];
          phi_proj(p0, p1, kb, dw);
          if (wg >= 2) mbar_wait(bar + 8 * (B_LINK + (wg & 1)), 0);
          uint32_t phi[10];
          feature_map(phi, p0);
#pragma unroll
          for (int u = 0; u < 10; u++) sts32(ph + (u % 5) * 2048 + orow + (u / 5) * 128, phi[u]);
          feature_map(phi, p1);
#pragma unroll
          for (int u = 0; u < 10; u++) sts32(ph + (u % 5) * 2048 + orow + (u / 5) * 128 + 1024, phi[u]);
          PROXY_FENCE();
          bar_sync(1 + wg, 128);
          const uint64_t da = mkdesc(ph, 128, 2048, 0), db = mkdesc(kb + 3072, 128, 1024, 0);
          WG_FENCE();
#pragma unroll
          for (int kk = 0; kk < 8; kk++) {
            if (kk == 0) wg24_ss_bf16_tt_i(p0, da, db);
            else wg24_ss_bf16_tt(p0, da + kk * 16, db + (kk & 3) * 16 + (kk >> 2) * 384, 1);
          }
          WG_COMMIT();
          WG_WAIT(0);
          pin(p0);
          mbar_arrive_if(lane == 0 && wg < 2, bar + 8 * (B_LINK + wg));
          bar_sync(1 + wg, 128);
          const uint32_t ks = kb + ((w * 16 + g) * 24 + 2 * t) * 4;
#pragma unroll
          for (int j = 0; j < 3; j++) {
            if (w < 3) asm volatile("st.shared.v2.f32 [%0], {%1, %2};" ::"r"(ks + 32 * j), "f"(p0[4 * j]), "f"(p0[4 * j + 1]) : "memory");
            if (w < 2) asm volatile("st.shared.v2.f32 [%0], {%1, %2};" ::"r"(ks + 768 + 32 * j), "f"(p0[4 * j + 2]), "f"(p0[4 * j + 3]) : "memory");
          }
          PROXY_FENCE();
          bar_sync(1 + wg, 128);
          bulk_addf_if(wt == 0, g_kv + h * 960, kb, 3840);
          BULK_COMMIT();
          TS_MARK(8);
        } else if (i == 18) {
          COORDS();
          wait_count(&g_cnt[C_KV + h], epoch * 16);
          float v[8];
#pragma unroll
          for (int u = 0; u < 8; u++) v[u] = (u < 7 || wt < 64) ? __ldcg(&g_kv[h * 960 + u * 128 + wt]) : 0.f;
#pragma unroll
          for (int u = 0; u < 9; u++) {
            const int e = u * 128 + wt, f = e / 24, d = e % 24;
            sts16(sb + SM_KVB + (f >> 3) * 384 + d * 16 + (f & 7) * 2, u < 8 ? __bfloat16_as_ushort(__float2bfloat16(v[u < 8 ? u : 0])) : (uint16_t)0);
          }
          PROXY_FENCE();
          mbar_arrive(bar + 8 * B_KVB);
        } else {
          WG_WAIT(0);
          COORDS();
          const uint64_t dw = mkdesc(sb + SM_WPHI, 384, 128, 0);
          TS_MARK(9);
          float gt[4];
#pragma unroll
          for (int u = 0; u < 4; u++) gt[u] = 1.f - __ldcg(&g_gate[rb * 128 + (u >> 1) * 64 + w * 16 + g + (u & 1) * 8]);
          mbar_wait(bar + 8 * B_QB, 0);
          float p0[12], p1[12];
          phi_proj(p0, p1, sb + P1_STB + wg * 12288, dw);
          const uint64_t dkv = mkdesc(sb + SM_KVB, 384, 128, 0);
          auto readout = [&](float (&p)[12], float g0, float g1, uint32_t a) {
            uint32_t phi[10];
            feature_map(phi, p);
            WG_FENCE();
            wg24_rs_bf16_i(p, phi[0], phi[5], phi[1], phi[6], dkv);
            wg24_rs_bf16(p, phi[2], phi[7], phi[3], phi[8], dkv + 48, 1);
            wg24_rs_bf16(p, phi[4], phi[9], 0u, 0u, dkv + 96, 1);
            WG_COMMIT();
            WG_WAIT(0);
            pin(p);
            const float l0 = __shfl_sync(0xffffffffu, odd ? p[0] : p[8], lsrc), l1 = __shfl_sync(0xffffffffu, odd ? p[2] : p[10], lsrc);
            stage_o(p, __fdividef(g0, l0 + 1e-6f), __fdividef(g1, l1 + 1e-6f), a, v0, v2);
          };
          mbar_wait(bar + 8 * B_KVB, 0);
          readout(p0, gt[0], gt[1], ostg + orow);
          readout(p1, gt[2], gt[3], ostg + orow + 1024);
          PROXY_FENCE();
          bar_sync(1 + wg, 128);
          flush_o(wt == 0, g_o + rb * ORB + (80 + c0) * 2048, ostg, odd);
          TS_MARK(10);
        }
      }
      if (!(i & 3)) TS_MARK(40 + (i >> 2));
#pragma unroll
      for (int m = 0; m < 2; m++) {
        float s[32];
        uint32_t p[16];
        WG_FENCE();
        wg64_rs_bf16_i(s, q[m][0], q[m][1], q[m][2], q[m][3], desc_lohi(dk0, 8));
        wg64_rs_bf16(s, q[m][4], q[m][5], qc[2 * m], qc[2 * m + 1], desc_lohi(dk1, 8), 1);
        WG_COMMIT();
        WG_WAIT(0);
        constexpr int A = 2 * NMB, B = 16 - A;
#pragma unroll
        for (int j = 0; j < B; j++) {
          if ((j * A) % B < A) { const int a = j * A / B; p[a] = exp2_pair_mufu(s[2 * a], s[2 * a + 1]); }
          p[A + j] = exp2_pair(s[2 * (A + j)], s[2 * (A + j) + 1]);
        }
        WG_FENCE();
#pragma unroll
        for (int kk = 0; kk < 4; kk++) wg24_rs_f16_t(o[m], p[4 * kk], p[4 * kk + 1], p[4 * kk + 2], p[4 * kk + 3], desc_lohi(dv + kk * 16, 64), 1);
        WG_COMMIT();
      }
      dk0 += 384; dk1 += 384u - (384u << 16); dv += 384;
    }
  }
  {
    COORDS();
    float gt[4];
#pragma unroll
    for (int u = 0; u < 4; u++) gt[u] = __ldcg(&g_gate[rb * 128 + (u >> 1) * 64 + w * 16 + g + (u & 1) * 8]);
    WG_WAIT(0);
    pin(o[0]); pin(o[1]);
    TS_MARK(11);
    int big = 0;
#pragma unroll
    for (int m = 0; m < 2; m++) {
      const float l0 = __shfl_sync(0xffffffffu, odd ? o[m][0] : o[m][8], lsrc), l1 = __shfl_sync(0xffffffffu, odd ? o[m][2] : o[m][10], lsrc);
      const float r0 = rcp(l0), r1 = rcp(l1);
      float chk = 0.f, mx0 = 0.f, mx1 = 0.f;
#pragma unroll
      for (int i = 0; i < 12; i++) chk = fmaf(o[m][i], 0.f, chk);
#pragma unroll
      for (int i = 4; i < 6; i++) { mx0 = fmaxf(mx0, fabsf(o[m][i])); mx1 = fmaxf(mx1, fabsf(o[m][i + 2])); }
      bad |= !(chk == 0.f) || !(l0 >= 32.f) || !(l1 >= 32.f);
      big |= fmaxf(mx0 * r0, mx1 * r1) >= 1.220703125e-4f;
      stage_o(o[m], r0 * gt[2 * m], r1 * gt[2 * m + 1], ostg + orow + m * 1024, v0, v2);
    }
    PROXY_FENCE();
    const int anybad = __syncthreads_or(bad), anybig = __syncthreads_or(big);
    if (anybad || !anybig) attn_exact(x, wqkv, h, qt, sb + SM_X);
  }
  TS_MARK(12);

  COORDS();
  if (wg == 3) {
    flush_o(lane == 0, g_o + (qt * 4 + w) * ORB + c0 * 2048, sb + SM_X + w * 6144, odd);
    signal_bulk_if(lane == 0, &g_cnt[C_OA + (qt * 4 + w) * 2 + (h >> 4)]);
    TS_MARK(18);
    if (wt == 0) atomicAdd(&g_cnt[C_EPOCH], 1);
  } else if (wg == 2) {
    if (w == 0) {
      const bool p = lane == 0;
      p3_load_w(p, 3); p3_load_a(p, 3);
      mbar_wait(bar + 8 * (B_P3EMPTY + 0), 0);
      p3_load_w(p, 4); p3_load_a(p, 4);
      for (int j = 5; j < 8; j++) { mbar_wait(bar + 8 * (B_P3EMPTY + (j & 3)), 0); p3_load_w(p, j); }
      wait_count(&g_cnt[C_OA + rb1 * 2 + kh], epoch * 16);
      TS_MARK(16);
      for (int j = 5; j < 8; j++) p3_load_a(p, j);
      for (int j = 8; j < 10; j++) { mbar_wait(bar + 8 * (B_P3EMPTY + (j & 3)), 1); p3_load_w(p, j); p3_load_a(p, j); }
    }
  } else {
    float acc[96];
    const bool wide = (cg & 1) == wg;
    const int skip = (!wide && (cg & 1)) ? 1 : 0;
    if (wide) {
#pragma unroll 1
      for (int j = 0; j < 10; j++) {
        mbar_wait(bar + 8 * (B_P3FULL + (j & 3)), (j >> 2) & 1);
        if (j == 5) TS_MARK(13);
        const uint32_t dst = sb + (j & 3) * P3_STB;
        const uint64_t da = mkdesc(dst + wg * 1024, 2048, 128, 0), db = mkdesc(dst + 16384, 8192, 1024, 1);
        WG_FENCE();
#pragma unroll
        for (int k = 0; k < 4; k++) wg192_ss(acc, da + k * 256, db + k * 128, (j | k) != 0);
        WG_COMMIT();
        WG_WAIT(1);
        mbar_arrive_if(j > 0 && wt == 0, bar + 8 * (B_P3EMPTY + ((j - 1) & 3)));
      }
      WG_WAIT(0);
    } else {
#pragma unroll 1
      for (int j = 0; j < 10; j++) {
        mbar_wait(bar + 8 * (B_P3FULL + (j & 3)), (j >> 2) & 1);
        if (j == 5) TS_MARK(13);
        const uint32_t dst = sb + (j & 3) * P3_STB;
        const uint64_t da = mkdesc(dst + wg * 1024, 2048, 128, 0), db = mkdesc(dst + 16384 + skip * 8192, 8192, 1024, 1);
        WG_FENCE();
#pragma unroll
        for (int k = 0; k < 4; k++) wg128_ss_of96(acc, da + k * 256, db + k * 128, (j | k) != 0);
        WG_COMMIT();
        WG_WAIT(1);
        mbar_arrive_if(j > 0 && wt == 0, bar + 8 * (B_P3EMPTY + ((j - 1) & 3)));
      }
      WG_WAIT(0);
    }
    pin(acc);
    TS_MARK(14);
    if (!wide) mbar_wait(bar + 8 * (B_P3EMPTY + 2), 1);
    const uint32_t stg = sb + (wide ? 4 : 2) * P3_STB;
    const int r = w * 16 + (lane & 15);
#pragma unroll
    for (int i = 0; i < 24; i += 2)
      if (i < 16 || wide) {
        const int ch = (i & 7) + (lane >> 4);
        stsm4(stg + (i >> 3) * 8192 + r * 128 + ((ch ^ (r & 7)) << 4), pack_bf16(acc[4 * i], acc[4 * i + 1]), pack_bf16(acc[4 * i + 2], acc[4 * i + 3]),
              pack_bf16(acc[4 * i + 4], acc[4 * i + 5]), pack_bf16(acc[4 * i + 6], acc[4 * i + 7]));
      }
    PROXY_FENCE();
    bar_sync(1 + wg, 128);
    if (wt < (wide ? 3 : 2)) {
      PROXY_FENCE_G();
      asm volatile("cp.reduce.async.bulk.tensor.2d.global.shared::cta.add.bulk_group [%0, {%2, %3}], [%1];" ::"l"(&maps.out), "r"(stg + wt * 8192),
                   "r"((atom3 + skip + wt) * 64), "r"(rb1 * 128 + wg * 64) : "memory");
      asm volatile("cp.async.bulk.commit_group;" ::: "memory");
      asm volatile("cp.async.bulk.wait_group 0;" ::: "memory");
    }
    TS_MARK(15);
  }
  TS_DUMP();
}

typedef CUresult (*EncodeFn)(CUtensorMap*, CUtensorMapDataType, cuuint32_t, void*, const cuuint64_t*, const cuuint64_t*, const cuuint32_t*, const cuuint32_t*,
                             CUtensorMapInterleave, CUtensorMapSwizzle, CUtensorMapL2promotion, CUtensorMapFloatOOBfill);
void encode(EncodeFn enc, CUtensorMap* m, void* p, int rank, const cuuint64_t* gd, const cuuint64_t* gs, const cuuint32_t* bd) {
  const cuuint32_t es[3] = {1, 1, 1};
  enc(m, CU_TENSOR_MAP_DATA_TYPE_BFLOAT16, rank, p, gd, gs, bd, es, CU_TENSOR_MAP_INTERLEAVE_NONE, CU_TENSOR_MAP_SWIZZLE_128B,
      CU_TENSOR_MAP_L2_PROMOTION_L2_128B, CU_TENSOR_MAP_FLOAT_OOB_FILL_NONE);
}

}

extern "C" void kernel_launch(void* const* d_in, const int* in_sizes, int n_in, void* d_out, int out_size) {
  static EncodeFn enc = nullptr;
  if (!enc) {
    cudaDriverEntryPointQueryResult qr;
    cudaGetDriverEntryPoint("cuTensorMapEncodeTiled", (void**)&enc, cudaEnableDefault, &qr);
    cudaFuncSetAttribute(gated_mix_kernel, cudaFuncAttributeMaxDynamicSharedMemorySize, SMEM_BYTES);
  }
  Maps m;
  {
    const cuuint64_t gd[2] = {640, 2048}, gs[1] = {1280};
    const cuuint32_t bx[2] = {64, 128}, bo[2] = {64, 64};
    encode(enc, &m.x, d_in[0], 2, gd, gs, bx);
    encode(enc, &m.out, d_out, 2, gd, gs, bo);
  }
  for (int b = 0; b < 2; b++) {
    const cuuint64_t gd[3] = {64, 640, 30}, gs[2] = {3840, 128}, gd3[3] = {64, 640, 10}, gs3[2] = {1280, 128};
    const cuuint32_t bd[3] = {64, 64, 4}, bd3[3] = {64, 64, 3};
    encode(enc, &m.w[b], d_in[b ? 4 : 1], 3, gd, gs, bd);
    encode(enc, &m.wo[b], d_in[b ? 6 : 2], 3, gd3, gs3, bd3);
  }
  {
    void* qp = nullptr;
    cudaGetSymbolAddress(&qp, g_qkv);
    const cuuint64_t gd[5] = {128, 80, 3, 2, 32}, gs[4] = {2048, QTY, 1024, QRB};
    const cuuint32_t bl[5] = {128, 3, 2, 2, 4}, bs[5] = {128, 8, 1, 1, 1}, es[5] = {1, 1, 1, 1, 1};
    enc(&m.qld, CU_TENSOR_MAP_DATA_TYPE_UINT64, 5, qp, gd, gs, bl, es, CU_TENSOR_MAP_INTERLEAVE_NONE, CU_TENSOR_MAP_SWIZZLE_NONE, CU_TENSOR_MAP_L2_PROMOTION_L2_128B, CU_TENSOR_MAP_FLOAT_OOB_FILL_NONE);
    enc(&m.qst, CU_TENSOR_MAP_DATA_TYPE_UINT64, 5, qp, gd, gs, bs, es, CU_TENSOR_MAP_INTERLEAVE_NONE, CU_TENSOR_MAP_SWIZZLE_NONE, CU_TENSOR_MAP_L2_PROMOTION_NONE, CU_TENSOR_MAP_FLOAT_OOB_FILL_NONE);
  }
  gated_mix_kernel<<<128, 512, SMEM_BYTES, cudaStreamPerThread>>>(m, (const __nv_bfloat16*)d_in[0], (const __nv_bfloat16*)d_in[1], (const __nv_bfloat16*)d_in[5],
                                                                 (const __nv_bfloat16*)d_in[7], d_in[4], d_in[2], d_in[6], (uint4*)d_out);
}
```

```cpp
#include <cuda_runtime.h>
#include <cuda.h>
#include <cuda_bf16.h>
#include <cuda_fp16.h>
#include <stdint.h>
#pragma nv_diag_suppress 550

namespace {

constexpr int QRB = 240 * 2048;
constexpr int QBR = 16 * QRB;
constexpr int QTY = 80 * 2048;
constexpr int ORB = 160 * 2048;
constexpr int NMB = 3;

__device__ __align__(1024) uint8_t g_qkv[2 * QBR];
__device__ __align__(1024) uint8_t g_o[16 * ORB];
__device__ float g_gate[2048];
__device__ __align__(16) float g_kv[32 * 960];
__device__ uint32_t g_kbad;
__device__ uint32_t g_fb[128 * 2048 * 20];
__device__ uint32_t g_cnt[192];
constexpr int C_EPOCH = 0, C_TA = 32, C_TB = 64, C_KV = 96, C_OB = 128, C_OA = 160;

#define TS_MARK(i)
#define TS_INIT()
#define TS_FIRST()
#define TS_DUMP()

__device__ __forceinline__ uint64_t mkdesc(uint32_t addr, uint32_t lbo, uint32_t sbo, int mode) {
  return (uint64_t)((addr & 0x3FFFF) >> 4) | ((uint64_t)(lbo >> 4) << 16) | ((uint64_t)(sbo >> 4) << 32) | ((uint64_t)mode << 62);
}
__device__ __forceinline__ uint64_t desc_lohi(uint32_t lo, uint32_t hi) { return ((uint64_t)hi << 32) | lo; }
#define WG_FENCE() asm volatile("wgmma.fence.sync.aligned;" ::: "memory")
#define WG_COMMIT() asm volatile("wgmma.commit_group.sync.aligned;" ::: "memory")
#define WG_WAIT(n) asm volatile("wgmma.wait_group.sync.aligned %0;" ::"n"(n) : "memory")
#define PROXY_FENCE() asm volatile("fence.proxy.async.shared::cta;" ::: "memory")
#define PROXY_FENCE_G() asm volatile("fence.proxy.async.global;" ::: "memory")
__device__ __forceinline__ void bar_sync(int id, int n) { asm volatile("bar.sync %0, %1;" ::"r"(id), "r"(n) : "memory"); }
__device__ __forceinline__ void mbar_init(uint32_t a, int c) { asm volatile("mbarrier.init.shared::cta.b64 [%0], %1;" ::"r"(a), "r"(c)); }
__device__ __forceinline__ uint32_t mbar_try(uint32_t a, int par) {
  uint32_t ok;
  asm volatile("{.reg .pred p; mbarrier.try_wait.parity.shared::cta.b64 p, [%1], %2; selp.b32 %0, 1, 0, p;}" : "=r"(ok) : "r"(a), "r"(par) : "memory");
  return ok;
}
__device__ __forceinline__ void mbar_wait(uint32_t a, int par) {
  for (int i = 0; !mbar_try(a, par); i++)
    if (i > (1 << 22)) break;
}
__device__ __forceinline__ void mbar_arrive(uint32_t a) { asm volatile("mbarrier.arrive.shared::cta.b64 _, [%0];" ::"r"(a) : "memory"); }
__device__ __forceinline__ void mbar_arrive_if(bool p, uint32_t a) {
  asm volatile("{.reg .pred p; setp.ne.b32 p, %0, 0; @p mbarrier.arrive.shared::cta.b64 _, [%1];}" ::"r"((int)p), "r"(a) : "memory");
}
__device__ __forceinline__ void mbar_expect_if(bool p, uint32_t a, int bytes) {
  asm volatile("{.reg .pred p; setp.ne.b32 p, %0, 0; @p mbarrier.arrive.expect_tx.shared::cta.b64 _, [%1], %2;}" ::"r"((int)p), "r"(a), "r"(bytes) : "memory");
}
__device__ __forceinline__ void tma2d_if(bool p, uint32_t dst, const CUtensorMap* m, int c0, int c1, uint32_t bar) {
  asm volatile("{.reg .pred p; setp.ne.b32 p, %0, 0; @p cp.async.bulk.tensor.2d.shared::cluster.global.mbarrier::complete_tx::bytes [%1], [%2, {%4, %5}], [%3];}"
               ::"r"((int)p), "r"(dst), "l"(m), "r"(bar), "r"(c0), "r"(c1) : "memory");
}
__device__ __forceinline__ void tma3d_if(bool p, uint32_t dst, const CUtensorMap* m, int c1, int c2, uint32_t bar) {
  asm volatile("{.reg .pred p; setp.ne.b32 p, %0, 0; @p cp.async.bulk.tensor.3d.shared::cluster.global.mbarrier::complete_tx::bytes [%1], [%2, {%6, %4, %5}], [%3];}"
               ::"r"((int)p), "r"(dst), "l"(m), "r"(bar), "r"(c1), "r"(c2), "r"(0) : "memory");
}
__device__ __forceinline__ void bulk_g2s_if(bool p, uint32_t dst, const void* src, int bytes, uint32_t bar) {
  asm volatile("{.reg .pred p; setp.ne.b32 p, %0, 0; @p cp.async.bulk.shared::cluster.global.mbarrier::complete_tx::bytes [%1], [%2], %3, [%4];}"
               ::"r"((int)p), "r"(dst), "l"(src), "r"(bytes), "r"(bar) : "memory");
}
__device__ __forceinline__ void tma5d_if(bool p, uint32_t dst, const CUtensorMap* m, int c1, int c2, int c4, uint32_t bar) {
  asm volatile("{.reg .pred p; setp.ne.b32 p, %0, 0; @p cp.async.bulk.tensor.5d.shared::cluster.global.mbarrier::complete_tx::bytes [%1], [%2, {%7, %4, %5, %7, %6}], [%3];}"
               ::"r"((int)p), "r"(dst), "l"(m), "r"(bar), "r"(c1), "r"(c2), "r"(c4), "r"(0) : "memory");
}
__device__ __forceinline__ void tma5d_store_if(bool p, const CUtensorMap* m, uint32_t src, int c1, int c2, int c3, int c4) {
  asm volatile("{.reg .pred p; setp.ne.b32 p, %0, 0; @p cp.async.bulk.tensor.5d.global.shared::cta.bulk_group [%1, {%7, %3, %4, %5, %6}], [%2];}"
               ::"r"((int)p), "l"(m), "r"(src), "r"(c1), "r"(c2), "r"(c3), "r"(c4), "r"(0) : "memory");
}
__device__ __forceinline__ void bulk_s2g_if(bool p, void* dst, uint32_t src, int bytes) {
  asm volatile("{.reg .pred p; setp.ne.b32 p, %0, 0; @p cp.async.bulk.global.shared::cta.bulk_group [%1], [%2], %3;}" ::"r"((int)p), "l"(dst), "r"(src), "r"(bytes) : "memory");
}
__device__ __forceinline__ void bulk_or_if(bool p, void* dst, uint32_t src, int bytes) {
  asm volatile("{.reg .pred p; setp.ne.b32 p, %0, 0; @p cp.reduce.async.bulk.global.shared::cta.bulk_group.or.b32 [%1], [%2], %3;}" ::"r"((int)p), "l"(dst), "r"(src), "r"(bytes) : "memory");
}
__device__ __forceinline__ void bulk_addf_if(bool p, void* dst, uint32_t src, int bytes) {
  asm volatile("{.reg .pred p; setp.ne.b32 p, %0, 0; @p cp.reduce.async.bulk.global.shared::cta.bulk_group.add.f32 [%1], [%2], %3;}" ::"r"((int)p), "l"(dst), "r"(src), "r"(bytes) : "memory");
}
#define BULK_COMMIT() asm volatile("cp.async.bulk.commit_group;" ::: "memory")
#define BULK_WAIT() asm volatile("cp.async.bulk.wait_group 0;" ::: "memory")
#define BULK_WAIT_READ() asm volatile("cp.async.bulk.wait_group.read 0;" ::: "memory")
__device__ __forceinline__ void signal_bulk_if(bool p, uint32_t* c) {
  asm volatile("{.reg .pred p; setp.ne.b32 p, %0, 0; cp.async.bulk.wait_group 0; @p red.relaxed.gpu.global.add.u32 [%1], 1;}" ::"r"((int)p), "l"(c) : "memory");
}
__device__ __forceinline__ void wait_count(const uint32_t* c, uint32_t target) {
  for (int i = 0;; i++) {
    uint32_t v;
    asm volatile("ld.relaxed.gpu.global.u32 %0, [%1];" : "=r"(v) : "l"(c) : "memory");
    if ((int)(v - target) >= 0) break;
    if (i > (1 << 20)) break;
  }
  PROXY_FENCE_G();
}
__device__ __forceinline__ uint32_t pack_bf16(float lo, float hi) { uint32_t r; asm("cvt.rn.bf16x2.f32 %0, %1, %2;" : "=r"(r) : "f"(hi), "f"(lo)); return r; }
__device__ __forceinline__ uint32_t pack_f16(float lo, float hi) { uint32_t r; asm("cvt.rn.f16x2.f32 %0, %1, %2;" : "=r"(r) : "f"(hi), "f"(lo)); return r; }
__device__ __forceinline__ float ex2(float a) { float r; asm("ex2.approx.ftz.f32 %0, %1;" : "=f"(r) : "f"(a)); return r; }
__device__ __forceinline__ float rcp(float a) { float r; asm("rcp.approx.ftz.f32 %0, %1;" : "=f"(r) : "f"(a)); return r; }
__device__ __forceinline__ uint32_t maxabs_bf16x2(uint32_t a, uint32_t b) { uint32_t r; asm("max.NaN.xorsign.abs.bf16x2 %0, %1, %2;" : "=r"(r) : "r"(a), "r"(b)); return r; }
__device__ __forceinline__ uint32_t ldg32(const void* p) { return __ldg(reinterpret_cast<const uint32_t*>(p)); }
__device__ __forceinline__ uint32_t ldcg32(const void* p) { uint32_t v; asm volatile("ld.global.cg.u32 %0, [%1];" : "=r"(v) : "l"(p) : "memory"); return v; }
__device__ __forceinline__ uint32_t lds32(uint32_t a) { uint32_t v; asm volatile("ld.shared.b32 %0, [%1];" : "=r"(v) : "r"(a) : "memory"); return v; }
__device__ __forceinline__ void sts32(uint32_t a, uint32_t v) { asm volatile("st.shared.b32 [%0], %1;" ::"r"(a), "r"(v) : "memory"); }
__device__ __forceinline__ void sts16(uint32_t a, uint16_t v) { asm volatile("st.shared.b16 [%0], %1;" ::"r"(a), "h"(v) : "memory"); }
__device__ __forceinline__ void stsm4(uint32_t a, uint32_t r0, uint32_t r1, uint32_t r2, uint32_t r3) {
  asm volatile("stmatrix.sync.aligned.m8n8.x4.shared.b16 [%0], {%1, %2, %3, %4};" ::"r"(a), "r"(r0), "r"(r1), "r"(r2), "r"(r3) : "memory");
}
template <int N> __device__ __forceinline__ void pin(float (&d)[N]) {
#pragma unroll
  for (int i = 0; i < N; i++) asm volatile("" : "+f"(d[i])::"memory");
}

__device__ __forceinline__ void wg128_ss(float (&d)[64], uint64_t da, uint64_t db, int scale_d) {
  asm volatile("{\n.reg .pred p;\nsetp.ne.b32 p, %66, 0;\n"
    "wgmma.mma_async.sync.aligned.m64n128k16.f32.bf16.bf16 "
    "{%0, %1, %2, %3, %4, %5, %6, %7, %8, %9, %10, %11, %12, %13, %14, %15,"
    "%16, %17, %18, %19, %20, %21, %22, %23, %24, %25, %26, %27, %28, %29, %30, %31,"
    "%32, %33, %34, %35, %36, %37, %38, %39, %40, %41, %42, %43, %44, %45, %46, %47,"
    "%48, %49, %50, %51, %52, %53, %54, %55, %56, %57, %58, %59, %60, %61, %62, %63}, "
    "%64, %65, p, 1, 1, 0, 1;\n}\n"
    : "+f"(d[0]), "+f"(d[1]), "+f"(d[2]), "+f"(d[3]), "+f"(d[4]), "+f"(d[5]), "+f"(d[6]), "+f"(d[7]),
      "+f"(d[8]), "+f"(d[9]), "+f"(d[10]), "+f"(d[11]), "+f"(d[12]), "+f"(d[13]), "+f"(d[14]), "+f"(d[15]),
      "+f"(d[16]), "+f"(d[17]), "+f"(d[18]), "+f"(d[19]), "+f"(d[20]), "+f"(d[21]), "+f"(d[22]), "+f"(d[23]),
      "+f"(d[24]), "+f"(d[25]), "+f"(d[26]), "+f"(d[27]), "+f"(d[28]), "+f"(d[29]), "+f"(d[30]), "+f"(d[31]),
      "+f"(d[32]), "+f"(d[33]), "+f"(d[34]), "+f"(d[35]), "+f"(d[36]), "+f"(d[37]), "+f"(d[38]), "+f"(d[39]),
      "+f"(d[40]), "+f"(d[41]), "+f"(d[42]), "+f"(d[43]), "+f"(d[44]), "+f"(d[45]), "+f"(d[46]), "+f"(d[47]),
      "+f"(d[48]), "+f"(d[49]), "+f"(d[50]), "+f"(d[51]), "+f"(d[52]), "+f"(d[53]), "+f"(d[54]), "+f"(d[55]),
      "+f"(d[56]), "+f"(d[57]), "+f"(d[58]), "+f"(d[59]), "+f"(d[60]), "+f"(d[61]), "+f"(d[62]), "+f"(d[63])
    : "l"(da), "l"(db), "r"(scale_d));
}

__device__ __forceinline__ void wg64_ss_of64(float (&d)[64], uint64_t da, uint64_t db, int scale_d) {
  asm volatile("{\n.reg .pred p;\nsetp.ne.b32 p, %34, 0;\n"
    "wgmma.mma_async.sync.aligned.m64n64k16.f32.bf16.bf16 "
    "{%0, %1, %2, %3, %4, %5, %6, %7, %8, %9, %10, %11, %12, %13, %14, %15,"
    "%16, %17, %18, %19, %20, %21, %22, %23, %24, %25, %26, %27, %28, %29, %30, %31}, "
    "%32, %33, p, 1, 1, 0, 1;\n}\n"
    : "+f"(d[0]), "+f"(d[1]), "+f"(d[2]), "+f"(d[3]), "+f"(d[4]), "+f"(d[5]), "+f"(d[6]), "+f"(d[7]),
      "+f"(d[8]), "+f"(d[9]), "+f"(d[10]), "+f"(d[11]), "+f"(d[12]), "+f"(d[13]), "+f"(d[14]), "+f"(d[15]),
      "+f"(d[16]), "+f"(d[17]), "+f"(d[18]), "+f"(d[19]), "+f"(d[20]), "+f"(d[21]), "+f"(d[22]), "+f"(d[23]),
      "+f"(d[24]), "+f"(d[25]), "+f"(d[26]), "+f"(d[27]), "+f"(d[28]), "+f"(d[29]), "+f"(d[30]), "+f"(d[31])
    : "l"(da), "l"(db), "r"(scale_d));
}

__device__ __forceinline__ void wg192_ss(float (&d)[96], uint64_t da, uint64_t db, int scale_d) {
  asm volatile("{\n.reg .pred p;\nsetp.ne.b32 p, %98, 0;\n"
    "wgmma.mma_async.sync.aligned.m64n192k16.f32.bf16.bf16 "
    "{%0, %1, %2, %3, %4, %5, %6, %7, %8, %9, %10, %11, %12, %13, %14, %15,"
    "%16, %17, %18, %19, %20, %21, %22, %23, %24, %25, %26, %27, %28, %29, %30, %31,"
    "%32, %33, %34, %35, %36, %37, %38, %39, %40, %41, %42, %43, %44, %45, %46, %47,"
    "%48, %49, %50, %51, %52, %53, %54, %55, %56, %57, %58, %59, %60, %61, %62, %63,"
    "%64, %65, %66, %67, %68, %69, %70, %71, %72, %73, %74, %75, %76, %77, %78, %79,"
    "%80, %81, %82, %83, %84, %85, %86, %87, %88, %89, %90, %91, %92, %93, %94, %95}, "
    "%96, %97, p, 1, 1, 0, 1;\n}\n"
    : "+f"(d[0]), "+f"(d[1]), "+f"(d[2]), "+f"(d[3]), "+f"(d[4]), "+f"(d[5]), "+f"(d[6]), "+f"(d[7]),
      "+f"(d[8]), "+f"(d[9]), "+f"(d[10]), "+f"(d[11]), "+f"(d[12]), "+f"(d[13]), "+f"(d[14]), "+f"(d[15]),
      "+f"(d[16]), "+f"(d[17]), "+f"(d[18]), "+f"(d[19]), "+f"(d[20]), "+f"(d[21]), "+f"(d[22]), "+f"(d[23]),
      "+f"(d[24]), "+f"(d[25]), "+f"(d[26]), "+f"(d[27]), "+f"(d[28]), "+f"(d[29]), "+f"(d[30]), "+f"(d[31]),
      "+f"(d[32]), "+f"(d[33]), "+f"(d[34]), "+f"(d[35]), "+f"(d[36]), "+f"(d[37]), "+f"(d[38]), "+f"(d[39]),
      "+f"(d[40]), "+f"(d[41]), "+f"(d[42]), "+f"(d[43]), "+f"(d[44]), "+f"(d[45]), "+f"(d[46]), "+f"(d[47]),
      "+f"(d[48]), "+f"(d[49]), "+f"(d[50]), "+f"(d[51]), "+f"(d[52]), "+f"(d[53]), "+f"(d[54]), "+f"(d[55]),
      "+f"(d[56]), "+f"(d[57]), "+f"(d[58]), "+f"(d[59]), "+f"(d[60]), "+f"(d[61]), "+f"(d[62]), "+f"(d[63]),
      "+f"(d[64]), "+f"(d[65]), "+f"(d[66]), "+f"(d[67]), "+f"(d[68]), "+f"(d[69]), "+f"(d[70]), "+f"(d[71]),
      "+f"(d[72]), "+f"(d[73]), "+f"(d[74]), "+f"(d[75]), "+f"(d[76]), "+f"(d[77]), "+f"(d[78]), "+f"(d[79]),
      "+f"(d[80]), "+f"(d[81]), "+f"(d[82]), "+f"(d[83]), "+f"(d[84]), "+f"(d[85]), "+f"(d[86]), "+f"(d[87]),
      "+f"(d[88]), "+f"(d[89]), "+f"(d[90]), "+f"(d[91]), "+f"(d[92]), "+f"(d[93]), "+f"(d[94]), "+f"(d[95])
    : "l"(da), "l"(db), "r"(scale_d));
}

__device__ __forceinline__ void wg128_ss_of96(float (&d)[96], uint64_t da, uint64_t db, int scale_d) {
  asm volatile("{\n.reg .pred p;\nsetp.ne.b32 p, %66, 0;\n"
    "wgmma.mma_async.sync.aligned.m64n128k16.f32.bf16.bf16 "
    "{%0, %1, %2, %3, %4, %5, %6, %7, %8, %9, %10, %11, %12, %13, %14, %15,"
    "%16, %17, %18, %19, %20, %21, %22, %23, %24, %25, %26, %27, %28, %29, %30, %31,"
    "%32, %33, %34, %35, %36, %37, %38, %39, %40, %41, %42, %43, %44, %45, %46, %47,"
    "%48, %49, %50, %51, %52, %53, %54, %55, %56, %57, %58, %59, %60, %61, %62, %63}, "
    "%64, %65, p, 1, 1, 0, 1;\n}\n"
    : "+f"(d[0]), "+f"(d[1]), "+f"(d[2]), "+f"(d[3]), "+f"(d[4]), "+f"(d[5]), "+f"(d[6]), "+f"(d[7]),
      "+f"(d[8]), "+f"(d[9]), "+f"(d[10]), "+f"(d[11]), "+f"(d[12]), "+f"(d[13]), "+f"(d[14]), "+f"(d[15]),
      "+f"(d[16]), "+f"(d[17]), "+f"(d[18]), "+f"(d[19]), "+f"(d[20]), "+f"(d[21]), "+f"(d[22]), "+f"(d[23]),
      "+f"(d[24]), "+f"(d[25]), "+f"(d[26]), "+f"(d[27]), "+f"(d[28]), "+f"(d[29]), "+f"(d[30]), "+f"(d[31]),
      "+f"(d[32]), "+f"(d[33]), "+f"(d[34]), "+f"(d[35]), "+f"(d[36]), "+f"(d[37]), "+f"(d[38]), "+f"(d[39]),
      "+f"(d[40]), "+f"(d[41]), "+f"(d[42]), "+f"(d[43]), "+f"(d[44]), "+f"(d[45]), "+f"(d[46]), "+f"(d[47]),
      "+f"(d[48]), "+f"(d[49]), "+f"(d[50]), "+f"(d[51]), "+f"(d[52]), "+f"(d[53]), "+f"(d[54]), "+f"(d[55]),
      "+f"(d[56]), "+f"(d[57]), "+f"(d[58]), "+f"(d[59]), "+f"(d[60]), "+f"(d[61]), "+f"(d[62]), "+f"(d[63])
    : "l"(da), "l"(db), "r"(scale_d));
}

__device__ __forceinline__ void wg64_rs_bf16(float (&d)[32], uint32_t a0, uint32_t a1, uint32_t a2, uint32_t a3, uint64_t db, int scale_d) {
  asm volatile("{\n.reg .pred p;\nsetp.ne.b32 p, %37, 0;\n"
    "wgmma.mma_async.sync.aligned.m64n64k16.f32.bf16.bf16 "
    "{%0, %1, %2, %3, %4, %5, %6, %7, %8, %9, %10, %11, %12, %13, %14, %15,"
    "%16, %17, %18, %19, %20, %21, %22, %23, %24, %25, %26, %27, %28, %29, %30, %31}, "
    "{%32, %33, %34, %35}, %36, p, 1, 1, 0;\n}\n"
    : "+f"(d[0]), "+f"(d[1]), "+f"(d[2]), "+f"(d[3]), "+f"(d[4]), "+f"(d[5]), "+f"(d[6]), "+f"(d[7]),
      "+f"(d[8]), "+f"(d[9]), "+f"(d[10]), "+f"(d[11]), "+f"(d[12]), "+f"(d[13]), "+f"(d[14]), "+f"(d[15]),
      "+f"(d[16]), "+f"(d[17]), "+f"(d[18]), "+f"(d[19]), "+f"(d[20]), "+f"(d[21]), "+f"(d[22]), "+f"(d[23]),
      "+f"(d[24]), "+f"(d[25]), "+f"(d[26]), "+f"(d[27]), "+f"(d[28]), "+f"(d[29]), "+f"(d[30]), "+f"(d[31])
    : "r"(a0), "r"(a1), "r"(a2), "r"(a3), "l"(db), "r"(scale_d));
}

__device__ __forceinline__ void wg24_rs_f16_t(float (&d)[12], uint32_t a0, uint32_t a1, uint32_t a2, uint32_t a3, uint64_t db, int scale_d) {
  asm volatile("{\n.reg .pred p;\nsetp.ne.b32 p, %17, 0;\n"
    "wgmma.mma_async.sync.aligned.m64n24k16.f32.f16.f16 "
    "{%0, %1, %2, %3, %4, %5, %6, %7, %8, %9, %10, %11}, "
    "{%12, %13, %14, %15}, %16, p, 1, 1, 1;\n}\n"
    : "+f"(d[0]), "+f"(d[1]), "+f"(d[2]), "+f"(d[3]), "+f"(d[4]), "+f"(d[5]), "+f"(d[6]), "+f"(d[7]),
      "+f"(d[8]), "+f"(d[9]), "+f"(d[10]), "+f"(d[11])
    : "r"(a0), "r"(a1), "r"(a2), "r"(a3), "l"(db), "r"(scale_d));
}

__device__ __forceinline__ void wg24_rs_bf16(float (&d)[12], uint32_t a0, uint32_t a1, uint32_t a2, uint32_t a3, uint64_t db, int scale_d) {
  asm volatile("{\n.reg .pred p;\nsetp.ne.b32 p, %17, 0;\n"
    "wgmma.mma_async.sync.aligned.m64n24k16.f32.bf16.bf16 "
    "{%0, %1, %2, %3, %4, %5, %6, %7, %8, %9, %10, %11}, "
    "{%12, %13, %14, %15}, %16, p, 1, 1, 0;\n}\n"
    : "+f"(d[0]), "+f"(d[1]), "+f"(d[2]), "+f"(d[3]), "+f"(d[4]), "+f"(d[5]), "+f"(d[6]), "+f"(d[7]),
      "+f"(d[8]), "+f"(d[9]), "+f"(d[10]), "+f"(d[11])
    : "r"(a0), "r"(a1), "r"(a2), "r"(a3), "l"(db), "r"(scale_d));
}

__device__ __forceinline__ void wg24_ss_bf16_tt(float (&d)[12], uint64_t da, uint64_t db, int scale_d) {
  asm volatile("{\n.reg .pred p;\nsetp.ne.b32 p, %14, 0;\n"
    "wgmma.mma_async.sync.aligned.m64n24k16.f32.bf16.bf16 "
    "{%0, %1, %2, %3, %4, %5, %6, %7, %8, %9, %10, %11}, "
    "%12, %13, p, 1, 1, 1, 1;\n}\n"
    : "+f"(d[0]), "+f"(d[1]), "+f"(d[2]), "+f"(d[3]), "+f"(d[4]), "+f"(d[5]), "+f"(d[6]), "+f"(d[7]),
      "+f"(d[8]), "+f"(d[9]), "+f"(d[10]), "+f"(d[11])
    : "l"(da), "l"(db), "r"(scale_d));
}

__device__ __forceinline__ void wg64_rs_bf16_i(float (&d)[32], uint32_t a0, uint32_t a1, uint32_t a2, uint32_t a3, uint64_t db) {
  asm volatile("{\n.reg .pred p;\nsetp.ne.b32 p, 0, 0;\n"
    "wgmma.mma_async.sync.aligned.m64n64k16.f32.bf16.bf16 "
    "{%0, %1, %2, %3, %4, %5, %6, %7, %8, %9, %10, %11, %12, %13, %14, %15,"
    "%16, %17, %18, %19, %20, %21, %22, %23, %24, %25, %26, %27, %28, %29, %30, %31}, "
    "{%32, %33, %34, %35}, %36, p, 1, 1, 0;\n}\n"
    : "=f"(d[0]), "=f"(d[1]), "=f"(d[2]), "=f"(d[3]), "=f"(d[4]), "=f"(d[5]), "=f"(d[6]), "=f"(d[7]),
      "=f"(d[8]), "=f"(d[9]), "=f"(d[10]), "=f"(d[11]), "=f"(d[12]), "=f"(d[13]), "=f"(d[14]), "=f"(d[15]),
      "=f"(d[16]), "=f"(d[17]), "=f"(d[18]), "=f"(d[19]), "=f"(d[20]), "=f"(d[21]), "=f"(d[22]), "=f"(d[23]),
      "=f"(d[24]), "=f"(d[25]), "=f"(d[26]), "=f"(d[27]), "=f"(d[28]), "=f"(d[29]), "=f"(d[30]), "=f"(d[31])
    : "r"(a0), "r"(a1), "r"(a2), "r"(a3), "l"(db));
}

__device__ __forceinline__ void wg24_rs_bf16_i(float (&d)[12], uint32_t a0, uint32_t a1, uint32_t a2, uint32_t a3, uint64_t db) {
  asm volatile("{\n.reg .pred p;\nsetp.ne.b32 p, 0, 0;\n"
    "wgmma.mma_async.sync.aligned.m64n24k16.f32.bf16.bf16 "
    "{%0, %1, %2, %3, %4, %5, %6, %7, %8, %9, %10, %11}, "
    "{%12, %13, %14, %15}, %16, p, 1, 1, 0;\n}\n"
    : "=f"(d[0]), "=f"(d[1]), "=f"(d[2]), "=f"(d[3]), "=f"(d[4]), "=f"(d[5]), "=f"(d[6]), "=f"(d[7]),
      "=f"(d[8]), "=f"(d[9]), "=f"(d[10]), "=f"(d[11])
    : "r"(a0), "r"(a1), "r"(a2), "r"(a3), "l"(db));
}

__device__ __forceinline__ void wg24_ss_bf16_tt_i(float (&d)[12], uint64_t da, uint64_t db) {
  asm volatile("{\n.reg .pred p;\nsetp.ne.b32 p, 0, 0;\n"
    "wgmma.mma_async.sync.aligned.m64n24k16.f32.bf16.bf16 "
    "{%0, %1, %2, %3, %4, %5, %6, %7, %8, %9, %10, %11}, "
    "%12, %13, p, 1, 1, 1, 1;\n}\n"
    : "=f"(d[0]), "=f"(d[1]), "=f"(d[2]), "=f"(d[3]), "=f"(d[4]), "=f"(d[5]), "=f"(d[6]), "=f"(d[7]),
      "=f"(d[8]), "=f"(d[9]), "=f"(d[10]), "=f"(d[11])
    : "l"(da), "l"(db));
}

__device__ __forceinline__ void wg24_ss_bf16(float (&d)[12], uint64_t da, uint64_t db, int scale_d) {
  asm volatile("{\n.reg .pred p;\nsetp.ne.b32 p, %14, 0;\n"
    "wgmma.mma_async.sync.aligned.m64n24k16.f32.bf16.bf16 "
    "{%0, %1, %2, %3, %4, %5, %6, %7, %8, %9, %10, %11}, "
    "%12, %13, p, 1, 1, 0, 0;\n}\n"
    : "+f"(d[0]), "+f"(d[1]), "+f"(d[2]), "+f"(d[3]), "+f"(d[4]), "+f"(d[5]), "+f"(d[6]), "+f"(d[7]),
      "+f"(d[8]), "+f"(d[9]), "+f"(d[10]), "+f"(d[11])
    : "l"(da), "l"(db), "r"(scale_d));
}

__device__ __forceinline__ void wg24_ss_bf16_i(float (&d)[12], uint64_t da, uint64_t db) {
  asm volatile("{\n.reg .pred p;\nsetp.ne.b32 p, 0, 0;\n"
    "wgmma.mma_async.sync.aligned.m64n24k16.f32.bf16.bf16 "
    "{%0, %1, %2, %3, %4, %5, %6, %7, %8, %9, %10, %11}, "
    "%12, %13, p, 1, 1, 0, 0;\n}\n"
    : "=f"(d[0]), "=f"(d[1]), "=f"(d[2]), "=f"(d[3]), "=f"(d[4]), "=f"(d[5]), "=f"(d[6]), "=f"(d[7]),
      "=f"(d[8]), "=f"(d[9]), "=f"(d[10]), "=f"(d[11])
    : "l"(da), "l"(db));
}

constexpr int P1_STB = 49152, P3_STB = 40960;
constexpr int SM_X = 196608;
constexpr int SM_KVB = SM_X + 24576;
constexpr int SM_GW = SM_X + 8192, SM_WRAW = SM_GW + 1280, SM_EP = SM_WRAW + 800;
constexpr int SM_CONST = SM_X + 32768, SM_WPHI = SM_CONST + 1024, SM_BAR = SM_WPHI + 1536;
constexpr int SMEM_BYTES = SM_BAR + 512;
constexpr int B_FULL = 0, B_AUX = 4, B_KB = 5, B_QB = 6, B_KVFULL = 7, B_P3FULL = 11, B_P3EMPTY = 15, B_EMPTY = 19, B_LINK = 23, B_FREE = 25,
              B_STG = 28, B_B2 = 29, B_ZERO = 30, B_READY = 31, B_KVB = 35;

template <int V> struct Int { static constexpr int value = V; };
struct Maps { CUtensorMap x, w[2], wo[2], out, qld, qst; };

__device__ __forceinline__ int tile_atom(int t) { return (t >> 2) * 15 + ((0xB740 >> ((t & 3) * 4)) & 15); }

template <int MODE, int A>
__device__ __forceinline__ void pack_atom(const float (&acc)[64], uint32_t (&r)[32], float s0, float s1, uint32_t& m0, uint32_t& m1) {
#pragma unroll
  for (int e = A * 16; e < A * 16 + 16; e++) {
    const float s = (e & 1) ? s1 : s0;
    if (MODE == 0) r[e] = pack_bf16(acc[2 * e], acc[2 * e + 1]);
    else if (MODE == 3) r[e] = pack_f16(acc[2 * e], acc[2 * e + 1]);
    else r[e] = pack_bf16(acc[2 * e] * s, acc[2 * e + 1] * s);
    if (MODE == 2) { if (e & 1) m1 = maxabs_bf16x2(m1, r[e]); else m0 = maxabs_bf16x2(m0, r[e]); }
  }
}
template <int A>
__device__ __forceinline__ void pack_atom_a(const float (&acc)[64], uint32_t (&r)[32], int ga, float sk0, float sk1, uint32_t& m0, uint32_t& m1) {
  if (ga < 10) { const float cq = __uint_as_float(463809372u); pack_atom<1, A>(acc, r, cq, cq, m0, m1); }
  else if (ga < 20) pack_atom<2, A>(acc, r, sk0, sk1, m0, m1);
  else pack_atom<3, A>(acc, r, 0.f, 0.f, m0, m1);
}

__device__ __forceinline__ uint32_t exp2_pair(float a, float b) {
  uint32_t z, w, h;
  asm volatile("cvt.pack.sat.s16.s32 %0, %2, %1;" : "=r"(z) : "r"(__float_as_uint(a)), "r"(__float_as_uint(b)));
  asm volatile("lop3.b32 %0, %1, 0x03ff03ff, 0x34003400, 0xEA;" : "=r"(w) : "r"(z));
  asm volatile("fma.rn.f16x2 %0, %1, %1, %2;" : "=r"(h) : "r"(w), "r"(0x36203620));
  asm volatile("fma.rn.f16x2 %0, %0, %1, %2;" : "+r"(h) : "r"(w), "r"(0x2e012e01));
  return h + z - w;
}
__device__ __forceinline__ uint32_t exp2_pair_mufu(float a, float b) {
  float x, y; uint32_t r;
  asm volatile("ex2.approx.ftz.f32 %0, %1;" : "=f"(x) : "f"(a));
  asm volatile("ex2.approx.ftz.f32 %0, %1;" : "=f"(y) : "f"(b));
  asm volatile("cvt.rn.f16x2.f32 %0, %1, %2;" : "=r"(r) : "f"(y), "f"(x));
  return r;
}
__device__ __forceinline__ void load_frag(uint32_t (&a)[6], const uint8_t* p) {
  a[0] = ldcg32(p); a[1] = ldcg32(p + 128); a[2] = ldcg32(p + 2048); a[3] = ldcg32(p + 2048 + 128); a[4] = ldcg32(p + 4096); a[5] = ldcg32(p + 4096 + 128);
}
template <bool EXACT>
__device__ __forceinline__ bool feature_rows(uint32_t (&phi)[10], const float (&p)[12]) {
  const float L = 1.4426950408889634f;
  bool ok = true;
#pragma unroll
  for (int r = 0; r < 2; r++) {
    const float v[5] = {p[2 * r], p[2 * r + 1], p[4 + 2 * r], p[5 + 2 * r], p[8 + 2 * r]};
    float ep[5], en[5];
    if (EXACT) {
      float mx = fmaxf(fmaxf(fmaxf(v[0], v[1]), fmaxf(v[2], v[3])), v[4]);
      float mn = fminf(fminf(fminf(v[0], v[1]), fminf(v[2], v[3])), v[4]);
      mx = fmaxf(mx, __shfl_xor_sync(0xffffffffu, mx, 1)); mn = fminf(mn, __shfl_xor_sync(0xffffffffu, mn, 1));
      mx = fmaxf(mx, __shfl_xor_sync(0xffffffffu, mx, 2)); mn = fminf(mn, __shfl_xor_sync(0xffffffffu, mn, 2));
#pragma unroll
      for (int i = 0; i < 5; i++) { ep[i] = ex2((v[i] - mx) * L); en[i] = ex2((mn - v[i]) * L); }
    } else {
#pragma unroll
      for (int i = 0; i < 5; i++) { const float u = v[i] * L; ep[i] = ex2(u); en[i] = ex2(-u); }
    }
    float sp = (ep[0] + ep[1]) + (ep[2] + ep[3]) + ep[4], sn = (en[0] + en[1]) + (en[2] + en[3]) + en[4];
    sp += __shfl_xor_sync(0xffffffffu, sp, 1); sn += __shfl_xor_sync(0xffffffffu, sn, 1);
    sp += __shfl_xor_sync(0xffffffffu, sp, 2); sn += __shfl_xor_sync(0xffffffffu, sn, 2);
    ok = ok && sp + sn < 1.2676506e30f;
    const float rp = rcp(sp), rn = rcp(sn);
#pragma unroll
    for (int i = 0; i < 5; i++) phi[5 * r + i] = pack_bf16(ep[i] * rp, en[i] * rn);
  }
  return ok;
}
__device__ __forceinline__ void feature_map(uint32_t (&phi)[10], const float (&p)[12]) {
  if (!__all_sync(0xffffffffu, feature_rows<false>(phi, p))) feature_rows<true>(phi, p);
}
__device__ __forceinline__ void phi_proj(float (&p0)[12], float (&p1)[12], uint32_t a, uint64_t dw) {
  const uint64_t da = mkdesc(a, 1024, 128, 0), db = mkdesc(a + 2048, 0, 128, 0);
  WG_FENCE();
  wg24_ss_bf16_i(p0, da, dw);
  wg24_ss_bf16(p0, db, dw + 48, 1);
  wg24_ss_bf16_i(p1, da + 384, dw);
  wg24_ss_bf16(p1, db + 384, dw + 48, 1);
  WG_COMMIT();
  WG_WAIT(0);
  pin(p0); pin(p1);
}
__device__ __forceinline__ void stage_o(const float (&o)[12], float s0, float s1, uint32_t a, bool v0, bool v2) {
#pragma unroll
  for (int j = 0; j < 3; j++) {
    const bool v = j == 1 || (j == 0 ? v0 : v2);
    sts32(a + j * 2048, v ? pack_bf16(o[4 * j] * s0, o[4 * j + 1] * s0) : 0u);
    sts32(a + j * 2048 + 128, v ? pack_bf16(o[4 * j + 2] * s1, o[4 * j + 3] * s1) : 0u);
  }
}
__device__ __forceinline__ void flush_o(bool p, uint8_t* dst, uint32_t src, bool odd) {
  bulk_s2g_if(p, dst + (odd ? 2048 : 0), src + (odd ? 2048 : 0), 4096);
  bulk_or_if(p, dst + (odd ? 0 : 4096), src + (odd ? 0 : 4096), 2048);
  BULK_COMMIT();
}

__device__ __forceinline__ void proj20(float (&acc)[20], const __nv_bfloat16* __restrict__ xr, const __nv_bfloat16* __restrict__ wc) {
#pragma unroll
  for (int d = 0; d < 20; d++) acc[d] = 0.f;
#pragma unroll 2
  for (int k = 0; k < 640; k++) {
    const float xv = __bfloat162float(xr[k]);
#pragma unroll
    for (int d = 0; d < 10; d++) {
      const uint32_t u = ldg32(wc + k * 1920 + 2 * d);
      acc[2 * d] = fmaf(xv, __uint_as_float(u << 16), acc[2 * d]);
      acc[2 * d + 1] = fmaf(xv, __uint_as_float(u & 0xffff0000u), acc[2 * d + 1]);
    }
  }
}
__device__ __noinline__ void attn_exact(const __nv_bfloat16* __restrict__ x, const __nv_bfloat16* __restrict__ wqkv, int h, int qt, uint32_t stg) {
  const int tid = threadIdx.x;
  uint32_t* kvs = g_fb + blockIdx.x * (2048 * 20);
  float a[20];
  for (int i = 0; i < 8; i++) {
    const int key = (i >> 1) * 512 + tid, ty = 1 + (i & 1);
    proj20(a, x + key * 640, wqkv + ty * 640 + h * 20);
#pragma unroll
    for (int d = 0; d < 10; d++) kvs[key * 20 + (i & 1) * 10 + d] = pack_bf16(a[2 * d], a[2 * d + 1]);
  }
  const int row = qt * 512 + tid;
  proj20(a, x + row * 640, wqkv + h * 20);
#pragma unroll
  for (int d = 0; d < 20; d++) a[d] = __bfloat162float(__float2bfloat16(a[d]));
  __syncthreads();
  float o[20], m = -INFINITY, l = 0.f;
#pragma unroll
  for (int d = 0; d < 20; d++) o[d] = 0.f;
  for (int key = 0; key < 2048; key++) {
    uint32_t u[20];
#pragma unroll
    for (int d = 0; d < 5; d++) {
      const uint4 t4 = *reinterpret_cast<const uint4*>(kvs + key * 20 + 4 * d);
      u[4 * d] = t4.x; u[4 * d + 1] = t4.y; u[4 * d + 2] = t4.z; u[4 * d + 3] = t4.w;
    }
    float s = 0.f;
#pragma unroll
    for (int d = 0; d < 10; d++) {
      s = fmaf(a[2 * d], __uint_as_float(u[d] << 16), s);
      s = fmaf(a[2 * d + 1], __uint_as_float(u[d] & 0xffff0000u), s);
    }
    s *= 0.22360679774997896f;
    const float mn = fmaxf(m, s), cr = __expf(m - mn), p = __expf(s - mn);
    m = mn;
    l = l * cr + p;
#pragma unroll
    for (int d = 0; d < 10; d++) {
      o[2 * d] = fmaf(p, __uint_as_float(u[10 + d] << 16), o[2 * d] * cr);
      o[2 * d + 1] = fmaf(p, __uint_as_float(u[10 + d] & 0xffff0000u), o[2 * d + 1] * cr);
    }
  }
  const float sc = __ldcg(&g_gate[row]) / l;
#pragma unroll
  for (int d = 0; d < 10; d++) {
    const int col = (h & 1) * 4 + 2 * d;
    sts32(stg + (tid >> 7) * 6144 + (col >> 3) * 2048 + (tid & 127) * 16 + (col & 7) * 2, pack_bf16(o[2 * d] * sc, o[2 * d + 1] * sc));
  }
  PROXY_FENCE();
  __syncthreads();
}

#define COORDS()                                                                                                        \
  int tid, bid;                                                                                                         \
  asm volatile("mov.u32 %0, %%tid.x;" : "=r"(tid));                                                                     \
  asm volatile("mov.u32 %0, %%ctaid.x;" : "=r"(bid));                                                                   \
  const int wg = __shfl_sync(0xffffffffu, tid >> 7, 0);                                                                 \
  const int lane = tid & 31, w = (tid >> 5) & 3, g = lane >> 2, t = lane & 3, wt = tid & 127;                           \
  const int rb1 = bid >> 3, c1 = bid & 7;                                       \
  const int h = bid >> 2, qt = bid & 3, rb = qt * 4 + wg;                    \
  const bool odd = h & 1;                                                                                               \
  const int c0 = (h * 5) >> 1;                                               \
  const int lsrc = (lane & ~3) | (odd ? 0 : 2);                                                                         \
  const bool v0 = !odd || t >= 2, v2 = odd || t < 2;                                                                    \
  const uint32_t ostg = sb + SM_X + wg * 6144, orow = (w * 16 + g) * 16 + t * 4;                                        \
  const uint32_t onepos = (wt >> 6) * 6144 + 3072 + (odd ? 0 : 2048 + 8) + (wt & 63) * 16;                              \
  const int kh = bid & 1, cg = (bid >> 1) & 3, atom3 = (cg >> 1) * 5 + (cg & 1) * 2;                                    \
  auto p3_load_w = [&](bool p, int j) {                                                                                 \
    const uint32_t fb = bar + 8 * (B_P3FULL + (j & 3));                                                                 \
    mbar_expect_if(p, fb, P3_STB);                                                                                      \
    tma3d_if(p, sb + (j & 3) * P3_STB + 16384, &maps.wo[j < 5], (kh * 5 + (j < 5 ? j : j - 5)) * 64, atom3, fb);       \
  };                                                                                                                    \
  auto p3_load_a = [&](bool p, int j) {                                                                                 \
    bulk_g2s_if(p, sb + (j & 3) * P3_STB, g_o + rb1 * ORB + ((j < 5 ? 10 + j : j - 5) + kh * 5) * 16384, 16384,         \
                bar + 8 * (B_P3FULL + (j & 3)));                                                                        \
  };                                                                                                                    \
  (void)g; (void)t; (void)wt; (void)rb1; (void)c1; (void)rb; (void)c0; (void)lsrc; (void)v0; (void)v2; (void)ostg;      \
  (void)orow; (void)onepos; (void)atom3; (void)p3_load_w; (void)p3_load_a

__global__ void __launch_bounds__(512, 1)
gated_mix_kernel(const __grid_constant__ Maps maps, const __nv_bfloat16* __restrict__ x, const __nv_bfloat16* __restrict__ wqkv, const __nv_bfloat16* __restrict__ w_phi,
                 const __nv_bfloat16* __restrict__ gate_w, const void* wqkv_b, const void* wo_a, const void* wo_b, uint4* __restrict__ out) {
  extern __shared__ __align__(1024) uint8_t smem_raw[];
  const uint32_t sb = (uint32_t)__cvta_generic_to_shared(smem_raw);
  const uint32_t bar = sb + SM_BAR;
  uint32_t q[2][6], qc[4], epoch, events;
  int bad;
  {
  COORDS();
  TS_INIT();

  auto p1_load = [&](bool p, int it) {
    const int st = it & 3, br = it >= 10, ks = it - br * 10;
    const uint32_t dst = sb + st * P1_STB, fb = bar + 8 * (B_FULL + st);
    mbar_expect_if(p, fb, P1_STB);
    tma2d_if(p, dst, &maps.x, ks * 64, rb1 * 128, fb);
    tma3d_if(p, dst + 16384, &maps.w[br], ks * 64, tile_atom(c1 ^ br), fb);
  };
  if (wt == 0) {
    mbar_init(bar + 8 * (B_FULL + wg), 1);
    asm volatile("fence.mbarrier_init.release.cluster;" ::: "memory");
    p1_load(true, wg);
  }
  if (tid == 64) {
    mbar_init(bar + 8 * B_AUX, 1);
    asm volatile("fence.mbarrier_init.release.cluster;" ::: "memory");
    mbar_expect_if(true, bar + 8 * B_AUX, 1280 + 800 + 16);
    bulk_g2s_if(true, sb + SM_GW, gate_w, 1280, bar + 8 * B_AUX);
    bulk_g2s_if(true, sb + SM_WRAW, w_phi + h * 400, 800, bar + 8 * B_AUX);
    bulk_g2s_if(true, sb + SM_EP, &g_cnt[C_EPOCH], 16, bar + 8 * B_AUX);
  }
  if (tid >= 32 && tid < 63) {
    const int i = tid - 32 + 5;
    mbar_init(bar + 8 * i, i < B_P3EMPTY ? 1 : i < B_EMPTY ? 2 : i < B_ZERO ? 4 : i == B_ZERO ? 16 : i < B_READY + 2 ? 512 : 128);
    asm volatile("fence.mbarrier_init.release.cluster;" ::: "memory");
  }
  asm volatile("st.shared.v4.b32 [%0], {%1, %1, %1, %1};" ::"r"(sb + SM_X + tid * 16), "r"(0) : "memory");
  if (tid < 256) sts32(sb + SM_CONST + tid * 4, (tid & 3) ? 0u : ((tid >> 5) < NMB ? 0xdd02e192u : 0x00001ef0u));
  PROXY_FENCE();
  __syncthreads();
  TS_FIRST();
  TS_MARK(1);

  {
    float acc[64];
    const int r = wg & 1, ch = wg >> 1;
    const bool mufu0 = 2 * w < NMB, mufu1 = 2 * w + 1 < NMB;
    uint32_t pk[32];
    float gs = 0.f;
    const int grow = c1 * 16 + (tid >> 5);
    auto stage = [&](uint32_t stg, int e0) {
#pragma unroll
      for (int e = 0; e < 16; e += 4) stsm4(stg + (w * 16 + (lane & 15)) * 16 + (lane >> 4) * 1024 + e * 512, pk[e0 + e], pk[e0 + e + 1], pk[e0 + e + 2], pk[e0 + e + 3]);
    };
    auto duties = [&](auto BR, int it, int ga0, bool narrow_a) {
      constexpr int br = decltype(BR)::value;
      if (wg == (it & 3) && it >= 1 && it <= 16) {
        mbar_wait(bar + 8 * (B_EMPTY + ((it - 1) & 3)), ((it - 1) >> 2) & 1);
        p1_load(wt == 0, it + 3);
      }
      if (br == 0 && wg == 0 && it >= 1 && it <= 4) {
        const bool p = wt == 0;
        if (it < 4) bulk_s2g_if(p, reinterpret_cast<uint8_t*>(out) + bid * 20480 + (it - 1) * 8192, sb + SM_X, it == 3 ? 4096 : 8192);
        else bulk_s2g_if(p, g_kv + bid * 240, sb + SM_X, 960);
        bulk_s2g_if(p, g_o + rb1 * ORB + ((c1 * 4 + it - 1) * 5 + 2) * 2048, sb + SM_X, 2048);
        BULK_COMMIT();
      }
      if (br == 0 && it == 2 && wg == 1 && wt < 3) {
        const int bytes = wt == 0 ? 19200 : 6400;
        const uint8_t* p = reinterpret_cast<const uint8_t*>(wt == 0 ? wqkv_b : wt == 1 ? wo_a : wo_b) + bid * bytes;
        asm volatile("cp.async.bulk.prefetch.L2.global [%0], %1;" ::"l"(p), "r"(bytes) : "memory");
      }
      if (br == 0 && it == 3) {
        epoch = (lds32(sb + SM_EP) >> 7) + 1;
#pragma unroll
        for (int u = 0; u < 2; u++) {
          const int i = tid + u * 512, k = i / 24, n = i % 24, ii = 2 * (n >> 3) + (n & 1), f = 4 * ii + ((n & 7) >> 1), d = k - (odd ? 4 : 0);
          uint16_t v = 0;
          if (d >= 0 && d < 20 && ii < 5) asm volatile("ld.shared.u16 %0, [%1];" : "=h"(v) : "r"(sb + SM_WRAW + (d * 20 + f) * 2) : "memory");
          if (i < 768) sts16(sb + SM_WPHI + (k >> 3) * 384 + n * 16 + (k & 7) * 2, v);
        }
      }
      if (br == 0 && it == 6 && wg == 0) BULK_WAIT_READ();
      if (br == 1 && (it == 10 || it == 12)) {
        const int u = it == 12;
        if (!u) {
#pragma unroll
          for (int o = 16; o; o >>= 1) gs += __shfl_xor_sync(0xffffffffu, gs, o);
          if (lane == 0) sts32(sb + SM_BAR + 448 + (tid >> 5) * 4, __float_as_uint(1.f / (1.f + __expf(-gs))));
          mbar_wait(bar + 8 * B_ZERO, 0);
          stage(sb + SM_X + wg * 8192, 0);
        } else {
          BULK_WAIT_READ();
          bar_sync(1 + wg, 128);
          stage(sb + SM_X + wg * 8192, 16);
        }
        PROXY_FENCE();
        bar_sync(1 + wg, 128);
        tma5d_store_if(wt == 0 && !(u && narrow_a), &maps.qst, sb + SM_X + wg * 8192, ((ga0 + u) % 10) * 8, (ga0 + u) / 10, wg & 1, rb1);
        bulk_s2g_if(wt == 0 && !u, g_gate + rb1 * 128 + c1 * 16 + wg * 4, sb + SM_BAR + 448 + wg * 16, 16);
        BULK_COMMIT();
      }
      if (br == 1 && it == 15) signal_bulk_if(wt == 0, &g_cnt[C_TA]);
      if (br == 1 && it >= 17 && it <= 18 && wg == (it & 3)) {
        wait_count(&g_cnt[C_TA], epoch * 512);
        mbar_wait(bar + 8 * (B_EMPTY + (it - 17)), 0);
        mbar_expect_if(wt == 0, bar + 8 * (B_KVFULL + it - 17), P1_STB);
        tma5d_if(wt == 0, sb + (it - 17) * P1_STB, &maps.qld, c0, 1, (it - 17) * 4, bar + 8 * (B_KVFULL + it - 17));
      }
      if (br == 1 && it == 19) {
        mbar_wait(bar + 8 * (B_KVFULL + 0), 0);
        const uint8_t* qp = g_qkv + rb * QRB + c0 * 2048 + orow;
        load_frag(q[0], qp);
        load_frag(q[1], qp + 1024);
        bad = ldcg32(&g_kbad);
        sts16(sb + wg * 12288 + onepos, 0x3c00);
        PROXY_FENCE();
        mbar_arrive(bar + 8 * (B_READY + 0));
      }
    };
    const int ga_a = tile_atom(c1) + 2 * ch + (((c1 & 3) == 2 && wg == 0) ? 1 : 0);
    const bool narrow_a = ((c1 & 3) == 1 && wg == 3) || ((c1 & 3) == 2 && wg == 0);
    auto gate_step = [&](uint32_t dst, int ks) {
      if (ks == 0) mbar_wait(bar + 8 * B_AUX, 0);
      const uint32_t a = lds32(dst + grow * 128 + (((lane >> 2) ^ (grow & 7)) << 4) + t * 4), b = lds32(sb + SM_GW + ks * 128 + lane * 4);
      gs = fmaf(__uint_as_float(a << 16), __uint_as_float(b << 16), gs);
      gs = fmaf(__uint_as_float(a & 0xffff0000u), __uint_as_float(b & 0xffff0000u), gs);
      __syncwarp();
      mbar_arrive_if(ks == 9 && lane == 0, bar + 8 * B_ZERO);
    };
    auto tile = [&](auto BR) {
      constexpr int br = decltype(BR)::value;
      const int tl = c1 ^ br, k4 = tl & 3;
      const bool narrow = (k4 == 1 && wg == 3) || (k4 == 2 && wg == 0);
      const int a0 = 2 * ch + ((k4 == 2 && wg == 0) ? 1 : 0);
      if (!narrow) {
#pragma unroll 1
        for (int ks = 0; ks < 10; ks++) {
          const int it = br * 10 + ks, st = it & 3;
          mbar_wait(bar + 8 * (B_FULL + st), (it >> 2) & 1);
          TS_MARK(20 + it);
          const uint32_t dst = sb + st * P1_STB;
          const uint64_t da = mkdesc(dst + r * 8192, 16, 1024, 1), db = mkdesc(dst + 16384 + a0 * 8192, 8192, 1024, 1);
          WG_FENCE();
#pragma unroll
          for (int k = 0; k < 4; k++) wg128_ss(acc, da + k * 2, db + k * 128, (ks | k) != 0);
          WG_COMMIT();
          if (br == 0) gate_step(dst, ks);
          WG_WAIT(1);
          mbar_arrive_if(ks > 0 && wt == 0, bar + 8 * (B_EMPTY + ((it - 1) & 3)));
          duties(BR, it, ga_a, narrow_a);
        }
        WG_WAIT(0);
      } else {
#pragma unroll 1
        for (int ks = 0; ks < 10; ks++) {
          const int it = br * 10 + ks, st = it & 3;
          mbar_wait(bar + 8 * (B_FULL + st), (it >> 2) & 1);
          TS_MARK(20 + it);
          const uint32_t dst = sb + st * P1_STB;
          const uint64_t da = mkdesc(dst + r * 8192, 16, 1024, 1), db = mkdesc(dst + 16384 + a0 * 8192, 8192, 1024, 1);
          WG_FENCE();
#pragma unroll
          for (int k = 0; k < 4; k++) wg64_ss_of64(acc, da + k * 2, db + k * 128, (ks | k) != 0);
          WG_COMMIT();
          if (br == 0) gate_step(dst, ks);
          WG_WAIT(1);
          mbar_arrive_if(ks > 0 && wt == 0, bar + 8 * (B_EMPTY + ((it - 1) & 3)));
          duties(BR, it, ga_a, narrow_a);
        }
        WG_WAIT(0);
      }
      pin(acc);
      TS_MARK(2 + 2 * br);
      mbar_arrive_if(wt == 0, bar + 8 * (B_EMPTY + ((br * 10 + 9) & 3)));
      const int ga0 = tile_atom(tl) + a0;
      uint32_t m0 = 0, m1 = 0;
      if (br == 0) {
        const float sk0 = __uint_as_float(mufu0 ? (127u + 70u) << 23 : (127u - 69u) << 23);
        const float sk1 = __uint_as_float(mufu1 ? (127u + 70u) << 23 : (127u - 69u) << 23);
        pack_atom_a<0>(acc, pk, ga0, sk0, sk1, m0, m1);
        if (!narrow) pack_atom_a<1>(acc, pk, ga0 + 1, sk0, sk1, m0, m1);
        const uint32_t lim0 = (mufu0 ? 127u + 110u : 127u - 29u) << 7, lim1 = (mufu1 ? 127u + 110u : 127u - 29u) << 7;
        if ((m0 & 0x7fffu) >= lim0 || ((m0 >> 16) & 0x7fffu) >= lim0 || (m1 & 0x7fffu) >= lim1 || ((m1 >> 16) & 0x7fffu) >= lim1) { g_kbad = epoch; __threadfence(); }
      } else {
        pack_atom<0, 0>(acc, pk, 0.f, 0.f, m0, m1);
        pack_atom<0, 1>(acc, pk, 0.f, 0.f, m0, m1);
        if (ch) mbar_wait(bar + 8 * (B_EMPTY + 2), 0);
        const uint32_t stg = sb + (ch ? 2 * P1_STB : SM_X) + r * 16384;
        stage(stg, 0);
        stage(stg + 8192, 16);
        mbar_wait(bar + 8 * (B_KVFULL + 1), 0);
        sts16(sb + P1_STB + wg * 12288 + onepos, 0x3c00);
        PROXY_FENCE();
        mbar_arrive(bar + 8 * (B_READY + 1));
        bar_sync(1 + wg, 128);
        tma5d_store_if(wt == 0, &maps.qst, stg, (ga0 % 10) * 8, ga0 / 10, r, 16 + rb1);
        tma5d_store_if(wt == 32 * 0 && !narrow, &maps.qst, stg + 8192, ((ga0 + 1) % 10) * 8, (ga0 + 1) / 10, r, 16 + rb1);
        BULK_COMMIT();
      }
      TS_MARK(3 + 2 * br);
    };
    tile(Int<0>{});
    tile(Int<1>{});
  }

  if (odd ? t < 2 : t >= 2) {
    if (odd) { q[0][0] = 0; q[0][1] = 0; q[1][0] = 0; q[1][1] = 0; }
    else { q[0][4] = 0; q[0][5] = 0; q[1][4] = 0; q[1][5] = 0; }
  }
  {
    uint32_t m = 0;
#pragma unroll
    for (int i = 0; i < 6; i++) m = maxabs_bf16x2(m, maxabs_bf16x2(q[0][i], q[1][i]));
    bad = bad == (int)epoch || (m & 0x7fffu) >= ((127u - 50u) << 7) || ((m >> 16) & 0x7fffu) >= ((127u - 50u) << 7);
  }
#pragma unroll
  for (int i = 0; i < 4; i++) { qc[i] = t == 0 ? 0x1c801c80u : 0u; asm volatile("" : "+r"(qc[i])); }
  events = 0x01010110u | (0x2008000u >> (2 * wg)) | (wg == 0 ? 0x8000440u : wg == 1 ? 0x40000u : wg == 2 ? 0x20000000u : 0x420000u);
  mbar_wait(bar + 8 * (B_READY + 0), 0);
  }
  float o[2][12];
#pragma unroll
  for (int i = 0; i < 12; i++) { o[0][i] = 0.f; o[1][i] = 0.f; }
  {
    uint32_t dk0 = (uint32_t)mkdesc(sb, 1024, 0, 0), dk1 = (uint32_t)mkdesc(sb + 2048, SM_CONST - 2048, 0, 0), dv = (uint32_t)mkdesc(sb + 3072, 128, 0, 0);
    TS_MARK(6);
#pragma unroll 1
    for (int i = 0; i < 32; i++) {
      if ((events >> i) & 1) {
        if ((i & 3) == 0 || i == 27) {
          COORDS();
          const bool p = wt == 0;
          signal_bulk_if(p && i != 8 && (i != 24 || wg != 0), &g_cnt[i == 4 ? C_TB : i == 16 ? C_KV + h : C_OB + rb * 2 + (h >> 4)]);
          if (i == 4) mbar_arrive_if(p, bar + 8 * B_STG);
          if ((i & 7) == 0) {
            WG_WAIT(0);
            mbar_arrive_if(p, bar + 8 * (B_FREE - 1) + i);
            mbar_wait(bar + 8 * B_READY + i, 0);
          }
        } else if (i == 6 || i == 10 || i == 17 || i == 22 || i == 29) {
          COORDS();
          const bool p = lane == 0;
          if (i == 6) {
            mbar_wait(bar + 8 * B_STG, 0);
            if (w == 1) wait_count(&g_cnt[C_TB], epoch * 512);
            const uint32_t fb = bar + 8 * (w ? B_KB : B_KVFULL + 2);
            mbar_expect_if(p && w < 2, fb, P1_STB);
            tma5d_if(p && w < 2, sb + (2 + w) * P1_STB, &maps.qld, c0, 1, w ? 16 + qt * 4 : 8, fb);
          } else if (i == 29) {
            mbar_wait(bar + 8 * (B_FREE + 2), 0);
            mbar_wait(bar + 8 * B_B2, 0);
            p3_load_w(p && w < 3, w);
            wait_count(&g_cnt[C_OB + rb1 * 2 + kh], epoch * 16);
            p3_load_a(p && w < 3, w);
          } else {
            if (i != 22) {
              const int u = i == 17;
              const uint32_t fb = bar + 8 * (u ? B_KVFULL + 3 : B_QB);
              mbar_wait(bar + 8 * (B_FREE + u), 0);
              mbar_expect_if(wt == 0, fb, P1_STB);
              tma5d_if(wt == 0, sb + u * 3 * P1_STB, &maps.qld, c0, u, u ? 12 : 16 + qt * 4, fb);
            }
            if (i != 17) {
              const int u = i == 10 ? 2 : 3;
              mbar_wait(bar + 8 * (B_KVFULL + u), 0);
#pragma unroll
              for (int e = 0; e < 4; e++) sts16(sb + u * P1_STB + e * 12288 + onepos, 0x3c00);
              PROXY_FENCE();
              mbar_arrive(bar + 8 * (B_READY + u));
            }
          }
        } else if (i < 16) {
          WG_WAIT(0);
          COORDS();
          const uint64_t dw = mkdesc(sb + SM_WPHI, 384, 128, 0);
          TS_MARK(7);
          const uint32_t kb = sb + 3 * P1_STB + wg * 12288, ph = sb + SM_X + (wg & 1) * 10240;
          mbar_wait(bar + 8 * B_KB, 0);
          sts16(kb + onepos, 0x3f80);
          float p0[12], p1[12];
          phi_proj(p0, p1, kb, dw);
          if (wg < 2) mbar_wait(bar + 8 * (B_LINK + wg), 0);
          uint32_t phi[10];
          feature_map(phi, p0);
#pragma unroll
          for (int u = 0; u < 10; u++) sts32(ph + (u % 5) * 2048 + orow + (u / 5) * 128, phi[u]);
          feature_map(phi, p1);
#pragma unroll
          for (int u = 0; u < 10; u++) sts32(ph + (u % 5) * 2048 + orow + (u / 5) * 128 + 1024, phi[u]);
          PROXY_FENCE();
          bar_sync(1 + wg, 128);
          const uint64_t da = mkdesc(ph, 128, 2048, 0), db = mkdesc(kb + 3072, 128, 1024, 0);
          WG_FENCE();
#pragma unroll
          for (int kk = 0; kk < 8; kk++) {
            if (kk == 0) wg24_ss_bf16_tt_i(p0, da, db);
            else wg24_ss_bf16_tt(p0, da + kk * 16, db + (kk & 3) * 16 + (kk >> 2) * 384, 1);
          }
          WG_COMMIT();
          WG_WAIT(0);
          pin(p0);
          mbar_arrive_if(lane == 0 && wg >= 2, bar + 8 * (B_LINK + (wg & 1)));
          bar_sync(1 + wg, 128);
          const uint32_t ks = kb + ((w * 16 + g) * 24 + 2 * t) * 4;
#pragma unroll
          for (int j = 0; j < 3; j++) {
            if (w < 3) asm volatile("st.shared.v2.f32 [%0], {%1, %2};" ::"r"(ks + 32 * j), "f"(p0[4 * j]), "f"(p0[4 * j + 1]) : "memory");
            if (w < 2) asm volatile("st.shared.v2.f32 [%0], {%1, %2};" ::"r"(ks + 768 + 32 * j), "f"(p0[4 * j + 2]), "f"(p0[4 * j + 3]) : "memory");
          }
          PROXY_FENCE();
          bar_sync(1 + wg, 128);
          bulk_addf_if(wt == 0, g_kv + h * 960, kb, 3840);
          BULK_COMMIT();
          TS_MARK(8);
        } else if (i == 18) {
          COORDS();
          wait_count(&g_cnt[C_KV + h], epoch * 16);
          float v[8];
#pragma unroll
          for (int u = 0; u < 8; u++) v[u] = (u < 7 || wt < 64) ? __ldcg(&g_kv[h * 960 + u * 128 + wt]) : 0.f;
#pragma unroll
          for (int u = 0; u < 9; u++) {
            const int e = u * 128 + wt, f = e / 24, d = e % 24;
            sts16(sb + SM_KVB + (f >> 3) * 384 + d * 16 + (f & 7) * 2, u < 8 ? __bfloat16_as_ushort(__float2bfloat16(v[u < 8 ? u : 0])) : (uint16_t)0);
          }
          PROXY_FENCE();
          mbar_arrive(bar + 8 * B_KVB);
        } else {
          WG_WAIT(0);
          COORDS();
          const uint64_t dw = mkdesc(sb + SM_WPHI, 384, 128, 0);
          TS_MARK(9);
          float gt[4];
#pragma unroll
          for (int u = 0; u < 4; u++) gt[u] = 1.f - __ldcg(&g_gate[rb * 128 + (u >> 1) * 64 + w * 16 + g + (u & 1) * 8]);
          mbar_wait(bar + 8 * B_QB, 0);
          float p0[12], p1[12];
          phi_proj(p0, p1, sb + wg * 12288, dw);
          const uint64_t dkv = mkdesc(sb + SM_KVB, 384, 128, 0);
          auto readout = [&](float (&p)[12], float g0, float g1, uint32_t a) {
            uint32_t phi[10];
            feature_map(phi, p);
            WG_FENCE();
            wg24_rs_bf16_i(p, phi[0], phi[5], phi[1], phi[6], dkv);
            wg24_rs_bf16(p, phi[2], phi[7], phi[3], phi[8], dkv + 48, 1);
            wg24_rs_bf16(p, phi[4], phi[9], 0u, 0u, dkv + 96, 1);
            WG_COMMIT();
            WG_WAIT(0);
            pin(p);
            const float l0 = __shfl_sync(0xffffffffu, odd ? p[0] : p[8], lsrc), l1 = __shfl_sync(0xffffffffu, odd ? p[2] : p[10], lsrc);
            stage_o(p, __fdividef(g0, l0 + 1e-6f), __fdividef(g1, l1 + 1e-6f), a, v0, v2);
          };
          mbar_wait(bar + 8 * B_KVB, 0);
          readout(p0, gt[0], gt[1], ostg + orow);
          readout(p1, gt[2], gt[3], ostg + orow + 1024);
          PROXY_FENCE();
          bar_sync(1 + wg, 128);
          mbar_arrive_if(wt == 0, bar + 8 * B_B2);
          flush_o(wt == 0, g_o + rb * ORB + (80 + c0) * 2048, ostg, odd);
          TS_MARK(10);
        }
      }
      if (!(i & 3)) TS_MARK(40 + (i >> 2));
#pragma unroll
      for (int m = 0; m < 2; m++) {
        float s[32];
        uint32_t p[16];
        WG_FENCE();
        wg64_rs_bf16_i(s, q[m][0], q[m][1], q[m][2], q[m][3], desc_lohi(dk0, 8));
        wg64_rs_bf16(s, q[m][4], q[m][5], qc[2 * m], qc[2 * m + 1], desc_lohi(dk1, 8), 1);
        WG_COMMIT();
        WG_WAIT(0);
        constexpr int A = 2 * NMB, B = 16 - A;
#pragma unroll
        for (int j = 0; j < B; j++) {
          if ((j * A) % B < A) { const int a = j * A / B; p[a] = exp2_pair_mufu(s[2 * a], s[2 * a + 1]); }
          p[A + j] = exp2_pair(s[2 * (A + j)], s[2 * (A + j) + 1]);
        }
        WG_FENCE();
#pragma unroll
        for (int kk = 0; kk < 4; kk++) wg24_rs_f16_t(o[m], p[4 * kk], p[4 * kk + 1], p[4 * kk + 2], p[4 * kk + 3], desc_lohi(dv + kk * 16, 64), 1);
        WG_COMMIT();
      }
      dk0 += 384; dk1 += 384u - (384u << 16); dv += 384;
    }
  }
  {
    COORDS();
    float gt[4];
#pragma unroll
    for (int u = 0; u < 4; u++) gt[u] = __ldcg(&g_gate[rb * 128 + (u >> 1) * 64 + w * 16 + g + (u & 1) * 8]);
    WG_WAIT(0);
    pin(o[0]); pin(o[1]);
    TS_MARK(11);
    int big = 0;
#pragma unroll
    for (int m = 0; m < 2; m++) {
      const float l0 = __shfl_sync(0xffffffffu, odd ? o[m][0] : o[m][8], lsrc), l1 = __shfl_sync(0xffffffffu, odd ? o[m][2] : o[m][10], lsrc);
      const float r0 = rcp(l0), r1 = rcp(l1);
      float chk = 0.f, mx0 = 0.f, mx1 = 0.f;
#pragma unroll
      for (int i = 0; i < 12; i++) chk = fmaf(o[m][i], 0.f, chk);
#pragma unroll
      for (int i = 4; i < 6; i++) { mx0 = fmaxf(mx0, fabsf(o[m][i])); mx1 = fmaxf(mx1, fabsf(o[m][i + 2])); }
      bad |= !(chk == 0.f) || !(l0 >= 32.f) || !(l1 >= 32.f);
      big |= fmaxf(mx0 * r0, mx1 * r1) >= 1.220703125e-4f;
      stage_o(o[m], r0 * gt[2 * m], r1 * gt[2 * m + 1], ostg + orow + m * 1024, v0, v2);
    }
    PROXY_FENCE();
    const int anybad = __syncthreads_or(bad), anybig = __syncthreads_or(big);
    if (anybad || !anybig) attn_exact(x, wqkv, h, qt, sb + SM_X);
  }
  TS_MARK(12);

  COORDS();
  if (wg == 3) {
    flush_o(lane == 0, g_o + (qt * 4 + w) * ORB + c0 * 2048, sb + SM_X + w * 6144, odd);
    signal_bulk_if(lane == 0, &g_cnt[C_OA + (qt * 4 + w) * 2 + (h >> 4)]);
    TS_MARK(18);
    if (wt == 0) atomicAdd(&g_cnt[C_EPOCH], 1);
  } else if (wg == 2) {
    const bool p = lane == 0;
    if (w == 3) { p3_load_w(p, 3); p3_load_a(p, 3); }
    mbar_wait(bar + 8 * (B_P3EMPTY + w), 0);
    p3_load_w(p, 4 + w);
    if (w > 0) wait_count(&g_cnt[C_OA + rb1 * 2 + kh], epoch * 16);
    p3_load_a(p, 4 + w);
    if (w < 2) {
      mbar_wait(bar + 8 * (B_P3EMPTY + w), 1);
      p3_load_w(p, 8 + w);
      if (w == 0) wait_count(&g_cnt[C_OA + rb1 * 2 + kh], epoch * 16);
      p3_load_a(p, 8 + w);
    }
  } else {
    float acc[96];
    const bool wide = (cg & 1) == wg;
    const int skip = (!wide && (cg & 1)) ? 1 : 0;
    if (wide) {
#pragma unroll 1
      for (int j = 0; j < 10; j++) {
        mbar_wait(bar + 8 * (B_P3FULL + (j & 3)), (j >> 2) & 1);
        if (j == 5) TS_MARK(13);
        const uint32_t dst = sb + (j & 3) * P3_STB;
        const uint64_t da = mkdesc(dst + wg * 1024, 2048, 128, 0), db = mkdesc(dst + 16384, 8192, 1024, 1);
        WG_FENCE();
#pragma unroll
        for (int k = 0; k < 4; k++) wg192_ss(acc, da + k * 256, db + k * 128, (j | k) != 0);
        WG_COMMIT();
        WG_WAIT(1);
        mbar_arrive_if(j > 0 && wt == 0, bar + 8 * (B_P3EMPTY + ((j - 1) & 3)));
      }
      WG_WAIT(0);
    } else {
#pragma unroll 1
      for (int j = 0; j < 10; j++) {
        mbar_wait(bar + 8 * (B_P3FULL + (j & 3)), (j >> 2) & 1);
        if (j == 5) TS_MARK(13);
        const uint32_t dst = sb + (j & 3) * P3_STB;
        const uint64_t da = mkdesc(dst + wg * 1024, 2048, 128, 0), db = mkdesc(dst + 16384 + skip * 8192, 8192, 1024, 1);
        WG_FENCE();
#pragma unroll
        for (int k = 0; k < 4; k++) wg128_ss_of96(acc, da + k * 256, db + k * 128, (j | k) != 0);
        WG_COMMIT();
        WG_WAIT(1);
        mbar_arrive_if(j > 0 && wt == 0, bar + 8 * (B_P3EMPTY + ((j - 1) & 3)));
      }
      WG_WAIT(0);
    }
    pin(acc);
    TS_MARK(14);
    if (!wide) mbar_wait(bar + 8 * (B_P3EMPTY + 2), 1);
    const uint32_t stg = sb + (wide ? 4 : 2) * P3_STB;
    const int r = w * 16 + (lane & 15);
#pragma unroll
    for (int i = 0; i < 24; i += 2)
      if (i < 16 || wide) {
        const int ch = (i & 7) + (lane >> 4);
        stsm4(stg + (i >> 3) * 8192 + r * 128 + ((ch ^ (r & 7)) << 4), pack_bf16(acc[4 * i], acc[4 * i + 1]), pack_bf16(acc[4 * i + 2], acc[4 * i + 3]),
              pack_bf16(acc[4 * i + 4], acc[4 * i + 5]), pack_bf16(acc[4 * i + 6], acc[4 * i + 7]));
      }
    PROXY_FENCE();
    bar_sync(1 + wg, 128);
    if (wt < (wide ? 3 : 2)) {
      PROXY_FENCE_G();
      asm volatile("cp.reduce.async.bulk.tensor.2d.global.shared::cta.add.bulk_group [%0, {%2, %3}], [%1];" ::"l"(&maps.out), "r"(stg + wt * 8192),
                   "r"((atom3 + skip + wt) * 64), "r"(rb1 * 128 + wg * 64) : "memory");
      asm volatile("cp.async.bulk.commit_group;" ::: "memory");
      asm volatile("cp.async.bulk.wait_group 0;" ::: "memory");
    }
    TS_MARK(15);
  }
  TS_DUMP();
}

typedef CUresult (*EncodeFn)(CUtensorMap*, CUtensorMapDataType, cuuint32_t, void*, const cuuint64_t*, const cuuint64_t*, const cuuint32_t*, const cuuint32_t*,
                             CUtensorMapInterleave, CUtensorMapSwizzle, CUtensorMapL2promotion, CUtensorMapFloatOOBfill);
void encode(EncodeFn enc, CUtensorMap* m, void* p, int rank, const cuuint64_t* gd, const cuuint64_t* gs, const cuuint32_t* bd) {
  const cuuint32_t es[3] = {1, 1, 1};
  enc(m, CU_TENSOR_MAP_DATA_TYPE_BFLOAT16, rank, p, gd, gs, bd, es, CU_TENSOR_MAP_INTERLEAVE_NONE, CU_TENSOR_MAP_SWIZZLE_128B,
      CU_TENSOR_MAP_L2_PROMOTION_L2_128B, CU_TENSOR_MAP_FLOAT_OOB_FILL_NONE);
}

}

extern "C" void kernel_launch(void* const* d_in, const int* in_sizes, int n_in, void* d_out, int out_size) {
  static EncodeFn enc = nullptr;
  if (!enc) {
    cudaDriverEntryPointQueryResult qr;
    cudaGetDriverEntryPoint("cuTensorMapEncodeTiled", (void**)&enc, cudaEnableDefault, &qr);
    cudaFuncSetAttribute(gated_mix_kernel, cudaFuncAttributeMaxDynamicSharedMemorySize, SMEM_BYTES);
  }
  Maps m;
  {
    const cuuint64_t gd[2] = {640, 2048}, gs[1] = {1280};
    const cuuint32_t bx[2] = {64, 128}, bo[2] = {64, 64};
    encode(enc, &m.x, d_in[0], 2, gd, gs, bx);
    encode(enc, &m.out, d_out, 2, gd, gs, bo);
  }
  for (int b = 0; b < 2; b++) {
    const cuuint64_t gd[3] = {64, 640, 30}, gs[2] = {3840, 128}, gd3[3] = {64, 640, 10}, gs3[2] = {1280, 128};
    const cuuint32_t bd[3] = {64, 64, 4}, bd3[3] = {64, 64, 3};
    encode(enc, &m.w[b], d_in[b ? 4 : 1], 3, gd, gs, bd);
    encode(enc, &m.wo[b], d_in[b ? 6 : 2], 3, gd3, gs3, bd3);
  }
  {
    void* qp = nullptr;
    cudaGetSymbolAddress(&qp, g_qkv);
    const cuuint64_t gd[5] = {128, 80, 3, 2, 32}, gs[4] = {2048, QTY, 1024, QRB};
    const cuuint32_t bl[5] = {128, 3, 2, 2, 4}, bs[5] = {128, 8, 1, 1, 1}, es[5] = {1, 1, 1, 1, 1};
    enc(&m.qld, CU_TENSOR_MAP_DATA_TYPE_UINT64, 5, qp, gd, gs, bl, es, CU_TENSOR_MAP_INTERLEAVE_NONE, CU_TENSOR_MAP_SWIZZLE_NONE, CU_TENSOR_MAP_L2_PROMOTION_L2_128B, CU_TENSOR_MAP_FLOAT_OOB_FILL_NONE);
    enc(&m.qst, CU_TENSOR_MAP_DATA_TYPE_UINT64, 5, qp, gd, gs, bs, es, CU_TENSOR_MAP_INTERLEAVE_NONE, CU_TENSOR_MAP_SWIZZLE_NONE, CU_TENSOR_MAP_L2_PROMOTION_NONE, CU_TENSOR_MAP_FLOAT_OOB_FILL_NONE);
  }
  gated_mix_kernel<<<128, 512, SMEM_BYTES, cudaStreamPerThread>>>(m, (const __nv_bfloat16*)d_in[0], (const __nv_bfloat16*)d_in[1], (const __nv_bfloat16*)d_in[5],
                                                                 (const __nv_bfloat16*)d_in[7], d_in[4], d_in[2], d_in[6], (uint4*)d_out);
}
```

```cpp
#include <cuda_runtime.h>
#include <cuda.h>
#include <cuda_bf16.h>
#include <cuda_fp16.h>
#include <stdint.h>
#pragma nv_diag_suppress 550

namespace {

constexpr int QRB = 240 * 2048;
constexpr int QBR = 16 * QRB;
constexpr int QTY = 80 * 2048;
constexpr int ORB = 160 * 2048;
constexpr int NMB = 3;

__device__ __align__(1024) uint8_t g_qkv[2 * QBR];
__device__ __align__(1024) uint8_t g_o[16 * ORB];
__device__ float g_gate[2048];
__device__ __align__(16) float g_kv[32 * 960];
__device__ uint32_t g_kbad;
__device__ uint32_t g_fb[128 * 2048 * 20];
__device__ uint32_t g_cnt[192];
constexpr int C_EPOCH = 0, C_TA = 32, C_TB = 64, C_KV = 96, C_OB = 128, C_OA = 160;

#define TS_MARK(i)
#define TS_INIT()
#define TS_FIRST()
#define TS_DUMP()

__device__ __forceinline__ uint64_t mkdesc(uint32_t addr, uint32_t lbo, uint32_t sbo, int mode) {
  return (uint64_t)((addr & 0x3FFFF) >> 4) | ((uint64_t)(lbo >> 4) << 16) | ((uint64_t)(sbo >> 4) << 32) | ((uint64_t)mode << 62);
}
__device__ __forceinline__ uint64_t desc_lohi(uint32_t lo, uint32_t hi) { return ((uint64_t)hi << 32) | lo; }
#define WG_FENCE() asm volatile("wgmma.fence.sync.aligned;" ::: "memory")
#define WG_COMMIT() asm volatile("wgmma.commit_group.sync.aligned;" ::: "memory")
#define WG_WAIT(n) asm volatile("wgmma.wait_group.sync.aligned %0;" ::"n"(n) : "memory")
#define PROXY_FENCE() asm volatile("fence.proxy.async.shared::cta;" ::: "memory")
#define PROXY_FENCE_G() asm volatile("fence.proxy.async.global;" ::: "memory")
__device__ __forceinline__ void bar_sync(int id, int n) { asm volatile("bar.sync %0, %1;" ::"r"(id), "r"(n) : "memory"); }
__device__ __forceinline__ void mbar_init(uint32_t a, int c) { asm volatile("mbarrier.init.shared::cta.b64 [%0], %1;" ::"r"(a), "r"(c)); }
__device__ __forceinline__ uint32_t mbar_try(uint32_t a, int par) {
  uint32_t ok;
  asm volatile("{.reg .pred p; mbarrier.try_wait.parity.shared::cta.b64 p, [%1], %2; selp.b32 %0, 1, 0, p;}" : "=r"(ok) : "r"(a), "r"(par) : "memory");
  return ok;
}
__device__ __forceinline__ void mbar_wait(uint32_t a, int par) {
  for (int i = 0; !mbar_try(a, par); i++)
    if (i > (1 << 22)) break;
}
__device__ __forceinline__ void mbar_arrive(uint32_t a) { asm volatile("mbarrier.arrive.shared::cta.b64 _, [%0];" ::"r"(a) : "memory"); }
__device__ __forceinline__ void mbar_arrive_if(bool p, uint32_t a) {
  asm volatile("{.reg .pred p; setp.ne.b32 p, %0, 0; @p mbarrier.arrive.shared::cta.b64 _, [%1];}" ::"r"((int)p), "r"(a) : "memory");
}
__device__ __forceinline__ void mbar_expect_if(bool p, uint32_t a, int bytes) {
  asm volatile("{.reg .pred p; setp.ne.b32 p, %0, 0; @p mbarrier.arrive.expect_tx.shared::cta.b64 _, [%1], %2;}" ::"r"((int)p), "r"(a), "r"(bytes) : "memory");
}
__device__ __forceinline__ void tma2d_if(bool p, uint32_t dst, const CUtensorMap* m, int c0, int c1, uint32_t bar) {
  asm volatile("{.reg .pred p; setp.ne.b32 p, %0, 0; @p cp.async.bulk.tensor.2d.shared::cluster.global.mbarrier::complete_tx::bytes [%1], [%2, {%4, %5}], [%3];}"
               ::"r"((int)p), "r"(dst), "l"(m), "r"(bar), "r"(c0), "r"(c1) : "memory");
}
__device__ __forceinline__ void tma3d_if(bool p, uint32_t dst, const CUtensorMap* m, int c1, int c2, uint32_t bar) {
  asm volatile("{.reg .pred p; setp.ne.b32 p, %0, 0; @p cp.async.bulk.tensor.3d.shared::cluster.global.mbarrier::complete_tx::bytes [%1], [%2, {%6, %4, %5}], [%3];}"
               ::"r"((int)p), "r"(dst), "l"(m), "r"(bar), "r"(c1), "r"(c2), "r"(0) : "memory");
}
__device__ __forceinline__ void bulk_g2s_if(bool p, uint32_t dst, const void* src, int bytes, uint32_t bar) {
  asm volatile("{.reg .pred p; setp.ne.b32 p, %0, 0; @p cp.async.bulk.shared::cluster.global.mbarrier::complete_tx::bytes [%1], [%2], %3, [%4];}"
               ::"r"((int)p), "r"(dst), "l"(src), "r"(bytes), "r"(bar) : "memory");
}
__device__ __forceinline__ void tma5d_if(bool p, uint32_t dst, const CUtensorMap* m, int c1, int c2, int c4, uint32_t bar) {
  asm volatile("{.reg .pred p; setp.ne.b32 p, %0, 0; @p cp.async.bulk.tensor.5d.shared::cluster.global.mbarrier::complete_tx::bytes [%1], [%2, {%7, %4, %5, %7, %6}], [%3];}"
               ::"r"((int)p), "r"(dst), "l"(m), "r"(bar), "r"(c1), "r"(c2), "r"(c4), "r"(0) : "memory");
}
__device__ __forceinline__ void tma5d_store_if(bool p, const CUtensorMap* m, uint32_t src, int c1, int c2, int c3, int c4) {
  asm volatile("{.reg .pred p; setp.ne.b32 p, %0, 0; @p cp.async.bulk.tensor.5d.global.shared::cta.bulk_group [%1, {%7, %3, %4, %5, %6}], [%2];}"
               ::"r"((int)p), "l"(m), "r"(src), "r"(c1), "r"(c2), "r"(c3), "r"(c4), "r"(0) : "memory");
}
__device__ __forceinline__ void bulk_s2g_if(bool p, void* dst, uint32_t src, int bytes) {
  asm volatile("{.reg .pred p; setp.ne.b32 p, %0, 0; @p cp.async.bulk.global.shared::cta.bulk_group [%1], [%2], %3;}" ::"r"((int)p), "l"(dst), "r"(src), "r"(bytes) : "memory");
}
__device__ __forceinline__ void bulk_or_if(bool p, void* dst, uint32_t src, int bytes) {
  asm volatile("{.reg .pred p; setp.ne.b32 p, %0, 0; @p cp.reduce.async.bulk.global.shared::cta.bulk_group.or.b32 [%1], [%2], %3;}" ::"r"((int)p), "l"(dst), "r"(src), "r"(bytes) : "memory");
}
__device__ __forceinline__ void bulk_addf_if(bool p, void* dst, uint32_t src, int bytes) {
  asm volatile("{.reg .pred p; setp.ne.b32 p, %0, 0; @p cp.reduce.async.bulk.global.shared::cta.bulk_group.add.f32 [%1], [%2], %3;}" ::"r"((int)p), "l"(dst), "r"(src), "r"(bytes) : "memory");
}
#define BULK_COMMIT() asm volatile("cp.async.bulk.commit_group;" ::: "memory")
#define BULK_WAIT() asm volatile("cp.async.bulk.wait_group 0;" ::: "memory")
#define BULK_WAIT_READ() asm volatile("cp.async.bulk.wait_group.read 0;" ::: "memory")
__device__ __forceinline__ void signal_bulk_if(bool p, uint32_t* c) {
  asm volatile("{.reg .pred p; setp.ne.b32 p, %0, 0; cp.async.bulk.wait_group 0; @p red.relaxed.gpu.global.add.u32 [%1], 1;}" ::"r"((int)p), "l"(c) : "memory");
}
__device__ __forceinline__ void wait_count(const uint32_t* c, uint32_t target) {
  for (int i = 0;; i++) {
    uint32_t v;
    asm volatile("ld.relaxed.gpu.global.u32 %0, [%1];" : "=r"(v) : "l"(c) : "memory");
    if ((int)(v - target) >= 0) break;
    if (i > (1 << 20)) break;
  }
  PROXY_FENCE_G();
}
__device__ __forceinline__ uint32_t pack_bf16(float lo, float hi) { uint32_t r; asm("cvt.rn.bf16x2.f32 %0, %1, %2;" : "=r"(r) : "f"(hi), "f"(lo)); return r; }
__device__ __forceinline__ uint32_t pack_f16(float lo, float hi) { uint32_t r; asm("cvt.rn.f16x2.f32 %0, %1, %2;" : "=r"(r) : "f"(hi), "f"(lo)); return r; }
__device__ __forceinline__ float ex2(float a) { float r; asm("ex2.approx.ftz.f32 %0, %1;" : "=f"(r) : "f"(a)); return r; }
__device__ __forceinline__ float rcp(float a) { float r; asm("rcp.approx.ftz.f32 %0, %1;" : "=f"(r) : "f"(a)); return r; }
__device__ __forceinline__ uint32_t maxabs_bf16x2(uint32_t a, uint32_t b) { uint32_t r; asm("max.NaN.xorsign.abs.bf16x2 %0, %1, %2;" : "=r"(r) : "r"(a), "r"(b)); return r; }
__device__ __forceinline__ uint32_t ldg32(const void* p) { return __ldg(reinterpret_cast<const uint32_t*>(p)); }
__device__ __forceinline__ uint32_t ldcg32(const void* p) { uint32_t v; asm volatile("ld.global.cg.u32 %0, [%1];" : "=r"(v) : "l"(p) : "memory"); return v; }
__device__ __forceinline__ uint32_t lds32(uint32_t a) { uint32_t v; asm volatile("ld.shared.b32 %0, [%1];" : "=r"(v) : "r"(a) : "memory"); return v; }
__device__ __forceinline__ void sts32(uint32_t a, uint32_t v) { asm volatile("st.shared.b32 [%0], %1;" ::"r"(a), "r"(v) : "memory"); }
__device__ __forceinline__ void sts16(uint32_t a, uint16_t v) { asm volatile("st.shared.b16 [%0], %1;" ::"r"(a), "h"(v) : "memory"); }
__device__ __forceinline__ void stsm4(uint32_t a, uint32_t r0, uint32_t r1, uint32_t r2, uint32_t r3) {
  asm volatile("stmatrix.sync.aligned.m8n8.x4.shared.b16 [%0], {%1, %2, %3, %4};" ::"r"(a), "r"(r0), "r"(r1), "r"(r2), "r"(r3) : "memory");
}
template <int N> __device__ __forceinline__ void pin(float (&d)[N]) {
#pragma unroll
  for (int i = 0; i < N; i++) asm volatile("" : "+f"(d[i])::"memory");
}

__device__ __forceinline__ void wg128_ss(float (&d)[64], uint64_t da, uint64_t db, int scale_d) {
  asm volatile("{\n.reg .pred p;\nsetp.ne.b32 p, %66, 0;\n"
    "wgmma.mma_async.sync.aligned.m64n128k16.f32.bf16.bf16 "
    "{%0, %1, %2, %3, %4, %5, %6, %7, %8, %9, %10, %11, %12, %13, %14, %15,"
    "%16, %17, %18, %19, %20, %21, %22, %23, %24, %25, %26, %27, %28, %29, %30, %31,"
    "%32, %33, %34, %35, %36, %37, %38, %39, %40, %41, %42, %43, %44, %45, %46, %47,"
    "%48, %49, %50, %51, %52, %53, %54, %55, %56, %57, %58, %59, %60, %61, %62, %63}, "
    "%64, %65, p, 1, 1, 0, 1;\n}\n"
    : "+f"(d[0]), "+f"(d[1]), "+f"(d[2]), "+f"(d[3]), "+f"(d[4]), "+f"(d[5]), "+f"(d[6]), "+f"(d[7]),
      "+f"(d[8]), "+f"(d[9]), "+f"(d[10]), "+f"(d[11]), "+f"(d[12]), "+f"(d[13]), "+f"(d[14]), "+f"(d[15]),
      "+f"(d[16]), "+f"(d[17]), "+f"(d[18]), "+f"(d[19]), "+f"(d[20]), "+f"(d[21]), "+f"(d[22]), "+f"(d[23]),
      "+f"(d[24]), "+f"(d[25]), "+f"(d[26]), "+f"(d[27]), "+f"(d[28]), "+f"(d[29]), "+f"(d[30]), "+f"(d[31]),
      "+f"(d[32]), "+f"(d[33]), "+f"(d[34]), "+f"(d[35]), "+f"(d[36]), "+f"(d[37]), "+f"(d[38]), "+f"(d[39]),
      "+f"(d[40]), "+f"(d[41]), "+f"(d[42]), "+f"(d[43]), "+f"(d[44]), "+f"(d[45]), "+f"(d[46]), "+f"(d[47]),
      "+f"(d[48]), "+f"(d[49]), "+f"(d[50]), "+f"(d[51]), "+f"(d[52]), "+f"(d[53]), "+f"(d[54]), "+f"(d[55]),
      "+f"(d[56]), "+f"(d[57]), "+f"(d[58]), "+f"(d[59]), "+f"(d[60]), "+f"(d[61]), "+f"(d[62]), "+f"(d[63])
    : "l"(da), "l"(db), "r"(scale_d));
}

__device__ __forceinline__ void wg64_ss_of64(float (&d)[64], uint64_t da, uint64_t db, int scale_d) {
  asm volatile("{\n.reg .pred p;\nsetp.ne.b32 p, %34, 0;\n"
    "wgmma.mma_async.sync.aligned.m64n64k16.f32.bf16.bf16 "
    "{%0, %1, %2, %3, %4, %5, %6, %7, %8, %9, %10, %11, %12, %13, %14, %15,"
    "%16, %17, %18, %19, %20, %21, %22, %23, %24, %25, %26, %27, %28, %29, %30, %31}, "
    "%32, %33, p, 1, 1, 0, 1;\n}\n"
    : "+f"(d[0]), "+f"(d[1]), "+f"(d[2]), "+f"(d[3]), "+f"(d[4]), "+f"(d[5]), "+f"(d[6]), "+f"(d[7]),
      "+f"(d[8]), "+f"(d[9]), "+f"(d[10]), "+f"(d[11]), "+f"(d[12]), "+f"(d[13]), "+f"(d[14]), "+f"(d[15]),
      "+f"(d[16]), "+f"(d[17]), "+f"(d[18]), "+f"(d[19]), "+f"(d[20]), "+f"(d[21]), "+f"(d[22]), "+f"(d[23]),
      "+f"(d[24]), "+f"(d[25]), "+f"(d[26]), "+f"(d[27]), "+f"(d[28]), "+f"(d[29]), "+f"(d[30]), "+f"(d[31])
    : "l"(da), "l"(db), "r"(scale_d));
}

__device__ __forceinline__ void wg192_ss(float (&d)[96], uint64_t da, uint64_t db, int scale_d) {
  asm volatile("{\n.reg .pred p;\nsetp.ne.b32 p, %98, 0;\n"
    "wgmma.mma_async.sync.aligned.m64n192k16.f32.bf16.bf16 "
    "{%0, %1, %2, %3, %4, %5, %6, %7, %8, %9, %10, %11, %12, %13, %14, %15,"
    "%16, %17, %18, %19, %20, %21, %22, %23, %24, %25, %26, %27, %28, %29, %30, %31,"
    "%32, %33, %34, %35, %36, %37, %38, %39, %40, %41, %42, %43, %44, %45, %46, %47,"
    "%48, %49, %50, %51, %52, %53, %54, %55, %56, %57, %58, %59, %60, %61, %62, %63,"
    "%64, %65, %66, %67, %68, %69, %70, %71, %72, %73, %74, %75, %76, %77, %78, %79,"
    "%80, %81, %82, %83, %84, %85, %86, %87, %88, %89, %90, %91, %92, %93, %94, %95}, "
    "%96, %97, p, 1, 1, 0, 1;\n}\n"
    : "+f"(d[0]), "+f"(d[1]), "+f"(d[2]), "+f"(d[3]), "+f"(d[4]), "+f"(d[5]), "+f"(d[6]), "+f"(d[7]),
      "+f"(d[8]), "+f"(d[9]), "+f"(d[10]), "+f"(d[11]), "+f"(d[12]), "+f"(d[13]), "+f"(d[14]), "+f"(d[15]),
      "+f"(d[16]), "+f"(d[17]), "+f"(d[18]), "+f"(d[19]), "+f"(d[20]), "+f"(d[21]), "+f"(d[22]), "+f"(d[23]),
      "+f"(d[24]), "+f"(d[25]), "+f"(d[26]), "+f"(d[27]), "+f"(d[28]), "+f"(d[29]), "+f"(d[30]), "+f"(d[31]),
      "+f"(d[32]), "+f"(d[33]), "+f"(d[34]), "+f"(d[35]), "+f"(d[36]), "+f"(d[37]), "+f"(d[38]), "+f"(d[39]),
      "+f"(d[40]), "+f"(d[41]), "+f"(d[42]), "+f"(d[43]), "+f"(d[44]), "+f"(d[45]), "+f"(d[46]), "+f"(d[47]),
      "+f"(d[48]), "+f"(d[49]), "+f"(d[50]), "+f"(d[51]), "+f"(d[52]), "+f"(d[53]), "+f"(d[54]), "+f"(d[55]),
      "+f"(d[56]), "+f"(d[57]), "+f"(d[58]), "+f"(d[59]), "+f"(d[60]), "+f"(d[61]), "+f"(d[62]), "+f"(d[63]),
      "+f"(d[64]), "+f"(d[65]), "+f"(d[66]), "+f"(d[67]), "+f"(d[68]), "+f"(d[69]), "+f"(d[70]), "+f"(d[71]),
      "+f"(d[72]), "+f"(d[73]), "+f"(d[74]), "+f"(d[75]), "+f"(d[76]), "+f"(d[77]), "+f"(d[78]), "+f"(d[79]),
      "+f"(d[80]), "+f"(d[81]), "+f"(d[82]), "+f"(d[83]), "+f"(d[84]), "+f"(d[85]), "+f"(d[86]), "+f"(d[87]),
      "+f"(d[88]), "+f"(d[89]), "+f"(d[90]), "+f"(d[91]), "+f"(d[92]), "+f"(d[93]), "+f"(d[94]), "+f"(d[95])
    : "l"(da), "l"(db), "r"(scale_d));
}

__device__ __forceinline__ void wg128_ss_of96(float (&d)[96], uint64_t da, uint64_t db, int scale_d) {
  asm volatile("{\n.reg .pred p;\nsetp.ne.b32 p, %66, 0;\n"
    "wgmma.mma_async.sync.aligned.m64n128k16.f32.bf16.bf16 "
    "{%0, %1, %2, %3, %4, %5, %6, %7, %8, %9, %10, %11, %12, %13, %14, %15,"
    "%16, %17, %18, %19, %20, %21, %22, %23, %24, %25, %26, %27, %28, %29, %30, %31,"
    "%32, %33, %34, %35, %36, %37, %38, %39, %40, %41, %42, %43, %44, %45, %46, %47,"
    "%48, %49, %50, %51, %52, %53, %54, %55, %56, %57, %58, %59, %60, %61, %62, %63}, "
    "%64, %65, p, 1, 1, 0, 1;\n}\n"
    : "+f"(d[0]), "+f"(d[1]), "+f"(d[2]), "+f"(d[3]), "+f"(d[4]), "+f"(d[5]), "+f"(d[6]), "+f"(d[7]),
      "+f"(d[8]), "+f"(d[9]), "+f"(d[10]), "+f"(d[11]), "+f"(d[12]), "+f"(d[13]), "+f"(d[14]), "+f"(d[15]),
      "+f"(d[16]), "+f"(d[17]), "+f"(d[18]), "+f"(d[19]), "+f"(d[20]), "+f"(d[21]), "+f"(d[22]), "+f"(d[23]),
      "+f"(d[24]), "+f"(d[25]), "+f"(d[26]), "+f"(d[27]), "+f"(d[28]), "+f"(d[29]), "+f"(d[30]), "+f"(d[31]),
      "+f"(d[32]), "+f"(d[33]), "+f"(d[34]), "+f"(d[35]), "+f"(d[36]), "+f"(d[37]), "+f"(d[38]), "+f"(d[39]),
      "+f"(d[40]), "+f"(d[41]), "+f"(d[42]), "+f"(d[43]), "+f"(d[44]), "+f"(d[45]), "+f"(d[46]), "+f"(d[47]),
      "+f"(d[48]), "+f"(d[49]), "+f"(d[50]), "+f"(d[51]), "+f"(d[52]), "+f"(d[53]), "+f"(d[54]), "+f"(d[55]),
      "+f"(d[56]), "+f"(d[57]), "+f"(d[58]), "+f"(d[59]), "+f"(d[60]), "+f"(d[61]), "+f"(d[62]), "+f"(d[63])
    : "l"(da), "l"(db), "r"(scale_d));
}

__device__ __forceinline__ void wg64_rs_bf16(float (&d)[32], uint32_t a0, uint32_t a1, uint32_t a2, uint32_t a3, uint64_t db, int scale_d) {
  asm volatile("{\n.reg .pred p;\nsetp.ne.b32 p, %37, 0;\n"
    "wgmma.mma_async.sync.aligned.m64n64k16.f32.bf16.bf16 "
    "{%0, %1, %2, %3, %4, %5, %6, %7, %8, %9, %10, %11, %12, %13, %14, %15,"
    "%16, %17, %18, %19, %20, %21, %22, %23, %24, %25, %26, %27, %28, %29, %30, %31}, "
    "{%32, %33, %34, %35}, %36, p, 1, 1, 0;\n}\n"
    : "+f"(d[0]), "+f"(d[1]), "+f"(d[2]), "+f"(d[3]), "+f"(d[4]), "+f"(d[5]), "+f"(d[6]), "+f"(d[7]),
      "+f"(d[8]), "+f"(d[9]), "+f"(d[10]), "+f"(d[11]), "+f"(d[12]), "+f"(d[13]), "+f"(d[14]), "+f"(d[15]),
      "+f"(d[16]), "+f"(d[17]), "+f"(d[18]), "+f"(d[19]), "+f"(d[20]), "+f"(d[21]), "+f"(d[22]), "+f"(d[23]),
      "+f"(d[24]), "+f"(d[25]), "+f"(d[26]), "+f"(d[27]), "+f"(d[28]), "+f"(d[29]), "+f"(d[30]), "+f"(d[31])
    : "r"(a0), "r"(a1), "r"(a2), "r"(a3), "l"(db), "r"(scale_d));
}

__device__ __forceinline__ void wg24_rs_f16_t(float (&d)[12], uint32_t a0, uint32_t a1, uint32_t a2, uint32_t a3, uint64_t db, int scale_d) {
  asm volatile("{\n.reg .pred p;\nsetp.ne.b32 p, %17, 0;\n"
    "wgmma.mma_async.sync.aligned.m64n24k16.f32.f16.f16 "
    "{%0, %1, %2, %3, %4, %5, %6, %7, %8, %9, %10, %11}, "
    "{%12, %13, %14, %15}, %16, p, 1, 1, 1;\n}\n"
    : "+f"(d[0]), "+f"(d[1]), "+f"(d[2]), "+f"(d[3]), "+f"(d[4]), "+f"(d[5]), "+f"(d[6]), "+f"(d[7]),
      "+f"(d[8]), "+f"(d[9]), "+f"(d[10]), "+f"(d[11])
    : "r"(a0), "r"(a1), "r"(a2), "r"(a3), "l"(db), "r"(scale_d));
}

__device__ __forceinline__ void wg24_rs_bf16(float (&d)[12], uint32_t a0, uint32_t a1, uint32_t a2, uint32_t a3, uint64_t db, int scale_d) {
  asm volatile("{\n.reg .pred p;\nsetp.ne.b32 p, %17, 0;\n"
    "wgmma.mma_async.sync.aligned.m64n24k16.f32.bf16.bf16 "
    "{%0, %1, %2, %3, %4, %5, %6, %7, %8, %9, %10, %11}, "
    "{%12, %13, %14, %15}, %16, p, 1, 1, 0;\n}\n"
    : "+f"(d[0]), "+f"(d[1]), "+f"(d[2]), "+f"(d[3]), "+f"(d[4]), "+f"(d[5]), "+f"(d[6]), "+f"(d[7]),
      "+f"(d[8]), "+f"(d[9]), "+f"(d[10]), "+f"(d[11])
    : "r"(a0), "r"(a1), "r"(a2), "r"(a3), "l"(db), "r"(scale_d));
}

__device__ __forceinline__ void wg24_ss_bf16_tt(float (&d)[12], uint64_t da, uint64_t db, int scale_d) {
  asm volatile("{\n.reg .pred p;\nsetp.ne.b32 p, %14, 0;\n"
    "wgmma.mma_async.sync.aligned.m64n24k16.f32.bf16.bf16 "
    "{%0, %1, %2, %3, %4, %5, %6, %7, %8, %9, %10, %11}, "
    "%12, %13, p, 1, 1, 1, 1;\n}\n"
    : "+f"(d[0]), "+f"(d[1]), "+f"(d[2]), "+f"(d[3]), "+f"(d[4]), "+f"(d[5]), "+f"(d[6]), "+f"(d[7]),
      "+f"(d[8]), "+f"(d[9]), "+f"(d[10]), "+f"(d[11])
    : "l"(da), "l"(db), "r"(scale_d));
}

__device__ __forceinline__ void wg64_rs_bf16_i(float (&d)[32], uint32_t a0, uint32_t a1, uint32_t a2, uint32_t a3, uint64_t db) {
  asm volatile("{\n.reg .pred p;\nsetp.ne.b32 p, 0, 0;\n"
    "wgmma.mma_async.sync.aligned.m64n64k16.f32.bf16.bf16 "
    "{%0, %1, %2, %3, %4, %5, %6, %7, %8, %9, %10, %11, %12, %13, %14, %15,"
    "%16, %17, %18, %19, %20, %21, %22, %23, %24, %25, %26, %27, %28, %29, %30, %31}, "
    "{%32, %33, %34, %35}, %36, p, 1, 1, 0;\n}\n"
    : "=f"(d[0]), "=f"(d[1]), "=f"(d[2]), "=f"(d[3]), "=f"(d[4]), "=f"(d[5]), "=f"(d[6]), "=f"(d[7]),
      "=f"(d[8]), "=f"(d[9]), "=f"(d[10]), "=f"(d[11]), "=f"(d[12]), "=f"(d[13]), "=f"(d[14]), "=f"(d[15]),
      "=f"(d[16]), "=f"(d[17]), "=f"(d[18]), "=f"(d[19]), "=f"(d[20]), "=f"(d[21]), "=f"(d[22]), "=f"(d[23]),
      "=f"(d[24]), "=f"(d[25]), "=f"(d[26]), "=f"(d[27]), "=f"(d[28]), "=f"(d[29]), "=f"(d[30]), "=f"(d[31])
    : "r"(a0), "r"(a1), "r"(a2), "r"(a3), "l"(db));
}

__device__ __forceinline__ void wg24_rs_bf16_i(float (&d)[12], uint32_t a0, uint32_t a1, uint32_t a2, uint32_t a3, uint64_t db) {
  asm volatile("{\n.reg .pred p;\nsetp.ne.b32 p, 0, 0;\n"
    "wgmma.mma_async.sync.aligned.m64n24k16.f32.bf16.bf16 "
    "{%0, %1, %2, %3, %4, %5, %6, %7, %8, %9, %10, %11}, "
    "{%12, %13, %14, %15}, %16, p, 1, 1, 0;\n}\n"
    : "=f"(d[0]), "=f"(d[1]), "=f"(d[2]), "=f"(d[3]), "=f"(d[4]), "=f"(d[5]), "=f"(d[6]), "=f"(d[7]),
      "=f"(d[8]), "=f"(d[9]), "=f"(d[10]), "=f"(d[11])
    : "r"(a0), "r"(a1), "r"(a2), "r"(a3), "l"(db));
}

__device__ __forceinline__ void wg24_ss_bf16_tt_i(float (&d)[12], uint64_t da, uint64_t db) {
  asm volatile("{\n.reg .pred p;\nsetp.ne.b32 p, 0, 0;\n"
    "wgmma.mma_async.sync.aligned.m64n24k16.f32.bf16.bf16 "
    "{%0, %1, %2, %3, %4, %5, %6, %7, %8, %9, %10, %11}, "
    "%12, %13, p, 1, 1, 1, 1;\n}\n"
    : "=f"(d[0]), "=f"(d[1]), "=f"(d[2]), "=f"(d[3]), "=f"(d[4]), "=f"(d[5]), "=f"(d[6]), "=f"(d[7]),
      "=f"(d[8]), "=f"(d[9]), "=f"(d[10]), "=f"(d[11])
    : "l"(da), "l"(db));
}

__device__ __forceinline__ void wg24_ss_bf16(float (&d)[12], uint64_t da, uint64_t db, int scale_d) {
  asm volatile("{\n.reg .pred p;\nsetp.ne.b32 p, %14, 0;\n"
    "wgmma.mma_async.sync.aligned.m64n24k16.f32.bf16.bf16 "
    "{%0, %1, %2, %3, %4, %5, %6, %7, %8, %9, %10, %11}, "
    "%12, %13, p, 1, 1, 0, 0;\n}\n"
    : "+f"(d[0]), "+f"(d[1]), "+f"(d[2]), "+f"(d[3]), "+f"(d[4]), "+f"(d[5]), "+f"(d[6]), "+f"(d[7]),
      "+f"(d[8]), "+f"(d[9]), "+f"(d[10]), "+f"(d[11])
    : "l"(da), "l"(db), "r"(scale_d));
}

__device__ __forceinline__ void wg24_ss_bf16_i(float (&d)[12], uint64_t da, uint64_t db) {
  asm volatile("{\n.reg .pred p;\nsetp.ne.b32 p, 0, 0;\n"
    "wgmma.mma_async.sync.aligned.m64n24k16.f32.bf16.bf16 "
    "{%0, %1, %2, %3, %4, %5, %6, %7, %8, %9, %10, %11}, "
    "%12, %13, p, 1, 1, 0, 0;\n}\n"
    : "=f"(d[0]), "=f"(d[1]), "=f"(d[2]), "=f"(d[3]), "=f"(d[4]), "=f"(d[5]), "=f"(d[6]), "=f"(d[7]),
      "=f"(d[8]), "=f"(d[9]), "=f"(d[10]), "=f"(d[11])
    : "l"(da), "l"(db));
}

constexpr int P1_STB = 49152, P3_STB = 40960;
constexpr int SM_X = 196608;
constexpr int SM_KVB = SM_X + 24576;
constexpr int SM_GW = SM_X + 8192, SM_WRAW = SM_GW + 1280, SM_EP = SM_WRAW + 800;
constexpr int SM_CONST = SM_X + 32768, SM_WPHI = SM_CONST + 1024, SM_BAR = SM_WPHI + 1536;
constexpr int SMEM_BYTES = SM_BAR + 512;
constexpr int B_FULL = 0, B_AUX = 4, B_KB = 5, B_QB = 6, B_KVFULL = 7, B_P3FULL = 11, B_P3EMPTY = 15, B_EMPTY = 19, B_LINK = 23, B_FREE = 25,
              B_STG = 28, B_B2 = 29, B_ZERO = 30, B_READY = 31, B_KVB = 35;

template <int V> struct Int { static constexpr int value = V; };
struct Maps { CUtensorMap x, w[2], wo[2], out, qld, qst; };

__device__ __forceinline__ int tile_atom(int t) { return (t >> 2) * 15 + ((0xB740 >> ((t & 3) * 4)) & 15); }

template <int MODE, int A>
__device__ __forceinline__ void pack_atom(const float (&acc)[64], uint32_t (&r)[32], float s0, float s1, uint32_t& m0, uint32_t& m1) {
#pragma unroll
  for (int e = A * 16; e < A * 16 + 16; e++) {
    const float s = (e & 1) ? s1 : s0;
    if (MODE == 0) r[e] = pack_bf16(acc[2 * e], acc[2 * e + 1]);
    else if (MODE == 3) r[e] = pack_f16(acc[2 * e], acc[2 * e + 1]);
    else r[e] = pack_bf16(acc[2 * e] * s, acc[2 * e + 1] * s);
    if (MODE == 2) { if (e & 1) m1 = maxabs_bf16x2(m1, r[e]); else m0 = maxabs_bf16x2(m0, r[e]); }
  }
}
template <int A>
__device__ __forceinline__ void pack_atom_a(const float (&acc)[64], uint32_t (&r)[32], int ga, float sk0, float sk1, uint32_t& m0, uint32_t& m1) {
  if (ga < 10) { const float cq = __uint_as_float(463809372u); pack_atom<1, A>(acc, r, cq, cq, m0, m1); }
  else if (ga < 20) pack_atom<2, A>(acc, r, sk0, sk1, m0, m1);
  else pack_atom<3, A>(acc, r, 0.f, 0.f, m0, m1);
}

__device__ __forceinline__ uint32_t exp2_pair(float a, float b) {
  uint32_t z, w, h;
  asm volatile("cvt.pack.sat.s16.s32 %0, %2, %1;" : "=r"(z) : "r"(__float_as_uint(a)), "r"(__float_as_uint(b)));
  asm volatile("lop3.b32 %0, %1, 0x03ff03ff, 0x34003400, 0xEA;" : "=r"(w) : "r"(z));
  asm volatile("fma.rn.f16x2 %0, %1, %1, %2;" : "=r"(h) : "r"(w), "r"(0x36203620));
  asm volatile("fma.rn.f16x2 %0, %0, %1, %2;" : "+r"(h) : "r"(w), "r"(0x2e012e01));
  return h + z - w;
}
__device__ __forceinline__ uint32_t exp2_pair_mufu(float a, float b) {
  float x, y; uint32_t r;
  asm volatile("ex2.approx.ftz.f32 %0, %1;" : "=f"(x) : "f"(a));
  asm volatile("ex2.approx.ftz.f32 %0, %1;" : "=f"(y) : "f"(b));
  asm volatile("cvt.rn.f16x2.f32 %0, %1, %2;" : "=r"(r) : "f"(y), "f"(x));
  return r;
}
__device__ __forceinline__ void load_frag(uint32_t (&a)[6], const uint8_t* p) {
  a[0] = ldcg32(p); a[1] = ldcg32(p + 128); a[2] = ldcg32(p + 2048); a[3] = ldcg32(p + 2048 + 128); a[4] = ldcg32(p + 4096); a[5] = ldcg32(p + 4096 + 128);
}
template <bool EXACT>
__device__ __forceinline__ bool feature_rows(uint32_t (&phi)[10], const float (&p)[12]) {
  const float L = 1.4426950408889634f;
  bool ok = true;
#pragma unroll
  for (int r = 0; r < 2; r++) {
    const float v[5] = {p[2 * r], p[2 * r + 1], p[4 + 2 * r], p[5 + 2 * r], p[8 + 2 * r]};
    float ep[5], en[5];
    if (EXACT) {
      float mx = fmaxf(fmaxf(fmaxf(v[0], v[1]), fmaxf(v[2], v[3])), v[4]);
      float mn = fminf(fminf(fminf(v[0], v[1]), fminf(v[2], v[3])), v[4]);
      mx = fmaxf(mx, __shfl_xor_sync(0xffffffffu, mx, 1)); mn = fminf(mn, __shfl_xor_sync(0xffffffffu, mn, 1));
      mx = fmaxf(mx, __shfl_xor_sync(0xffffffffu, mx, 2)); mn = fminf(mn, __shfl_xor_sync(0xffffffffu, mn, 2));
#pragma unroll
      for (int i = 0; i < 5; i++) { ep[i] = ex2((v[i] - mx) * L); en[i] = ex2((mn - v[i]) * L); }
    } else {
#pragma unroll
      for (int i = 0; i < 5; i++) { const float u = v[i] * L; ep[i] = ex2(u); en[i] = ex2(-u); }
    }
    float sp = (ep[0] + ep[1]) + (ep[2] + ep[3]) + ep[4], sn = (en[0] + en[1]) + (en[2] + en[3]) + en[4];
    sp += __shfl_xor_sync(0xffffffffu, sp, 1); sn += __shfl_xor_sync(0xffffffffu, sn, 1);
    sp += __shfl_xor_sync(0xffffffffu, sp, 2); sn += __shfl_xor_sync(0xffffffffu, sn, 2);
    ok = ok && sp + sn < 1.2676506e30f;
    const float rp = rcp(sp), rn = rcp(sn);
#pragma unroll
    for (int i = 0; i < 5; i++) phi[5 * r + i] = pack_bf16(ep[i] * rp, en[i] * rn);
  }
  return ok;
}
__device__ __forceinline__ void feature_map(uint32_t (&phi)[10], const float (&p)[12]) {
  if (!__all_sync(0xffffffffu, feature_rows<false>(phi, p))) feature_rows<true>(phi, p);
}
__device__ __forceinline__ void phi_proj(float (&p0)[12], float (&p1)[12], uint32_t a, uint64_t dw) {
  const uint64_t da = mkdesc(a, 1024, 128, 0), db = mkdesc(a + 2048, 0, 128, 0);
  WG_FENCE();
  wg24_ss_bf16_i(p0, da, dw);
  wg24_ss_bf16(p0, db, dw + 48, 1);
  wg24_ss_bf16_i(p1, da + 384, dw);
  wg24_ss_bf16(p1, db + 384, dw + 48, 1);
  WG_COMMIT();
  WG_WAIT(0);
  pin(p0); pin(p1);
}
__device__ __forceinline__ void stage_o(const float (&o)[12], float s0, float s1, uint32_t a, bool v0, bool v2) {
#pragma unroll
  for (int j = 0; j < 3; j++) {
    const bool v = j == 1 || (j == 0 ? v0 : v2);
    sts32(a + j * 2048, v ? pack_bf16(o[4 * j] * s0, o[4 * j + 1] * s0) : 0u);
    sts32(a + j * 2048 + 128, v ? pack_bf16(o[4 * j + 2] * s1, o[4 * j + 3] * s1) : 0u);
  }
}
__device__ __forceinline__ void flush_o(bool p, uint8_t* dst, uint32_t src, bool odd) {
  bulk_s2g_if(p, dst + (odd ? 2048 : 0), src + (odd ? 2048 : 0), 4096);
  bulk_or_if(p, dst + (odd ? 0 : 4096), src + (odd ? 0 : 4096), 2048);
  BULK_COMMIT();
}

__device__ __forceinline__ void proj20(float (&acc)[20], const __nv_bfloat16* __restrict__ xr, const __nv_bfloat16* __restrict__ wc) {
#pragma unroll
  for (int d = 0; d < 20; d++) acc[d] = 0.f;
#pragma unroll 2
  for (int k = 0; k < 640; k++) {
    const float xv = __bfloat162float(xr[k]);
#pragma unroll
    for (int d = 0; d < 10; d++) {
      const uint32_t u = ldg32(wc + k * 1920 + 2 * d);
      acc[2 * d] = fmaf(xv, __uint_as_float(u << 16), acc[2 * d]);
      acc[2 * d + 1] = fmaf(xv, __uint_as_float(u & 0xffff0000u), acc[2 * d + 1]);
    }
  }
}
__device__ __noinline__ void attn_exact(const __nv_bfloat16* __restrict__ x, const __nv_bfloat16* __restrict__ wqkv, int h, int qt, uint32_t stg) {
  const int tid = threadIdx.x;
  uint32_t* kvs = g_fb + blockIdx.x * (2048 * 20);
  float a[20];
  for (int i = 0; i < 8; i++) {
    const int key = (i >> 1) * 512 + tid, ty = 1 + (i & 1);
    proj20(a, x + key * 640, wqkv + ty * 640 + h * 20);
#pragma unroll
    for (int d = 0; d < 10; d++) kvs[key * 20 + (i & 1) * 10 + d] = pack_bf16(a[2 * d], a[2 * d + 1]);
  }
  const int row = qt * 512 + tid;
  proj20(a, x + row * 640, wqkv + h * 20);
#pragma unroll
  for (int d = 0; d < 20; d++) a[d] = __bfloat162float(__float2bfloat16(a[d]));
  __syncthreads();
  float o[20], m = -INFINITY, l = 0.f;
#pragma unroll
  for (int d = 0; d < 20; d++) o[d] = 0.f;
  for (int key = 0; key < 2048; key++) {
    uint32_t u[20];
#pragma unroll
    for (int d = 0; d < 5; d++) {
      const uint4 t4 = *reinterpret_cast<const uint4*>(kvs + key * 20 + 4 * d);
      u[4 * d] = t4.x; u[4 * d + 1] = t4.y; u[4 * d + 2] = t4.z; u[4 * d + 3] = t4.w;
    }
    float s = 0.f;
#pragma unroll
    for (int d = 0; d < 10; d++) {
      s = fmaf(a[2 * d], __uint_as_float(u[d] << 16), s);
      s = fmaf(a[2 * d + 1], __uint_as_float(u[d] & 0xffff0000u), s);
    }
    s *= 0.22360679774997896f;
    const float mn = fmaxf(m, s), cr = __expf(m - mn), p = __expf(s - mn);
    m = mn;
    l = l * cr + p;
#pragma unroll
    for (int d = 0; d < 10; d++) {
      o[2 * d] = fmaf(p, __uint_as_float(u[10 + d] << 16), o[2 * d] * cr);
      o[2 * d + 1] = fmaf(p, __uint_as_float(u[10 + d] & 0xffff0000u), o[2 * d + 1] * cr);
    }
  }
  const float sc = __ldcg(&g_gate[row]) / l;
#pragma unroll
  for (int d = 0; d < 10; d++) {
    const int col = (h & 1) * 4 + 2 * d;
    sts32(stg + (tid >> 7) * 6144 + (col >> 3) * 2048 + (tid & 127) * 16 + (col & 7) * 2, pack_bf16(o[2 * d] * sc, o[2 * d + 1] * sc));
  }
  PROXY_FENCE();
  __syncthreads();
}

#define COORDS()                                                                                                        \
  int tid, bid;                                                                                                         \
  asm volatile("mov.u32 %0, %%tid.x;" : "=r"(tid));                                                                     \
  asm volatile("mov.u32 %0, %%ctaid.x;" : "=r"(bid));                                                                   \
  const int wg = __shfl_sync(0xffffffffu, tid >> 7, 0);                                                                 \
  const int lane = tid & 31, w = (tid >> 5) & 3, g = lane >> 2, t = lane & 3, wt = tid & 127;                           \
  const int rb1 = bid >> 3, c1 = bid & 7;                                       \
  const int h = bid >> 2, qt = bid & 3, rb = qt * 4 + wg;                    \
  const bool odd = h & 1;                                                                                               \
  const int c0 = (h * 5) >> 1;                                               \
  const int lsrc = (lane & ~3) | (odd ? 0 : 2);                                                                         \
  const bool v0 = !odd || t >= 2, v2 = odd || t < 2;                                                                    \
  const uint32_t ostg = sb + SM_X + wg * 6144, orow = (w * 16 + g) * 16 + t * 4;                                        \
  const uint32_t onepos = (wt >> 6) * 6144 + 3072 + (odd ? 0 : 2048 + 8) + (wt & 63) * 16;                              \
  const int kh = bid & 1, cg = (bid >> 1) & 3, atom3 = (cg >> 1) * 5 + (cg & 1) * 2;                                    \
  auto p3_load_w = [&](bool p, int j) {                                                                                 \
    const uint32_t fb = bar + 8 * (B_P3FULL + (j & 3));                                                                 \
    mbar_expect_if(p, fb, P3_STB);                                                                                      \
    tma3d_if(p, sb + (j & 3) * P3_STB + 16384, &maps.wo[j < 5], (kh * 5 + (j < 5 ? j : j - 5)) * 64, atom3, fb);       \
  };                                                                                                                    \
  auto p3_load_a = [&](bool p, int j) {                                                                                 \
    bulk_g2s_if(p, sb + (j & 3) * P3_STB, g_o + rb1 * ORB + ((j < 5 ? 10 + j : j - 5) + kh * 5) * 16384, 16384,         \
                bar + 8 * (B_P3FULL + (j & 3)));                                                                        \
  };                                                                                                                    \
  (void)g; (void)t; (void)wt; (void)rb1; (void)c1; (void)rb; (void)c0; (void)lsrc; (void)v0; (void)v2; (void)ostg;      \
  (void)orow; (void)onepos; (void)atom3; (void)p3_load_w; (void)p3_load_a

__global__ void __launch_bounds__(512, 1)
gated_mix_kernel(const __grid_constant__ Maps maps, const __nv_bfloat16* __restrict__ x, const __nv_bfloat16* __restrict__ wqkv, const __nv_bfloat16* __restrict__ w_phi,
                 const __nv_bfloat16* __restrict__ gate_w, const void* wqkv_b, const void* wo_a, const void* wo_b, uint4* __restrict__ out) {
  extern __shared__ __align__(1024) uint8_t smem_raw[];
  const uint32_t sb = (uint32_t)__cvta_generic_to_shared(smem_raw);
  const uint32_t bar = sb + SM_BAR;
  uint32_t q[2][6], qc[4], epoch, events;
  int bad;
  {
  COORDS();
  TS_INIT();

  auto p1_load = [&](bool p, int it) {
    const int st = it & 3, br = it >= 10, ks = it - br * 10;
    const uint32_t dst = sb + st * P1_STB, fb = bar + 8 * (B_FULL + st);
    mbar_expect_if(p, fb, P1_STB);
    tma2d_if(p, dst, &maps.x, ks * 64, rb1 * 128, fb);
    tma3d_if(p, dst + 16384, &maps.w[br], ks * 64, tile_atom(c1 ^ br), fb);
  };
  if (wt == 0) {
    mbar_init(bar + 8 * (B_FULL + wg), 1);
    asm volatile("fence.mbarrier_init.release.cluster;" ::: "memory");
    if (wg == 0) p1_load(true, 0);
  }
  if (tid == 64) {
    mbar_init(bar + 8 * B_AUX, 1);
    asm volatile("fence.mbarrier_init.release.cluster;" ::: "memory");
    mbar_expect_if(true, bar + 8 * B_AUX, 1280 + 800 + 16);
    bulk_g2s_if(true, sb + SM_GW, gate_w, 1280, bar + 8 * B_AUX);
    bulk_g2s_if(true, sb + SM_WRAW, w_phi + h * 400, 800, bar + 8 * B_AUX);
    bulk_g2s_if(true, sb + SM_EP, &g_cnt[C_EPOCH], 16, bar + 8 * B_AUX);
  }
  if (lane == 0) {
    const int wi = __shfl_sync(1u, tid >> 5, 0);
#pragma unroll
    for (int u = 0; u < 2; u++) {
      const int i = 35 - (wi + u * 16);
      if (i > B_AUX) mbar_init(bar + 8 * i, i < B_P3EMPTY ? 1 : i < B_EMPTY ? 2 : i < B_ZERO ? 4 : i == B_ZERO ? 16 : i < B_READY + 2 ? 512 : 128);
    }
    asm volatile("fence.mbarrier_init.release.cluster;" ::: "memory");
  }
  asm volatile("st.shared.v4.b32 [%0], {%1, %1, %1, %1};" ::"r"(sb + SM_X + tid * 16), "r"(0) : "memory");
  if (tid < 256) sts32(sb + SM_CONST + tid * 4, (tid & 3) ? 0u : ((tid >> 5) < NMB ? 0xdd02e192u : 0x00001ef0u));
  PROXY_FENCE();
  __syncthreads();
  if (wg > 0) p1_load(wt == 0, wg);
  TS_FIRST();
  TS_MARK(1);

  {
    float acc[64];
    const int r = wg & 1, ch = wg >> 1;
    const bool mufu0 = 2 * w < NMB, mufu1 = 2 * w + 1 < NMB;
    uint32_t pk[32];
    float gs = 0.f;
    const int grow = c1 * 16 + (tid >> 5);
    auto stage = [&](uint32_t stg, int e0) {
#pragma unroll
      for (int e = 0; e < 16; e += 4) stsm4(stg + (w * 16 + (lane & 15)) * 16 + (lane >> 4) * 1024 + e * 512, pk[e0 + e], pk[e0 + e + 1], pk[e0 + e + 2], pk[e0 + e + 3]);
    };
    auto duties = [&](auto BR, int it, int ga0, bool narrow_a) {
      constexpr int br = decltype(BR)::value;
      if (wg == (it & 3) && it >= 1 && it <= 16) {
        mbar_wait(bar + 8 * (B_EMPTY + ((it - 1) & 3)), ((it - 1) >> 2) & 1);
        p1_load(wt == 0, it + 3);
      }
      if (br == 0 && wg == 0 && it >= 1 && it <= 4) {
        const bool p = wt == 0;
        if (it < 4) bulk_s2g_if(p, reinterpret_cast<uint8_t*>(out) + bid * 20480 + (it - 1) * 8192, sb + SM_X, it == 3 ? 4096 : 8192);
        else bulk_s2g_if(p, g_kv + bid * 240, sb + SM_X, 960);
        bulk_s2g_if(p, g_o + rb1 * ORB + ((c1 * 4 + it - 1) * 5 + 2) * 2048, sb + SM_X, 2048);
        BULK_COMMIT();
      }
      if (br == 0 && it == 2 && wg == 1 && wt < 3) {
        const int bytes = wt == 0 ? 19200 : 6400;
        const uint8_t* p = reinterpret_cast<const uint8_t*>(wt == 0 ? wqkv_b : wt == 1 ? wo_a : wo_b) + bid * bytes;
        asm volatile("cp.async.bulk.prefetch.L2.global [%0], %1;" ::"l"(p), "r"(bytes) : "memory");
      }
      if (br == 0 && it == 3) {
        epoch = (lds32(sb + SM_EP) >> 7) + 1;
#pragma unroll
        for (int u = 0; u < 2; u++) {
          const int i = tid + u * 512, k = i / 24, n = i % 24, ii = 2 * (n >> 3) + (n & 1), f = 4 * ii + ((n & 7) >> 1), d = k - (odd ? 4 : 0);
          uint16_t v = 0;
          if (d >= 0 && d < 20 && ii < 5) asm volatile("ld.shared.u16 %0, [%1];" : "=h"(v) : "r"(sb + SM_WRAW + (d * 20 + f) * 2) : "memory");
          if (i < 768) sts16(sb + SM_WPHI + (k >> 3) * 384 + n * 16 + (k & 7) * 2, v);
        }
      }
      if (br == 0 && it == 6 && wg == 0) BULK_WAIT_READ();
      if (br == 1 && (it == 10 || it == 12)) {
        const int u = it == 12;
        if (!u) {
#pragma unroll
          for (int o = 16; o; o >>= 1) gs += __shfl_xor_sync(0xffffffffu, gs, o);
          if (lane == 0) sts32(sb + SM_BAR + 448 + (tid >> 5) * 4, __float_as_uint(1.f / (1.f + __expf(-gs))));
          mbar_wait(bar + 8 * B_ZERO, 0);
          stage(sb + SM_X + wg * 8192, 0);
        } else {
          BULK_WAIT_READ();
          bar_sync(1 + wg, 128);
          stage(sb + SM_X + wg * 8192, 16);
        }
        PROXY_FENCE();
        bar_sync(1 + wg, 128);
        tma5d_store_if(wt == 0 && !(u && narrow_a), &maps.qst, sb + SM_X + wg * 8192, ((ga0 + u) % 10) * 8, (ga0 + u) / 10, wg & 1, rb1);
        bulk_s2g_if(wt == 0 && !u, g_gate + rb1 * 128 + c1 * 16 + wg * 4, sb + SM_BAR + 448 + wg * 16, 16);
        BULK_COMMIT();
      }
      if (br == 1 && it == 15) signal_bulk_if(wt == 0, &g_cnt[C_TA]);
      if (br == 1 && it >= 17 && it <= 18 && wg == (it & 3)) {
        wait_count(&g_cnt[C_TA], epoch * 512);
        mbar_wait(bar + 8 * (B_EMPTY + (it - 17)), 0);
        mbar_expect_if(wt == 0, bar + 8 * (B_KVFULL + it - 17), P1_STB);
        tma5d_if(wt == 0, sb + (it - 17) * P1_STB, &maps.qld, c0, 1, (it - 17) * 4, bar + 8 * (B_KVFULL + it - 17));
      }
      if (br == 1 && it == 19) {
        mbar_wait(bar + 8 * (B_KVFULL + 0), 0);
        const uint8_t* qp = g_qkv + rb * QRB + c0 * 2048 + orow;
        load_frag(q[0], qp);
        load_frag(q[1], qp + 1024);
        bad = ldcg32(&g_kbad);
        sts16(sb + wg * 12288 + onepos, 0x3c00);
        PROXY_FENCE();
        mbar_arrive(bar + 8 * (B_READY + 0));
      }
    };
    const int ga_a = tile_atom(c1) + 2 * ch + (((c1 & 3) == 2 && wg == 0) ? 1 : 0);
    const bool narrow_a = ((c1 & 3) == 1 && wg == 3) || ((c1 & 3) == 2 && wg == 0);
    auto gate_step = [&](uint32_t dst, int ks) {
      if (ks == 0) mbar_wait(bar + 8 * B_AUX, 0);
      const uint32_t a = lds32(dst + grow * 128 + (((lane >> 2) ^ (grow & 7)) << 4) + t * 4), b = lds32(sb + SM_GW + ks * 128 + lane * 4);
      gs = fmaf(__uint_as_float(a << 16), __uint_as_float(b << 16), gs);
      gs = fmaf(__uint_as_float(a & 0xffff0000u), __uint_as_float(b & 0xffff0000u), gs);
      __syncwarp();
      mbar_arrive_if(ks == 9 && lane == 0, bar + 8 * B_ZERO);
    };
    auto tile = [&](auto BR) {
      constexpr int br = decltype(BR)::value;
      const int tl = c1 ^ br, k4 = tl & 3;
      const bool narrow = (k4 == 1 && wg == 3) || (k4 == 2 && wg == 0);
      const int a0 = 2 * ch + ((k4 == 2 && wg == 0) ? 1 : 0);
      if (!narrow) {
#pragma unroll 1
        for (int ks = 0; ks < 10; ks++) {
          const int it = br * 10 + ks, st = it & 3;
          mbar_wait(bar + 8 * (B_FULL + st), (it >> 2) & 1);
          TS_MARK(20 + it);
          const uint32_t dst = sb + st * P1_STB;
          const uint64_t da = mkdesc(dst + r * 8192, 16, 1024, 1), db = mkdesc(dst + 16384 + a0 * 8192, 8192, 1024, 1);
          WG_FENCE();
#pragma unroll
          for (int k = 0; k < 4; k++) wg128_ss(acc, da + k * 2, db + k * 128, (ks | k) != 0);
          WG_COMMIT();
          if (br == 0) gate_step(dst, ks);
          WG_WAIT(1);
          mbar_arrive_if(ks > 0 && wt == 0, bar + 8 * (B_EMPTY + ((it - 1) & 3)));
          duties(BR, it, ga_a, narrow_a);
        }
        WG_WAIT(0);
      } else {
#pragma unroll 1
        for (int ks = 0; ks < 10; ks++) {
          const int it = br * 10 + ks, st = it & 3;
          mbar_wait(bar + 8 * (B_FULL + st), (it >> 2) & 1);
          TS_MARK(20 + it);
          const uint32_t dst = sb + st * P1_STB;
          const uint64_t da = mkdesc(dst + r * 8192, 16, 1024, 1), db = mkdesc(dst + 16384 + a0 * 8192, 8192, 1024, 1);
          WG_FENCE();
#pragma unroll
          for (int k = 0; k < 4; k++) wg64_ss_of64(acc, da + k * 2, db + k * 128, (ks | k) != 0);
          WG_COMMIT();
          if (br == 0) gate_step(dst, ks);
          WG_WAIT(1);
          mbar_arrive_if(ks > 0 && wt == 0, bar + 8 * (B_EMPTY + ((it - 1) & 3)));
          duties(BR, it, ga_a, narrow_a);
        }
        WG_WAIT(0);
      }
      pin(acc);
      TS_MARK(2 + 2 * br);
      mbar_arrive_if(wt == 0, bar + 8 * (B_EMPTY + ((br * 10 + 9) & 3)));
      const int ga0 = tile_atom(tl) + a0;
      uint32_t m0 = 0, m1 = 0;
      if (br == 0) {
        const float sk0 = __uint_as_float(mufu0 ? (127u + 70u) << 23 : (127u - 69u) << 23);
        const float sk1 = __uint_as_float(mufu1 ? (127u + 70u) << 23 : (127u - 69u) << 23);
        pack_atom_a<0>(acc, pk, ga0, sk0, sk1, m0, m1);
        if (!narrow) pack_atom_a<1>(acc, pk, ga0 + 1, sk0, sk1, m0, m1);
        const uint32_t lim0 = (mufu0 ? 127u + 110u : 127u - 29u) << 7, lim1 = (mufu1 ? 127u + 110u : 127u - 29u) << 7;
        if ((m0 & 0x7fffu) >= lim0 || ((m0 >> 16) & 0x7fffu) >= lim0 || (m1 & 0x7fffu) >= lim1 || ((m1 >> 16) & 0x7fffu) >= lim1) { g_kbad = epoch; __threadfence(); }
      } else {
        pack_atom<0, 0>(acc, pk, 0.f, 0.f, m0, m1);
        pack_atom<0, 1>(acc, pk, 0.f, 0.f, m0, m1);
        if (ch) mbar_wait(bar + 8 * (B_EMPTY + 2), 0);
        const uint32_t stg = sb + (ch ? 2 * P1_STB : SM_X) + r * 16384;
        stage(stg, 0);
        stage(stg + 8192, 16);
        mbar_wait(bar + 8 * (B_KVFULL + 1), 0);
        sts16(sb + P1_STB + wg * 12288 + onepos, 0x3c00);
        PROXY_FENCE();
        mbar_arrive(bar + 8 * (B_READY + 1));
        bar_sync(1 + wg, 128);
        tma5d_store_if(wt == 0, &maps.qst, stg, (ga0 % 10) * 8, ga0 / 10, r, 16 + rb1);
        tma5d_store_if(wt == 32 * 0 && !narrow, &maps.qst, stg + 8192, ((ga0 + 1) % 10) * 8, (ga0 + 1) / 10, r, 16 + rb1);
        BULK_COMMIT();
      }
      TS_MARK(3 + 2 * br);
    };
    tile(Int<0>{});
    tile(Int<1>{});
  }

  if (odd ? t < 2 : t >= 2) {
    if (odd) { q[0][0] = 0; q[0][1] = 0; q[1][0] = 0; q[1][1] = 0; }
    else { q[0][4] = 0; q[0][5] = 0; q[1][4] = 0; q[1][5] = 0; }
  }
  {
    uint32_t m = 0;
#pragma unroll
    for (int i = 0; i < 6; i++) m = maxabs_bf16x2(m, maxabs_bf16x2(q[0][i], q[1][i]));
    bad = bad == (int)epoch || (m & 0x7fffu) >= ((127u - 50u) << 7) || ((m >> 16) & 0x7fffu) >= ((127u - 50u) << 7);
  }
#pragma unroll
  for (int i = 0; i < 4; i++) { qc[i] = t == 0 ? 0x1c801c80u : 0u; asm volatile("" : "+r"(qc[i])); }
  events = 0x01010110u | (0x2008000u >> (2 * wg)) | (wg == 0 ? 0x8000440u : wg == 1 ? 0x40000u : wg == 2 ? 0x20000000u : 0x420000u);
  mbar_wait(bar + 8 * (B_READY + 0), 0);
  }
  float o[2][12];
#pragma unroll
  for (int i = 0; i < 12; i++) { o[0][i] = 0.f; o[1][i] = 0.f; }
  {
    uint32_t dk0 = (uint32_t)mkdesc(sb, 1024, 0, 0), dk1 = (uint32_t)mkdesc(sb + 2048, SM_CONST - 2048, 0, 0), dv = (uint32_t)mkdesc(sb + 3072, 128, 0, 0);
    TS_MARK(6);
#pragma unroll 1
    for (int i = 0; i < 32; i++) {
      if ((events >> i) & 1) {
        if ((i & 3) == 0 || i == 27) {
          COORDS();
          const bool p = wt == 0;
          signal_bulk_if(p && i != 8 && (i != 24 || wg != 0), &g_cnt[i == 4 ? C_TB : i == 16 ? C_KV + h : C_OB + rb * 2 + (h >> 4)]);
          if (i == 4) mbar_arrive_if(p, bar + 8 * B_STG);
          if ((i & 7) == 0) {
            WG_WAIT(0);
            mbar_arrive_if(p, bar + 8 * (B_FREE - 1) + i);
            mbar_wait(bar + 8 * B_READY + i, 0);
          }
        } else if (i == 6 || i == 10 || i == 17 || i == 22 || i == 29) {
          COORDS();
          const bool p = lane == 0;
          if (i == 6) {
            mbar_wait(bar + 8 * B_STG, 0);
            if (w == 1) wait_count(&g_cnt[C_TB], epoch * 512);
            const uint32_t fb = bar + 8 * (w ? B_KB : B_KVFULL + 2);
            mbar_expect_if(p && w < 2, fb, P1_STB);
            tma5d_if(p && w < 2, sb + (2 + w) * P1_STB, &maps.qld, c0, 1, w ? 16 + qt * 4 : 8, fb);
          } else if (i == 29) {
            mbar_wait(bar + 8 * (B_FREE + 2), 0);
            mbar_wait(bar + 8 * B_B2, 0);
            p3_load_w(p && w < 3, w);
            wait_count(&g_cnt[C_OB + rb1 * 2 + kh], epoch * 16);
            p3_load_a(p && w < 3, w);
          } else {
            if (i != 22) {
              const int u = i == 17;
              const uint32_t fb = bar + 8 * (u ? B_KVFULL + 3 : B_QB);
              mbar_wait(bar + 8 * (B_FREE + u), 0);
              mbar_expect_if(wt == 0, fb, P1_STB);
              tma5d_if(wt == 0, sb + u * 3 * P1_STB, &maps.qld, c0, u, u ? 12 : 16 + qt * 4, fb);
            }
            if (i != 17) {
              const int u = i == 10 ? 2 : 3;
              mbar_wait(bar + 8 * (B_KVFULL + u), 0);
#pragma unroll
              for (int e = 0; e < 4; e++) sts16(sb + u * P1_STB + e * 12288 + onepos, 0x3c00);
              PROXY_FENCE();
              mbar_arrive(bar + 8 * (B_READY + u));
            }
          }
        } else if (i < 16) {
          WG_WAIT(0);
          COORDS();
          const uint64_t dw = mkdesc(sb + SM_WPHI, 384, 128, 0);
          TS_MARK(7);
          const uint32_t kb = sb + 3 * P1_STB + wg * 12288, ph = sb + SM_X + (wg & 1) * 10240;
          mbar_wait(bar + 8 * B_KB, 0);
          sts16(kb + onepos, 0x3f80);
          float p0[12], p1[12];
          phi_proj(p0, p1, kb, dw);
          if (wg < 2) mbar_wait(bar + 8 * (B_LINK + wg), 0);
          uint32_t phi[10];
          feature_map(phi, p0);
#pragma unroll
          for (int u = 0; u < 10; u++) sts32(ph + (u % 5) * 2048 + orow + (u / 5) * 128, phi[u]);
          feature_map(phi, p1);
#pragma unroll
          for (int u = 0; u < 10; u++) sts32(ph + (u % 5) * 2048 + orow + (u / 5) * 128 + 1024, phi[u]);
          PROXY_FENCE();
          bar_sync(1 + wg, 128);
          const uint64_t da = mkdesc(ph, 128, 2048, 0), db = mkdesc(kb + 3072, 128, 1024, 0);
          WG_FENCE();
#pragma unroll
          for (int kk = 0; kk < 8; kk++) {
            if (kk == 0) wg24_ss_bf16_tt_i(p0, da, db);
            else wg24_ss_bf16_tt(p0, da + kk * 16, db + (kk & 3) * 16 + (kk >> 2) * 384, 1);
          }
          WG_COMMIT();
          WG_WAIT(0);
          pin(p0);
          mbar_arrive_if(lane == 0 && wg >= 2, bar + 8 * (B_LINK + (wg & 1)));
          bar_sync(1 + wg, 128);
          const uint32_t ks = kb + ((w * 16 + g) * 24 + 2 * t) * 4;
#pragma unroll
          for (int j = 0; j < 3; j++) {
            if (w < 3) asm volatile("st.shared.v2.f32 [%0], {%1, %2};" ::"r"(ks + 32 * j), "f"(p0[4 * j]), "f"(p0[4 * j + 1]) : "memory");
            if (w < 2) asm volatile("st.shared.v2.f32 [%0], {%1, %2};" ::"r"(ks + 768 + 32 * j), "f"(p0[4 * j + 2]), "f"(p0[4 * j + 3]) : "memory");
          }
          PROXY_FENCE();
          bar_sync(1 + wg, 128);
          bulk_addf_if(wt == 0, g_kv + h * 960, kb, 3840);
          BULK_COMMIT();
          TS_MARK(8);
        } else if (i == 18) {
          COORDS();
          wait_count(&g_cnt[C_KV + h], epoch * 16);
          float v[8];
#pragma unroll
          for (int u = 0; u < 8; u++) v[u] = (u < 7 || wt < 64) ? __ldcg(&g_kv[h * 960 + u * 128 + wt]) : 0.f;
#pragma unroll
          for (int u = 0; u < 9; u++) {
            const int e = u * 128 + wt, f = e / 24, d = e % 24;
            sts16(sb + SM_KVB + (f >> 3) * 384 + d * 16 + (f & 7) * 2, u < 8 ? __bfloat16_as_ushort(__float2bfloat16(v[u < 8 ? u : 0])) : (uint16_t)0);
          }
          PROXY_FENCE();
          mbar_arrive(bar + 8 * B_KVB);
        } else {
          WG_WAIT(0);
          COORDS();
          const uint64_t dw = mkdesc(sb + SM_WPHI, 384, 128, 0);
          TS_MARK(9);
          float gt[4];
#pragma unroll
          for (int u = 0; u < 4; u++) gt[u] = 1.f - __ldcg(&g_gate[rb * 128 + (u >> 1) * 64 + w * 16 + g + (u & 1) * 8]);
          mbar_wait(bar + 8 * B_QB, 0);
          float p0[12], p1[12];
          phi_proj(p0, p1, sb + wg * 12288, dw);
          const uint64_t dkv = mkdesc(sb + SM_KVB, 384, 128, 0);
          auto readout = [&](float (&p)[12], float g0, float g1, uint32_t a) {
            uint32_t phi[10];
            feature_map(phi, p);
            WG_FENCE();
            wg24_rs_bf16_i(p, phi[0], phi[5], phi[1], phi[6], dkv);
            wg24_rs_bf16(p, phi[2], phi[7], phi[3], phi[8], dkv + 48, 1);
            wg24_rs_bf16(p, phi[4], phi[9], 0u, 0u, dkv + 96, 1);
            WG_COMMIT();
            WG_WAIT(0);
            pin(p);
            const float l0 = __shfl_sync(0xffffffffu, odd ? p[0] : p[8], lsrc), l1 = __shfl_sync(0xffffffffu, odd ? p[2] : p[10], lsrc);
            stage_o(p, __fdividef(g0, l0 + 1e-6f), __fdividef(g1, l1 + 1e-6f), a, v0, v2);
          };
          mbar_wait(bar + 8 * B_KVB, 0);
          readout(p0, gt[0], gt[1], ostg + orow);
          readout(p1, gt[2], gt[3], ostg + orow + 1024);
          PROXY_FENCE();
          bar_sync(1 + wg, 128);
          mbar_arrive_if(wt == 0, bar + 8 * B_B2);
          flush_o(wt == 0, g_o + rb * ORB + (80 + c0) * 2048, ostg, odd);
          TS_MARK(10);
        }
      }
      if (!(i & 3)) TS_MARK(40 + (i >> 2));
#pragma unroll
      for (int m = 0; m < 2; m++) {
        float s[32];
        uint32_t p[16];
        WG_FENCE();
        wg64_rs_bf16_i(s, q[m][0], q[m][1], q[m][2], q[m][3], desc_lohi(dk0, 8));
        wg64_rs_bf16(s, q[m][4], q[m][5], qc[2 * m], qc[2 * m + 1], desc_lohi(dk1, 8), 1);
        WG_COMMIT();
        WG_WAIT(0);
        constexpr int A = 2 * NMB, B = 16 - A;
#pragma unroll
        for (int j = 0; j < B; j++) {
          if ((j * A) % B < A) { const int a = j * A / B; p[a] = exp2_pair_mufu(s[2 * a], s[2 * a + 1]); }
          p[A + j] = exp2_pair(s[2 * (A + j)], s[2 * (A + j) + 1]);
        }
        WG_FENCE();
#pragma unroll
        for (int kk = 0; kk < 4; kk++) wg24_rs_f16_t(o[m], p[4 * kk], p[4 * kk + 1], p[4 * kk + 2], p[4 * kk + 3], desc_lohi(dv + kk * 16, 64), 1);
        WG_COMMIT();
      }
      dk0 += 384; dk1 += 384u - (384u << 16); dv += 384;
    }
  }
  {
    COORDS();
    float gt[4];
#pragma unroll
    for (int u = 0; u < 4; u++) gt[u] = __ldcg(&g_gate[rb * 128 + (u >> 1) * 64 + w * 16 + g + (u & 1) * 8]);
    WG_WAIT(0);
    pin(o[0]); pin(o[1]);
    TS_MARK(11);
    int big = 0;
#pragma unroll
    for (int m = 0; m < 2; m++) {
      const float l0 = __shfl_sync(0xffffffffu, odd ? o[m][0] : o[m][8], lsrc), l1 = __shfl_sync(0xffffffffu, odd ? o[m][2] : o[m][10], lsrc);
      const float r0 = rcp(l0), r1 = rcp(l1);
      float chk = 0.f, mx0 = 0.f, mx1 = 0.f;
#pragma unroll
      for (int i = 0; i < 12; i++) chk = fmaf(o[m][i], 0.f, chk);
#pragma unroll
      for (int i = 4; i < 6; i++) { mx0 = fmaxf(mx0, fabsf(o[m][i])); mx1 = fmaxf(mx1, fabsf(o[m][i + 2])); }
      bad |= !(chk == 0.f) || !(l0 >= 32.f) || !(l1 >= 32.f);
      big |= fmaxf(mx0 * r0, mx1 * r1) >= 1.220703125e-4f;
      stage_o(o[m], r0 * gt[2 * m], r1 * gt[2 * m + 1], ostg + orow + m * 1024, v0, v2);
    }
    PROXY_FENCE();
    const int anybad = __syncthreads_or(bad), anybig = __syncthreads_or(big);
    if (anybad || !anybig) attn_exact(x, wqkv, h, qt, sb + SM_X);
  }
  TS_MARK(12);

  COORDS();
  if (wg == 3) {
    flush_o(lane == 0, g_o + (qt * 4 + w) * ORB + c0 * 2048, sb + SM_X + w * 6144, odd);
    signal_bulk_if(lane == 0, &g_cnt[C_OA + (qt * 4 + w) * 2 + (h >> 4)]);
    TS_MARK(18);
    if (wt == 0) atomicAdd(&g_cnt[C_EPOCH], 1);
  } else if (wg == 2) {
    const bool p = lane == 0;
    if (w == 3) { p3_load_w(p, 3); p3_load_a(p, 3); }
    mbar_wait(bar + 8 * (B_P3EMPTY + w), 0);
    p3_load_w(p, 4 + w);
    if (w > 0) wait_count(&g_cnt[C_OA + rb1 * 2 + kh], epoch * 16);
    p3_load_a(p, 4 + w);
    if (w < 2) {
      mbar_wait(bar + 8 * (B_P3EMPTY + w), 1);
      p3_load_w(p, 8 + w);
      if (w == 0) wait_count(&g_cnt[C_OA + rb1 * 2 + kh], epoch * 16);
      p3_load_a(p, 8 + w);
    }
  } else {
    float acc[96];
    const bool wide = (cg & 1) == wg;
    const int skip = (!wide && (cg & 1)) ? 1 : 0;
    if (wide) {
#pragma unroll 1
      for (int j = 0; j < 10; j++) {
        mbar_wait(bar + 8 * (B_P3FULL + (j & 3)), (j >> 2) & 1);
        if (j == 5) TS_MARK(13);
        const uint32_t dst = sb + (j & 3) * P3_STB;
        const uint64_t da = mkdesc(dst + wg * 1024, 2048, 128, 0), db = mkdesc(dst + 16384, 8192, 1024, 1);
        WG_FENCE();
#pragma unroll
        for (int k = 0; k < 4; k++) wg192_ss(acc, da + k * 256, db + k * 128, (j | k) != 0);
        WG_COMMIT();
        WG_WAIT(1);
        mbar_arrive_if(j > 0 && wt == 0, bar + 8 * (B_P3EMPTY + ((j - 1) & 3)));
      }
      WG_WAIT(0);
    } else {
#pragma unroll 1
      for (int j = 0; j < 10; j++) {
        mbar_wait(bar + 8 * (B_P3FULL + (j & 3)), (j >> 2) & 1);
        if (j == 5) TS_MARK(13);
        const uint32_t dst = sb + (j & 3) * P3_STB;
        const uint64_t da = mkdesc(dst + wg * 1024, 2048, 128, 0), db = mkdesc(dst + 16384 + skip * 8192, 8192, 1024, 1);
        WG_FENCE();
#pragma unroll
        for (int k = 0; k < 4; k++) wg128_ss_of96(acc, da + k * 256, db + k * 128, (j | k) != 0);
        WG_COMMIT();
        WG_WAIT(1);
        mbar_arrive_if(j > 0 && wt == 0, bar + 8 * (B_P3EMPTY + ((j - 1) & 3)));
      }
      WG_WAIT(0);
    }
    pin(acc);
    TS_MARK(14);
    if (!wide) mbar_wait(bar + 8 * (B_P3EMPTY + 2), 1);
    const uint32_t stg = sb + (wide ? 4 : 2) * P3_STB;
    const int r = w * 16 + (lane & 15);
#pragma unroll
    for (int i = 0; i < 24; i += 2)
      if (i < 16 || wide) {
        const int ch = (i & 7) + (lane >> 4);
        stsm4(stg + (i >> 3) * 8192 + r * 128 + ((ch ^ (r & 7)) << 4), pack_bf16(acc[4 * i], acc[4 * i + 1]), pack_bf16(acc[4 * i + 2], acc[4 * i + 3]),
              pack_bf16(acc[4 * i + 4], acc[4 * i + 5]), pack_bf16(acc[4 * i + 6], acc[4 * i + 7]));
      }
    PROXY_FENCE();
    bar_sync(1 + wg, 128);
    if (wt < (wide ? 3 : 2)) {
      PROXY_FENCE_G();
      asm volatile("cp.reduce.async.bulk.tensor.2d.global.shared::cta.add.bulk_group [%0, {%2, %3}], [%1];" ::"l"(&maps.out), "r"(stg + wt * 8192),
                   "r"((atom3 + skip + wt) * 64), "r"(rb1 * 128 + wg * 64) : "memory");
      asm volatile("cp.async.bulk.commit_group;" ::: "memory");
      asm volatile("cp.async.bulk.wait_group 0;" ::: "memory");
    }
    TS_MARK(15);
  }
  TS_DUMP();
}

typedef CUresult (*EncodeFn)(CUtensorMap*, CUtensorMapDataType, cuuint32_t, void*, const cuuint64_t*, const cuuint64_t*, const cuuint32_t*, const cuuint32_t*,
                             CUtensorMapInterleave, CUtensorMapSwizzle, CUtensorMapL2promotion, CUtensorMapFloatOOBfill);
void encode(EncodeFn enc, CUtensorMap* m, void* p, int rank, const cuuint64_t* gd, const cuuint64_t* gs, const cuuint32_t* bd) {
  const cuuint32_t es[3] = {1, 1, 1};
  enc(m, CU_TENSOR_MAP_DATA_TYPE_BFLOAT16, rank, p, gd, gs, bd, es, CU_TENSOR_MAP_INTERLEAVE_NONE, CU_TENSOR_MAP_SWIZZLE_128B,
      CU_TENSOR_MAP_L2_PROMOTION_L2_128B, CU_TENSOR_MAP_FLOAT_OOB_FILL_NONE);
}

}

extern "C" void kernel_launch(void* const* d_in, const int* in_sizes, int n_in, void* d_out, int out_size) {
  static EncodeFn enc = nullptr;
  if (!enc) {
    cudaDriverEntryPointQueryResult qr;
    cudaGetDriverEntryPoint("cuTensorMapEncodeTiled", (void**)&enc, cudaEnableDefault, &qr);
    cudaFuncSetAttribute(gated_mix_kernel, cudaFuncAttributeMaxDynamicSharedMemorySize, SMEM_BYTES);
  }
  Maps m;
  {
    const cuuint64_t gd[2] = {640, 2048}, gs[1] = {1280};
    const cuuint32_t bx[2] = {64, 128}, bo[2] = {64, 64};
    encode(enc, &m.x, d_in[0], 2, gd, gs, bx);
    encode(enc, &m.out, d_out, 2, gd, gs, bo);
  }
  for (int b = 0; b < 2; b++) {
    const cuuint64_t gd[3] = {64, 640, 30}, gs[2] = {3840, 128}, gd3[3] = {64, 640, 10}, gs3[2] = {1280, 128};
    const cuuint32_t bd[3] = {64, 64, 4}, bd3[3] = {64, 64, 3};
    encode(enc, &m.w[b], d_in[b ? 4 : 1], 3, gd, gs, bd);
    encode(enc, &m.wo[b], d_in[b ? 6 : 2], 3, gd3, gs3, bd3);
  }
  {
    void* qp = nullptr;
    cudaGetSymbolAddress(&qp, g_qkv);
    const cuuint64_t gd[5] = {128, 80, 3, 2, 32}, gs[4] = {2048, QTY, 1024, QRB};
    const cuuint32_t bl[5] = {128, 3, 2, 2, 4}, bs[5] = {128, 8, 1, 1, 1}, es[5] = {1, 1, 1, 1, 1};
    enc(&m.qld, CU_TENSOR_MAP_DATA_TYPE_UINT64, 5, qp, gd, gs, bl, es, CU_TENSOR_MAP_INTERLEAVE_NONE, CU_TENSOR_MAP_SWIZZLE_NONE, CU_TENSOR_MAP_L2_PROMOTION_L2_128B, CU_TENSOR_MAP_FLOAT_OOB_FILL_NONE);
    enc(&m.qst, CU_TENSOR_MAP_DATA_TYPE_UINT64, 5, qp, gd, gs, bs, es, CU_TENSOR_MAP_INTERLEAVE_NONE, CU_TENSOR_MAP_SWIZZLE_NONE, CU_TENSOR_MAP_L2_PROMOTION_NONE, CU_TENSOR_MAP_FLOAT_OOB_FILL_NONE);
  }
  gated_mix_kernel<<<128, 512, SMEM_BYTES, cudaStreamPerThread>>>(m, (const __nv_bfloat16*)d_in[0], (const __nv_bfloat16*)d_in[1], (const __nv_bfloat16*)d_in[5],
                                                                 (const __nv_bfloat16*)d_in[7], d_in[4], d_in[2], d_in[6], (uint4*)d_out);
}
```

```cpp
#include <cuda_runtime.h>
#include <cuda.h>
#include <cuda_bf16.h>
#include <cuda_fp16.h>
#include <stdint.h>
#pragma nv_diag_suppress 550

namespace {

constexpr int QRB = 240 * 2048;
constexpr int QBR = 16 * QRB;
constexpr int QTY = 80 * 2048;
constexpr int ORB = 160 * 2048;
constexpr int NMB = 3;

__device__ __align__(1024) uint8_t g_qkv[2 * QBR];
__device__ __align__(1024) uint8_t g_o[16 * ORB];
__device__ float g_gate[2048];
__device__ __align__(16) float g_kv[32 * 960];
__device__ uint32_t g_kbad;
__device__ uint32_t g_fb[128 * 2048 * 20];
__device__ uint32_t g_cnt[192];
constexpr int C_EPOCH = 0, C_TA = 32, C_TB = 64, C_KV = 96, C_OB = 128, C_OA = 160;

#define TS_MARK(i)
#define TS_INIT()
#define TS_REG(x)
#define TS_PUT(i, x, th)
#define TS_FIRST()
#define TS_DUMP()

__device__ __forceinline__ uint64_t mkdesc(uint32_t addr, uint32_t lbo, uint32_t sbo, int mode) {
  return (uint64_t)((addr & 0x3FFFF) >> 4) | ((uint64_t)(lbo >> 4) << 16) | ((uint64_t)(sbo >> 4) << 32) | ((uint64_t)mode << 62);
}
__device__ __forceinline__ uint64_t desc_lohi(uint32_t lo, uint32_t hi) { return ((uint64_t)hi << 32) | lo; }
#define WG_FENCE() asm volatile("wgmma.fence.sync.aligned;" ::: "memory")
#define WG_COMMIT() asm volatile("wgmma.commit_group.sync.aligned;" ::: "memory")
#define WG_WAIT(n) asm volatile("wgmma.wait_group.sync.aligned %0;" ::"n"(n) : "memory")
#define PROXY_FENCE() asm volatile("fence.proxy.async.shared::cta;" ::: "memory")
#define PROXY_FENCE_G() asm volatile("fence.proxy.async.global;" ::: "memory")
__device__ __forceinline__ void bar_sync(int id, int n) { asm volatile("bar.sync %0, %1;" ::"r"(id), "r"(n) : "memory"); }
__device__ __forceinline__ void mbar_init(uint32_t a, int c) { asm volatile("mbarrier.init.shared::cta.b64 [%0], %1;" ::"r"(a), "r"(c)); }
__device__ __forceinline__ uint32_t mbar_try(uint32_t a, int par) {
  uint32_t ok;
  asm volatile("{.reg .pred p; mbarrier.try_wait.parity.shared::cta.b64 p, [%1], %2; selp.b32 %0, 1, 0, p;}" : "=r"(ok) : "r"(a), "r"(par) : "memory");
  return ok;
}
__device__ __forceinline__ void mbar_wait(uint32_t a, int par) {
  for (int i = 0; !mbar_try(a, par); i++)
    if (i > (1 << 22)) break;
}
__device__ __forceinline__ void mbar_arrive(uint32_t a) { asm volatile("mbarrier.arrive.shared::cta.b64 _, [%0];" ::"r"(a) : "memory"); }
__device__ __forceinline__ void mbar_arrive_if(bool p, uint32_t a) {
  asm volatile("{.reg .pred p; setp.ne.b32 p, %0, 0; @p mbarrier.arrive.shared::cta.b64 _, [%1];}" ::"r"((int)p), "r"(a) : "memory");
}
__device__ __forceinline__ void mbar_expect_if(bool p, uint32_t a, int bytes) {
  asm volatile("{.reg .pred p; setp.ne.b32 p, %0, 0; @p mbarrier.arrive.expect_tx.shared::cta.b64 _, [%1], %2;}" ::"r"((int)p), "r"(a), "r"(bytes) : "memory");
}
__device__ __forceinline__ void tma2d_if(bool p, uint32_t dst, const CUtensorMap* m, int c0, int c1, uint32_t bar) {
  asm volatile("{.reg .pred p; setp.ne.b32 p, %0, 0; @p cp.async.bulk.tensor.2d.shared::cluster.global.mbarrier::complete_tx::bytes [%1], [%2, {%4, %5}], [%3];}"
               ::"r"((int)p), "r"(dst), "l"(m), "r"(bar), "r"(c0), "r"(c1) : "memory");
}
__device__ __forceinline__ void tma3d_if(bool p, uint32_t dst, const CUtensorMap* m, int c1, int c2, uint32_t bar) {
  asm volatile("{.reg .pred p; setp.ne.b32 p, %0, 0; @p cp.async.bulk.tensor.3d.shared::cluster.global.mbarrier::complete_tx::bytes [%1], [%2, {%6, %4, %5}], [%3];}"
               ::"r"((int)p), "r"(dst), "l"(m), "r"(bar), "r"(c1), "r"(c2), "r"(0) : "memory");
}
__device__ __forceinline__ void bulk_g2s_if(bool p, uint32_t dst, const void* src, int bytes, uint32_t bar) {
  asm volatile("{.reg .pred p; setp.ne.b32 p, %0, 0; @p cp.async.bulk.shared::cluster.global.mbarrier::complete_tx::bytes [%1], [%2], %3, [%4];}"
               ::"r"((int)p), "r"(dst), "l"(src), "r"(bytes), "r"(bar) : "memory");
}
__device__ __forceinline__ void tma5d_if(bool p, uint32_t dst, const CUtensorMap* m, int c1, int c2, int c4, uint32_t bar) {
  asm volatile("{.reg .pred p; setp.ne.b32 p, %0, 0; @p cp.async.bulk.tensor.5d.shared::cluster.global.mbarrier::complete_tx::bytes [%1], [%2, {%7, %4, %5, %7, %6}], [%3];}"
               ::"r"((int)p), "r"(dst), "l"(m), "r"(bar), "r"(c1), "r"(c2), "r"(c4), "r"(0) : "memory");
}
__device__ __forceinline__ void tma5d_store_if(bool p, const CUtensorMap* m, uint32_t src, int c1, int c2, int c3, int c4) {
  asm volatile("{.reg .pred p; setp.ne.b32 p, %0, 0; @p cp.async.bulk.tensor.5d.global.shared::cta.bulk_group [%1, {%7, %3, %4, %5, %6}], [%2];}"
               ::"r"((int)p), "l"(m), "r"(src), "r"(c1), "r"(c2), "r"(c3), "r"(c4), "r"(0) : "memory");
}
__device__ __forceinline__ void bulk_s2g_if(bool p, void* dst, uint32_t src, int bytes) {
  asm volatile("{.reg .pred p; setp.ne.b32 p, %0, 0; @p cp.async.bulk.global.shared::cta.bulk_group [%1], [%2], %3;}" ::"r"((int)p), "l"(dst), "r"(src), "r"(bytes) : "memory");
}
__device__ __forceinline__ void bulk_or_if(bool p, void* dst, uint32_t src, int bytes) {
  asm volatile("{.reg .pred p; setp.ne.b32 p, %0, 0; @p cp.reduce.async.bulk.global.shared::cta.bulk_group.or.b32 [%1], [%2], %3;}" ::"r"((int)p), "l"(dst), "r"(src), "r"(bytes) : "memory");
}
__device__ __forceinline__ void bulk_addf_if(bool p, void* dst, uint32_t src, int bytes) {
  asm volatile("{.reg .pred p; setp.ne.b32 p, %0, 0; @p cp.reduce.async.bulk.global.shared::cta.bulk_group.add.f32 [%1], [%2], %3;}" ::"r"((int)p), "l"(dst), "r"(src), "r"(bytes) : "memory");
}
#define BULK_COMMIT() asm volatile("cp.async.bulk.commit_group;" ::: "memory")
#define BULK_WAIT() asm volatile("cp.async.bulk.wait_group 0;" ::: "memory")
#define BULK_WAIT_READ() asm volatile("cp.async.bulk.wait_group.read 0;" ::: "memory")
__device__ __forceinline__ void signal_bulk_if(bool p, uint32_t* c) {
  asm volatile("{.reg .pred p; setp.ne.b32 p, %0, 0; cp.async.bulk.wait_group 0; @p red.relaxed.gpu.global.add.u32 [%1], 1;}" ::"r"((int)p), "l"(c) : "memory");
}
__device__ __forceinline__ void wait_count(const uint32_t* c, uint32_t target) {
  for (int i = 0;; i++) {
    uint32_t v;
    asm volatile("ld.relaxed.gpu.global.u32 %0, [%1];" : "=r"(v) : "l"(c) : "memory");
    if ((int)(v - target) >= 0) break;
    if (i > (1 << 20)) break;
  }
  PROXY_FENCE_G();
}
__device__ __forceinline__ uint32_t pack_bf16(float lo, float hi) { uint32_t r; asm("cvt.rn.bf16x2.f32 %0, %1, %2;" : "=r"(r) : "f"(hi), "f"(lo)); return r; }
__device__ __forceinline__ uint32_t pack_f16(float lo, float hi) { uint32_t r; asm("cvt.rn.f16x2.f32 %0, %1, %2;" : "=r"(r) : "f"(hi), "f"(lo)); return r; }
__device__ __forceinline__ float ex2(float a) { float r; asm("ex2.approx.ftz.f32 %0, %1;" : "=f"(r) : "f"(a)); return r; }
__device__ __forceinline__ float rcp(float a) { float r; asm("rcp.approx.ftz.f32 %0, %1;" : "=f"(r) : "f"(a)); return r; }
__device__ __forceinline__ uint32_t maxabs_bf16x2(uint32_t a, uint32_t b) { uint32_t r; asm("max.NaN.xorsign.abs.bf16x2 %0, %1, %2;" : "=r"(r) : "r"(a), "r"(b)); return r; }
__device__ __forceinline__ uint32_t ldg32(const void* p) { return __ldg(reinterpret_cast<const uint32_t*>(p)); }
__device__ __forceinline__ uint32_t ldcg32(const void* p) { uint32_t v; asm volatile("ld.global.cg.u32 %0, [%1];" : "=r"(v) : "l"(p) : "memory"); return v; }
__device__ __forceinline__ uint32_t lds32(uint32_t a) { uint32_t v; asm volatile("ld.shared.b32 %0, [%1];" : "=r"(v) : "r"(a) : "memory"); return v; }
__device__ __forceinline__ void sts32(uint32_t a, uint32_t v) { asm volatile("st.shared.b32 [%0], %1;" ::"r"(a), "r"(v) : "memory"); }
__device__ __forceinline__ void sts16(uint32_t a, uint16_t v) { asm volatile("st.shared.b16 [%0], %1;" ::"r"(a), "h"(v) : "memory"); }
__device__ __forceinline__ void stsm4(uint32_t a, uint32_t r0, uint32_t r1, uint32_t r2, uint32_t r3) {
  asm volatile("stmatrix.sync.aligned.m8n8.x4.shared.b16 [%0], {%1, %2, %3, %4};" ::"r"(a), "r"(r0), "r"(r1), "r"(r2), "r"(r3) : "memory");
}
template <int N> __device__ __forceinline__ void pin(float (&d)[N]) {
#pragma unroll
  for (int i = 0; i < N; i++) asm volatile("" : "+f"(d[i])::"memory");
}

__device__ __forceinline__ void wg128_ss(float (&d)[64], uint64_t da, uint64_t db, int scale_d) {
  asm volatile("{\n.reg .pred p;\nsetp.ne.b32 p, %66, 0;\n"
    "wgmma.mma_async.sync.aligned.m64n128k16.f32.bf16.bf16 "
    "{%0, %1, %2, %3, %4, %5, %6, %7, %8, %9, %10, %11, %12, %13, %14, %15,"
    "%16, %17, %18, %19, %20, %21, %22, %23, %24, %25, %26, %27, %28, %29, %30, %31,"
    "%32, %33, %34, %35, %36, %37, %38, %39, %40, %41, %42, %43, %44, %45, %46, %47,"
    "%48, %49, %50, %51, %52, %53, %54, %55, %56, %57, %58, %59, %60, %61, %62, %63}, "
    "%64, %65, p, 1, 1, 0, 1;\n}\n"
    : "+f"(d[0]), "+f"(d[1]), "+f"(d[2]), "+f"(d[3]), "+f"(d[4]), "+f"(d[5]), "+f"(d[6]), "+f"(d[7]),
      "+f"(d[8]), "+f"(d[9]), "+f"(d[10]), "+f"(d[11]), "+f"(d[12]), "+f"(d[13]), "+f"(d[14]), "+f"(d[15]),
      "+f"(d[16]), "+f"(d[17]), "+f"(d[18]), "+f"(d[19]), "+f"(d[20]), "+f"(d[21]), "+f"(d[22]), "+f"(d[23]),
      "+f"(d[24]), "+f"(d[25]), "+f"(d[26]), "+f"(d[27]), "+f"(d[28]), "+f"(d[29]), "+f"(d[30]), "+f"(d[31]),
      "+f"(d[32]), "+f"(d[33]), "+f"(d[34]), "+f"(d[35]), "+f"(d[36]), "+f"(d[37]), "+f"(d[38]), "+f"(d[39]),
      "+f"(d[40]), "+f"(d[41]), "+f"(d[42]), "+f"(d[43]), "+f"(d[44]), "+f"(d[45]), "+f"(d[46]), "+f"(d[47]),
      "+f"(d[48]), "+f"(d[49]), "+f"(d[50]), "+f"(d[51]), "+f"(d[52]), "+f"(d[53]), "+f"(d[54]), "+f"(d[55]),
      "+f"(d[56]), "+f"(d[57]), "+f"(d[58]), "+f"(d[59]), "+f"(d[60]), "+f"(d[61]), "+f"(d[62]), "+f"(d[63])
    : "l"(da), "l"(db), "r"(scale_d));
}

__device__ __forceinline__ void wg64_ss_of64(float (&d)[64], uint64_t da, uint64_t db, int scale_d) {
  asm volatile("{\n.reg .pred p;\nsetp.ne.b32 p, %34, 0;\n"
    "wgmma.mma_async.sync.aligned.m64n64k16.f32.bf16.bf16 "
    "{%0, %1, %2, %3, %4, %5, %6, %7, %8, %9, %10, %11, %12, %13, %14, %15,"
    "%16, %17, %18, %19, %20, %21, %22, %23, %24, %25, %26, %27, %28, %29, %30, %31}, "
    "%32, %33, p, 1, 1, 0, 1;\n}\n"
    : "+f"(d[0]), "+f"(d[1]), "+f"(d[2]), "+f"(d[3]), "+f"(d[4]), "+f"(d[5]), "+f"(d[6]), "+f"(d[7]),
      "+f"(d[8]), "+f"(d[9]), "+f"(d[10]), "+f"(d[11]), "+f"(d[12]), "+f"(d[13]), "+f"(d[14]), "+f"(d[15]),
      "+f"(d[16]), "+f"(d[17]), "+f"(d[18]), "+f"(d[19]), "+f"(d[20]), "+f"(d[21]), "+f"(d[22]), "+f"(d[23]),
      "+f"(d[24]), "+f"(d[25]), "+f"(d[26]), "+f"(d[27]), "+f"(d[28]), "+f"(d[29]), "+f"(d[30]), "+f"(d[31])
    : "l"(da), "l"(db), "r"(scale_d));
}

__device__ __forceinline__ void wg192_ss(float (&d)[96], uint64_t da, uint64_t db, int scale_d) {
  asm volatile("{\n.reg .pred p;\nsetp.ne.b32 p, %98, 0;\n"
    "wgmma.mma_async.sync.aligned.m64n192k16.f32.bf16.bf16 "
    "{%0, %1, %2, %3, %4, %5, %6, %7, %8, %9, %10, %11, %12, %13, %14, %15,"
    "%16, %17, %18, %19, %20, %21, %22, %23, %24, %25, %26, %27, %28, %29, %30, %31,"
    "%32, %33, %34, %35, %36, %37, %38, %39, %40, %41, %42, %43, %44, %45, %46, %47,"
    "%48, %49, %50, %51, %52, %53, %54, %55, %56, %57, %58, %59, %60, %61, %62, %63,"
    "%64, %65, %66, %67, %68, %69, %70, %71, %72, %73, %74, %75, %76, %77, %78, %79,"
    "%80, %81, %82, %83, %84, %85, %86, %87, %88, %89, %90, %91, %92, %93, %94, %95}, "
    "%96, %97, p, 1, 1, 0, 1;\n}\n"
    : "+f"(d[0]), "+f"(d[1]), "+f"(d[2]), "+f"(d[3]), "+f"(d[4]), "+f"(d[5]), "+f"(d[6]), "+f"(d[7]),
      "+f"(d[8]), "+f"(d[9]), "+f"(d[10]), "+f"(d[11]), "+f"(d[12]), "+f"(d[13]), "+f"(d[14]), "+f"(d[15]),
      "+f"(d[16]), "+f"(d[17]), "+f"(d[18]), "+f"(d[19]), "+f"(d[20]), "+f"(d[21]), "+f"(d[22]), "+f"(d[23]),
      "+f"(d[24]), "+f"(d[25]), "+f"(d[26]), "+f"(d[27]), "+f"(d[28]), "+f"(d[29]), "+f"(d[30]), "+f"(d[31]),
      "+f"(d[32]), "+f"(d[33]), "+f"(d[34]), "+f"(d[35]), "+f"(d[36]), "+f"(d[37]), "+f"(d[38]), "+f"(d[39]),
      "+f"(d[40]), "+f"(d[41]), "+f"(d[42]), "+f"(d[43]), "+f"(d[44]), "+f"(d[45]), "+f"(d[46]), "+f"(d[47]),
      "+f"(d[48]), "+f"(d[49]), "+f"(d[50]), "+f"(d[51]), "+f"(d[52]), "+f"(d[53]), "+f"(d[54]), "+f"(d[55]),
      "+f"(d[56]), "+f"(d[57]), "+f"(d[58]), "+f"(d[59]), "+f"(d[60]), "+f"(d[61]), "+f"(d[62]), "+f"(d[63]),
      "+f"(d[64]), "+f"(d[65]), "+f"(d[66]), "+f"(d[67]), "+f"(d[68]), "+f"(d[69]), "+f"(d[70]), "+f"(d[71]),
      "+f"(d[72]), "+f"(d[73]), "+f"(d[74]), "+f"(d[75]), "+f"(d[76]), "+f"(d[77]), "+f"(d[78]), "+f"(d[79]),
      "+f"(d[80]), "+f"(d[81]), "+f"(d[82]), "+f"(d[83]), "+f"(d[84]), "+f"(d[85]), "+f"(d[86]), "+f"(d[87]),
      "+f"(d[88]), "+f"(d[89]), "+f"(d[90]), "+f"(d[91]), "+f"(d[92]), "+f"(d[93]), "+f"(d[94]), "+f"(d[95])
    : "l"(da), "l"(db), "r"(scale_d));
}

__device__ __forceinline__ void wg128_ss_of96(float (&d)[96], uint64_t da, uint64_t db, int scale_d) {
  asm volatile("{\n.reg .pred p;\nsetp.ne.b32 p, %66, 0;\n"
    "wgmma.mma_async.sync.aligned.m64n128k16.f32.bf16.bf16 "
    "{%0, %1, %2, %3, %4, %5, %6, %7, %8, %9, %10, %11, %12, %13, %14, %15,"
    "%16, %17, %18, %19, %20, %21, %22, %23, %24, %25, %26, %27, %28, %29, %30, %31,"
    "%32, %33, %34, %35, %36, %37, %38, %39, %40, %41, %42, %43, %44, %45, %46, %47,"
    "%48, %49, %50, %51, %52, %53, %54, %55, %56, %57, %58, %59, %60, %61, %62, %63}, "
    "%64, %65, p, 1, 1, 0, 1;\n}\n"
    : "+f"(d[0]), "+f"(d[1]), "+f"(d[2]), "+f"(d[3]), "+f"(d[4]), "+f"(d[5]), "+f"(d[6]), "+f"(d[7]),
      "+f"(d[8]), "+f"(d[9]), "+f"(d[10]), "+f"(d[11]), "+f"(d[12]), "+f"(d[13]), "+f"(d[14]), "+f"(d[15]),
      "+f"(d[16]), "+f"(d[17]), "+f"(d[18]), "+f"(d[19]), "+f"(d[20]), "+f"(d[21]), "+f"(d[22]), "+f"(d[23]),
      "+f"(d[24]), "+f"(d[25]), "+f"(d[26]), "+f"(d[27]), "+f"(d[28]), "+f"(d[29]), "+f"(d[30]), "+f"(d[31]),
      "+f"(d[32]), "+f"(d[33]), "+f"(d[34]), "+f"(d[35]), "+f"(d[36]), "+f"(d[37]), "+f"(d[38]), "+f"(d[39]),
      "+f"(d[40]), "+f"(d[41]), "+f"(d[42]), "+f"(d[43]), "+f"(d[44]), "+f"(d[45]), "+f"(d[46]), "+f"(d[47]),
      "+f"(d[48]), "+f"(d[49]), "+f"(d[50]), "+f"(d[51]), "+f"(d[52]), "+f"(d[53]), "+f"(d[54]), "+f"(d[55]),
      "+f"(d[56]), "+f"(d[57]), "+f"(d[58]), "+f"(d[59]), "+f"(d[60]), "+f"(d[61]), "+f"(d[62]), "+f"(d[63])
    : "l"(da), "l"(db), "r"(scale_d));
}

__device__ __forceinline__ void wg64_rs_bf16(float (&d)[32], uint32_t a0, uint32_t a1, uint32_t a2, uint32_t a3, uint64_t db, int scale_d) {
  asm volatile("{\n.reg .pred p;\nsetp.ne.b32 p, %37, 0;\n"
    "wgmma.mma_async.sync.aligned.m64n64k16.f32.bf16.bf16 "
    "{%0, %1, %2, %3, %4, %5, %6, %7, %8, %9, %10, %11, %12, %13, %14, %15,"
    "%16, %17, %18, %19, %20, %21, %22, %23, %24, %25, %26, %27, %28, %29, %30, %31}, "
    "{%32, %33, %34, %35}, %36, p, 1, 1, 0;\n}\n"
    : "+f"(d[0]), "+f"(d[1]), "+f"(d[2]), "+f"(d[3]), "+f"(d[4]), "+f"(d[5]), "+f"(d[6]), "+f"(d[7]),
      "+f"(d[8]), "+f"(d[9]), "+f"(d[10]), "+f"(d[11]), "+f"(d[12]), "+f"(d[13]), "+f"(d[14]), "+f"(d[15]),
      "+f"(d[16]), "+f"(d[17]), "+f"(d[18]), "+f"(d[19]), "+f"(d[20]), "+f"(d[21]), "+f"(d[22]), "+f"(d[23]),
      "+f"(d[24]), "+f"(d[25]), "+f"(d[26]), "+f"(d[27]), "+f"(d[28]), "+f"(d[29]), "+f"(d[30]), "+f"(d[31])
    : "r"(a0), "r"(a1), "r"(a2), "r"(a3), "l"(db), "r"(scale_d));
}

__device__ __forceinline__ void wg24_rs_f16_t(float (&d)[12], uint32_t a0, uint32_t a1, uint32_t a2, uint32_t a3, uint64_t db, int scale_d) {
  asm volatile("{\n.reg .pred p;\nsetp.ne.b32 p, %17, 0;\n"
    "wgmma.mma_async.sync.aligned.m64n24k16.f32.f16.f16 "
    "{%0, %1, %2, %3, %4, %5, %6, %7, %8, %9, %10, %11}, "
    "{%12, %13, %14, %15}, %16, p, 1, 1, 1;\n}\n"
    : "+f"(d[0]), "+f"(d[1]), "+f"(d[2]), "+f"(d[3]), "+f"(d[4]), "+f"(d[5]), "+f"(d[6]), "+f"(d[7]),
      "+f"(d[8]), "+f"(d[9]), "+f"(d[10]), "+f"(d[11])
    : "r"(a0), "r"(a1), "r"(a2), "r"(a3), "l"(db), "r"(scale_d));
}

__device__ __forceinline__ void wg24_rs_bf16(float (&d)[12], uint32_t a0, uint32_t a1, uint32_t a2, uint32_t a3, uint64_t db, int scale_d) {
  asm volatile("{\n.reg .pred p;\nsetp.ne.b32 p, %17, 0;\n"
    "wgmma.mma_async.sync.aligned.m64n24k16.f32.bf16.bf16 "
    "{%0, %1, %2, %3, %4, %5, %6, %7, %8, %9, %10, %11}, "
    "{%12, %13, %14, %15}, %16, p, 1, 1, 0;\n}\n"
    : "+f"(d[0]), "+f"(d[1]), "+f"(d[2]), "+f"(d[3]), "+f"(d[4]), "+f"(d[5]), "+f"(d[6]), "+f"(d[7]),
      "+f"(d[8]), "+f"(d[9]), "+f"(d[10]), "+f"(d[11])
    : "r"(a0), "r"(a1), "r"(a2), "r"(a3), "l"(db), "r"(scale_d));
}

__device__ __forceinline__ void wg24_ss_bf16_tt(float (&d)[12], uint64_t da, uint64_t db, int scale_d) {
  asm volatile("{\n.reg .pred p;\nsetp.ne.b32 p, %14, 0;\n"
    "wgmma.mma_async.sync.aligned.m64n24k16.f32.bf16.bf16 "
    "{%0, %1, %2, %3, %4, %5, %6, %7, %8, %9, %10, %11}, "
    "%12, %13, p, 1, 1, 1, 1;\n}\n"
    : "+f"(d[0]), "+f"(d[1]), "+f"(d[2]), "+f"(d[3]), "+f"(d[4]), "+f"(d[5]), "+f"(d[6]), "+f"(d[7]),
      "+f"(d[8]), "+f"(d[9]), "+f"(d[10]), "+f"(d[11])
    : "l"(da), "l"(db), "r"(scale_d));
}

__device__ __forceinline__ void wg64_rs_bf16_i(float (&d)[32], uint32_t a0, uint32_t a1, uint32_t a2, uint32_t a3, uint64_t db) {
  asm volatile("{\n.reg .pred p;\nsetp.ne.b32 p, 0, 0;\n"
    "wgmma.mma_async.sync.aligned.m64n64k16.f32.bf16.bf16 "
    "{%0, %1, %2, %3, %4, %5, %6, %7, %8, %9, %10, %11, %12, %13, %14, %15,"
    "%16, %17, %18, %19, %20, %21, %22, %23, %24, %25, %26, %27, %28, %29, %30, %31}, "
    "{%32, %33, %34, %35}, %36, p, 1, 1, 0;\n}\n"
    : "=f"(d[0]), "=f"(d[1]), "=f"(d[2]), "=f"(d[3]), "=f"(d[4]), "=f"(d[5]), "=f"(d[6]), "=f"(d[7]),
      "=f"(d[8]), "=f"(d[9]), "=f"(d[10]), "=f"(d[11]), "=f"(d[12]), "=f"(d[13]), "=f"(d[14]), "=f"(d[15]),
      "=f"(d[16]), "=f"(d[17]), "=f"(d[18]), "=f"(d[19]), "=f"(d[20]), "=f"(d[21]), "=f"(d[22]), "=f"(d[23]),
      "=f"(d[24]), "=f"(d[25]), "=f"(d[26]), "=f"(d[27]), "=f"(d[28]), "=f"(d[29]), "=f"(d[30]), "=f"(d[31])
    : "r"(a0), "r"(a1), "r"(a2), "r"(a3), "l"(db));
}

__device__ __forceinline__ void wg24_rs_bf16_i(float (&d)[12], uint32_t a0, uint32_t a1, uint32_t a2, uint32_t a3, uint64_t db) {
  asm volatile("{\n.reg .pred p;\nsetp.ne.b32 p, 0, 0;\n"
    "wgmma.mma_async.sync.aligned.m64n24k16.f32.bf16.bf16 "
    "{%0, %1, %2, %3, %4, %5, %6, %7, %8, %9, %10, %11}, "
    "{%12, %13, %14, %15}, %16, p, 1, 1, 0;\n}\n"
    : "=f"(d[0]), "=f"(d[1]), "=f"(d[2]), "=f"(d[3]), "=f"(d[4]), "=f"(d[5]), "=f"(d[6]), "=f"(d[7]),
      "=f"(d[8]), "=f"(d[9]), "=f"(d[10]), "=f"(d[11])
    : "r"(a0), "r"(a1), "r"(a2), "r"(a3), "l"(db));
}

__device__ __forceinline__ void wg24_ss_bf16_tt_i(float (&d)[12], uint64_t da, uint64_t db) {
  asm volatile("{\n.reg .pred p;\nsetp.ne.b32 p, 0, 0;\n"
    "wgmma.mma_async.sync.aligned.m64n24k16.f32.bf16.bf16 "
    "{%0, %1, %2, %3, %4, %5, %6, %7, %8, %9, %10, %11}, "
    "%12, %13, p, 1, 1, 1, 1;\n}\n"
    : "=f"(d[0]), "=f"(d[1]), "=f"(d[2]), "=f"(d[3]), "=f"(d[4]), "=f"(d[5]), "=f"(d[6]), "=f"(d[7]),
      "=f"(d[8]), "=f"(d[9]), "=f"(d[10]), "=f"(d[11])
    : "l"(da), "l"(db));
}

__device__ __forceinline__ void wg24_ss_bf16(float (&d)[12], uint64_t da, uint64_t db, int scale_d) {
  asm volatile("{\n.reg .pred p;\nsetp.ne.b32 p, %14, 0;\n"
    "wgmma.mma_async.sync.aligned.m64n24k16.f32.bf16.bf16 "
    "{%0, %1, %2, %3, %4, %5, %6, %7, %8, %9, %10, %11}, "
    "%12, %13, p, 1, 1, 0, 0;\n}\n"
    : "+f"(d[0]), "+f"(d[1]), "+f"(d[2]), "+f"(d[3]), "+f"(d[4]), "+f"(d[5]), "+f"(d[6]), "+f"(d[7]),
      "+f"(d[8]), "+f"(d[9]), "+f"(d[10]), "+f"(d[11])
    : "l"(da), "l"(db), "r"(scale_d));
}

__device__ __forceinline__ void wg24_ss_bf16_i(float (&d)[12], uint64_t da, uint64_t db) {
  asm volatile("{\n.reg .pred p;\nsetp.ne.b32 p, 0, 0;\n"
    "wgmma.mma_async.sync.aligned.m64n24k16.f32.bf16.bf16 "
    "{%0, %1, %2, %3, %4, %5, %6, %7, %8, %9, %10, %11}, "
    "%12, %13, p, 1, 1, 0, 0;\n}\n"
    : "=f"(d[0]), "=f"(d[1]), "=f"(d[2]), "=f"(d[3]), "=f"(d[4]), "=f"(d[5]), "=f"(d[6]), "=f"(d[7]),
      "=f"(d[8]), "=f"(d[9]), "=f"(d[10]), "=f"(d[11])
    : "l"(da), "l"(db));
}

constexpr int P1_STB = 49152, P3_STB = 40960;
constexpr int SM_X = 196608;
constexpr int SM_KVB = SM_X + 24576;
constexpr int SM_GW = SM_X + 8192, SM_WRAW = SM_GW + 1280, SM_EP = SM_WRAW + 800;
constexpr int SM_CONST = SM_X + 32768, SM_WPHI = SM_CONST + 1024, SM_BAR = SM_WPHI + 1536;
constexpr int SMEM_BYTES = SM_BAR + 512;
constexpr int B_FULL = 0, B_AUX = 4, B_KB = 5, B_QB = 6, B_KVFULL = 7, B_P3FULL = 11, B_P3EMPTY = 15, B_EMPTY = 19, B_LINK = 23, B_FREE = 25,
              B_STG = 28, B_B2 = 29, B_ZERO = 30, B_READY = 31, B_KVB = 35;

template <int V> struct Int { static constexpr int value = V; };
struct Maps { CUtensorMap x, w[2], wo[2], out, qld, qst; };

__device__ __forceinline__ int tile_atom(int t) { return (t >> 2) * 15 + ((0xB740 >> ((t & 3) * 4)) & 15); }

template <int MODE, int A>
__device__ __forceinline__ void pack_atom(const float (&acc)[64], uint32_t (&r)[32], float s0, float s1, uint32_t& m0, uint32_t& m1) {
#pragma unroll
  for (int e = A * 16; e < A * 16 + 16; e++) {
    const float s = (e & 1) ? s1 : s0;
    if (MODE == 0) r[e] = pack_bf16(acc[2 * e], acc[2 * e + 1]);
    else if (MODE == 3) r[e] = pack_f16(acc[2 * e], acc[2 * e + 1]);
    else r[e] = pack_bf16(acc[2 * e] * s, acc[2 * e + 1] * s);
    if (MODE == 2) { if (e & 1) m1 = maxabs_bf16x2(m1, r[e]); else m0 = maxabs_bf16x2(m0, r[e]); }
  }
}
template <int A>
__device__ __forceinline__ void pack_atom_a(const float (&acc)[64], uint32_t (&r)[32], int ga, float sk0, float sk1, uint32_t& m0, uint32_t& m1) {
  if (ga < 10) { const float cq = __uint_as_float(463809372u); pack_atom<1, A>(acc, r, cq, cq, m0, m1); }
  else if (ga < 20) pack_atom<2, A>(acc, r, sk0, sk1, m0, m1);
  else pack_atom<3, A>(acc, r, 0.f, 0.f, m0, m1);
}

__device__ __forceinline__ uint32_t exp2_pair(float a, float b) {
  uint32_t z, w, h;
  asm volatile("cvt.pack.sat.s16.s32 %0, %2, %1;" : "=r"(z) : "r"(__float_as_uint(a)), "r"(__float_as_uint(b)));
  asm volatile("lop3.b32 %0, %1, 0x03ff03ff, 0x34003400, 0xEA;" : "=r"(w) : "r"(z));
  asm volatile("fma.rn.f16x2 %0, %1, %1, %2;" : "=r"(h) : "r"(w), "r"(0x36203620));
  asm volatile("fma.rn.f16x2 %0, %0, %1, %2;" : "+r"(h) : "r"(w), "r"(0x2e012e01));
  return h + z - w;
}
__device__ __forceinline__ uint32_t exp2_pair_mufu(float a, float b) {
  float x, y; uint32_t r;
  asm volatile("ex2.approx.ftz.f32 %0, %1;" : "=f"(x) : "f"(a));
  asm volatile("ex2.approx.ftz.f32 %0, %1;" : "=f"(y) : "f"(b));
  asm volatile("cvt.rn.f16x2.f32 %0, %1, %2;" : "=r"(r) : "f"(y), "f"(x));
  return r;
}
__device__ __forceinline__ void load_frag(uint32_t (&a)[6], const uint8_t* p) {
  a[0] = ldcg32(p); a[1] = ldcg32(p + 128); a[2] = ldcg32(p + 2048); a[3] = ldcg32(p + 2048 + 128); a[4] = ldcg32(p + 4096); a[5] = ldcg32(p + 4096 + 128);
}
template <bool EXACT>
__device__ __forceinline__ bool feature_rows(uint32_t (&phi)[10], const float (&p)[12]) {
  const float L = 1.4426950408889634f;
  bool ok = true;
#pragma unroll
  for (int r = 0; r < 2; r++) {
    const float v[5] = {p[2 * r], p[2 * r + 1], p[4 + 2 * r], p[5 + 2 * r], p[8 + 2 * r]};
    float ep[5], en[5];
    if (EXACT) {
      float mx = fmaxf(fmaxf(fmaxf(v[0], v[1]), fmaxf(v[2], v[3])), v[4]);
      float mn = fminf(fminf(fminf(v[0], v[1]), fminf(v[2], v[3])), v[4]);
      mx = fmaxf(mx, __shfl_xor_sync(0xffffffffu, mx, 1)); mn = fminf(mn, __shfl_xor_sync(0xffffffffu, mn, 1));
      mx = fmaxf(mx, __shfl_xor_sync(0xffffffffu, mx, 2)); mn = fminf(mn, __shfl_xor_sync(0xffffffffu, mn, 2));
#pragma unroll
      for (int i = 0; i < 5; i++) { ep[i] = ex2((v[i] - mx) * L); en[i] = ex2((mn - v[i]) * L); }
    } else {
#pragma unroll
      for (int i = 0; i < 5; i++) { const float u = v[i] * L; ep[i] = ex2(u); en[i] = ex2(-u); }
    }
    float sp = (ep[0] + ep[1]) + (ep[2] + ep[3]) + ep[4], sn = (en[0] + en[1]) + (en[2] + en[3]) + en[4];
    sp += __shfl_xor_sync(0xffffffffu, sp, 1); sn += __shfl_xor_sync(0xffffffffu, sn, 1);
    sp += __shfl_xor_sync(0xffffffffu, sp, 2); sn += __shfl_xor_sync(0xffffffffu, sn, 2);
    ok = ok && sp + sn < 1.2676506e30f;
    const float rp = rcp(sp), rn = rcp(sn);
#pragma unroll
    for (int i = 0; i < 5; i++) phi[5 * r + i] = pack_bf16(ep[i] * rp, en[i] * rn);
  }
  return ok;
}
__device__ __forceinline__ void feature_map(uint32_t (&phi)[10], const float (&p)[12]) {
  if (!__all_sync(0xffffffffu, feature_rows<false>(phi, p))) feature_rows<true>(phi, p);
}
__device__ __forceinline__ void phi_proj(float (&p0)[12], float (&p1)[12], uint32_t a, uint64_t dw) {
  const uint64_t da = mkdesc(a, 1024, 128, 0), db = mkdesc(a + 2048, 0, 128, 0);
  WG_FENCE();
  wg24_ss_bf16_i(p0, da, dw);
  wg24_ss_bf16(p0, db, dw + 48, 1);
  wg24_ss_bf16_i(p1, da + 384, dw);
  wg24_ss_bf16(p1, db + 384, dw + 48, 1);
  WG_COMMIT();
  WG_WAIT(0);
  pin(p0); pin(p1);
}
__device__ __forceinline__ void stage_o(const float (&o)[12], float s0, float s1, uint32_t a, bool v0, bool v2) {
#pragma unroll
  for (int j = 0; j < 3; j++) {
    const bool v = j == 1 || (j == 0 ? v0 : v2);
    sts32(a + j * 2048, v ? pack_bf16(o[4 * j] * s0, o[4 * j + 1] * s0) : 0u);
    sts32(a + j * 2048 + 128, v ? pack_bf16(o[4 * j + 2] * s1, o[4 * j + 3] * s1) : 0u);
  }
}
__device__ __forceinline__ void flush_o(bool p, uint8_t* dst, uint32_t src, bool odd) {
  bulk_s2g_if(p, dst + (odd ? 2048 : 0), src + (odd ? 2048 : 0), 4096);
  bulk_or_if(p, dst + (odd ? 0 : 4096), src + (odd ? 0 : 4096), 2048);
  BULK_COMMIT();
}

__device__ __forceinline__ void proj20(float (&acc)[20], const __nv_bfloat16* __restrict__ xr, const __nv_bfloat16* __restrict__ wc) {
#pragma unroll
  for (int d = 0; d < 20; d++) acc[d] = 0.f;
#pragma unroll 2
  for (int k = 0; k < 640; k++) {
    const float xv = __bfloat162float(xr[k]);
#pragma unroll
    for (int d = 0; d < 10; d++) {
      const uint32_t u = ldg32(wc + k * 1920 + 2 * d);
      acc[2 * d] = fmaf(xv, __uint_as_float(u << 16), acc[2 * d]);
      acc[2 * d + 1] = fmaf(xv, __uint_as_float(u & 0xffff0000u), acc[2 * d + 1]);
    }
  }
}
__device__ __noinline__ void attn_exact(const __nv_bfloat16* __restrict__ x, const __nv_bfloat16* __restrict__ wqkv, int h, int qt, uint32_t stg) {
  const int tid = threadIdx.x;
  uint32_t* kvs = g_fb + blockIdx.x * (2048 * 20);
  float a[20];
  for (int i = 0; i < 8; i++) {
    const int key = (i >> 1) * 512 + tid, ty = 1 + (i & 1);
    proj20(a, x + key * 640, wqkv + ty * 640 + h * 20);
#pragma unroll
    for (int d = 0; d < 10; d++) kvs[key * 20 + (i & 1) * 10 + d] = pack_bf16(a[2 * d], a[2 * d + 1]);
  }
  const int row = qt * 512 + tid;
  proj20(a, x + row * 640, wqkv + h * 20);
#pragma unroll
  for (int d = 0; d < 20; d++) a[d] = __bfloat162float(__float2bfloat16(a[d]));
  __syncthreads();
  float o[20], m = -INFINITY, l = 0.f;
#pragma unroll
  for (int d = 0; d < 20; d++) o[d] = 0.f;
  for (int key = 0; key < 2048; key++) {
    uint32_t u[20];
#pragma unroll
    for (int d = 0; d < 5; d++) {
      const uint4 t4 = *reinterpret_cast<const uint4*>(kvs + key * 20 + 4 * d);
      u[4 * d] = t4.x; u[4 * d + 1] = t4.y; u[4 * d + 2] = t4.z; u[4 * d + 3] = t4.w;
    }
    float s = 0.f;
#pragma unroll
    for (int d = 0; d < 10; d++) {
      s = fmaf(a[2 * d], __uint_as_float(u[d] << 16), s);
      s = fmaf(a[2 * d + 1], __uint_as_float(u[d] & 0xffff0000u), s);
    }
    s *= 0.22360679774997896f;
    const float mn = fmaxf(m, s), cr = __expf(m - mn), p = __expf(s - mn);
    m = mn;
    l = l * cr + p;
#pragma unroll
    for (int d = 0; d < 10; d++) {
      o[2 * d] = fmaf(p, __uint_as_float(u[10 + d] << 16), o[2 * d] * cr);
      o[2 * d + 1] = fmaf(p, __uint_as_float(u[10 + d] & 0xffff0000u), o[2 * d + 1] * cr);
    }
  }
  const float sc = __ldcg(&g_gate[row]) / l;
#pragma unroll
  for (int d = 0; d < 10; d++) {
    const int col = (h & 1) * 4 + 2 * d;
    sts32(stg + (tid >> 7) * 6144 + (col >> 3) * 2048 + (tid & 127) * 16 + (col & 7) * 2, pack_bf16(o[2 * d] * sc, o[2 * d + 1] * sc));
  }
  PROXY_FENCE();
  __syncthreads();
}

#define COORDS()                                                                                                        \
  int tid, bid;                                                                                                         \
  asm volatile("mov.u32 %0, %%tid.x;" : "=r"(tid));                                                                     \
  asm volatile("mov.u32 %0, %%ctaid.x;" : "=r"(bid));                                                                   \
  const int wg = __shfl_sync(0xffffffffu, tid >> 7, 0);                                                                 \
  const int lane = tid & 31, w = (tid >> 5) & 3, g = lane >> 2, t = lane & 3, wt = tid & 127;                           \
  const int rb1 = bid >> 3, c1 = bid & 7;                                       \
  const int h = bid >> 2, qt = bid & 3, rb = qt * 4 + wg;                    \
  const bool odd = h & 1;                                                                                               \
  const int c0 = (h * 5) >> 1;                                               \
  const int lsrc = (lane & ~3) | (odd ? 0 : 2);                                                                         \
  const bool v0 = !odd || t >= 2, v2 = odd || t < 2;                                                                    \
  const uint32_t ostg = sb + SM_X + wg * 6144, orow = (w * 16 + g) * 16 + t * 4;                                        \
  const uint32_t onepos = (wt >> 6) * 6144 + 3072 + (odd ? 0 : 2048 + 8) + (wt & 63) * 16;                              \
  const int kh = bid & 1, cg = (bid >> 1) & 3, atom3 = (cg >> 1) * 5 + (cg & 1) * 2;                                    \
  auto p3_load_w = [&](bool p, int j) {                                                                                 \
    const uint32_t fb = bar + 8 * (B_P3FULL + (j & 3));                                                                 \
    mbar_expect_if(p, fb, P3_STB);                                                                                      \
    tma3d_if(p, sb + (j & 3) * P3_STB + 16384, &maps.wo[j < 5], (kh * 5 + (j < 5 ? j : j - 5)) * 64, atom3, fb);       \
  };                                                                                                                    \
  auto p3_load_a = [&](bool p, int j) {                                                                                 \
    bulk_g2s_if(p, sb + (j & 3) * P3_STB, g_o + rb1 * ORB + ((j < 5 ? 10 + j : j - 5) + kh * 5) * 16384, 16384,         \
                bar + 8 * (B_P3FULL + (j & 3)));                                                                        \
  };                                                                                                                    \
  (void)g; (void)t; (void)wt; (void)rb1; (void)c1; (void)rb; (void)c0; (void)lsrc; (void)v0; (void)v2; (void)ostg;      \
  (void)orow; (void)onepos; (void)atom3; (void)p3_load_w; (void)p3_load_a

__global__ void __launch_bounds__(512, 1)
gated_mix_kernel(const __grid_constant__ Maps maps, const __nv_bfloat16* __restrict__ x, const __nv_bfloat16* __restrict__ wqkv, const __nv_bfloat16* __restrict__ w_phi,
                 const __nv_bfloat16* __restrict__ gate_w, const void* wqkv_b, const void* wo_a, const void* wo_b, uint4* __restrict__ out) {
  extern __shared__ __align__(1024) uint8_t smem_raw[];
  const uint32_t sb = (uint32_t)__cvta_generic_to_shared(smem_raw);
  const uint32_t bar = sb + SM_BAR;
  uint32_t q[2][6], qc[4], epoch, events;
  int bad;
  {
  COORDS();
  TS_INIT();

  auto p1_load = [&](bool p, int it) {
    const int st = it & 3, br = it >= 10, ks = it - br * 10;
    const uint32_t dst = sb + st * P1_STB, fb = bar + 8 * (B_FULL + st);
    mbar_expect_if(p, fb, P1_STB);
    tma2d_if(p, dst, &maps.x, ks * 64, rb1 * 128, fb);
    tma3d_if(p, dst + 16384, &maps.w[br], ks * 64, tile_atom(c1 ^ br), fb);
  };
  if (wt == 0) {
    mbar_init(bar + 8 * (B_FULL + wg), 1);
    asm volatile("fence.mbarrier_init.release.cluster;" ::: "memory");
    if (wg == 0) p1_load(true, 0);
  }
  TS_REG(tsa_);
  if (wt == 32) {
#pragma unroll
    for (int u = 0; u < 4; u++)
      if (wg == u) {
#pragma unroll
        for (int i = B_AUX + u * 8; i < B_AUX + u * 8 + 8; i++)
          mbar_init(bar + 8 * i, i == B_AUX ? 3 : i < B_P3EMPTY ? 1 : i < B_EMPTY ? 2 : i < B_ZERO ? 4 : i == B_ZERO ? 16 : i < B_READY + 2 ? 512 : 128);
      }
    asm volatile("fence.mbarrier_init.release.cluster;" ::: "memory");
  }
  TS_REG(tsb_);
  TS_REG(tsc_);
  asm volatile("st.shared.v4.b32 [%0], {%1, %1, %1, %1};" ::"r"(sb + SM_X + tid * 16), "r"(0) : "memory");
  if (tid < 256) sts32(sb + SM_CONST + tid * 4, (tid & 3) ? 0u : ((tid >> 5) < NMB ? 0xdd02e192u : 0x00001ef0u));
  PROXY_FENCE();
  TS_REG(tsd_);
  __syncthreads();
  TS_PUT(16, tsa_, 0); TS_PUT(17, tsb_, 32); TS_PUT(18, tsc_, 32); TS_PUT(19, tsd_, 32);
  if (wg > 0) p1_load(wt == 0, wg);
  if (wt == 64) {
    if (wg == 1) { mbar_expect_if(true, bar + 8 * B_AUX, 1280); bulk_g2s_if(true, sb + SM_GW, gate_w, 1280, bar + 8 * B_AUX); }
    if (wg == 2) { mbar_expect_if(true, bar + 8 * B_AUX, 800); bulk_g2s_if(true, sb + SM_WRAW, w_phi + h * 400, 800, bar + 8 * B_AUX); }
    if (wg == 3) { mbar_expect_if(true, bar + 8 * B_AUX, 16); bulk_g2s_if(true, sb + SM_EP, &g_cnt[C_EPOCH], 16, bar + 8 * B_AUX); }
  }
  TS_FIRST();
  TS_MARK(1);

  {
    float acc[64];
    const int r = wg & 1, ch = wg >> 1;
    const bool mufu0 = 2 * w < NMB, mufu1 = 2 * w + 1 < NMB;
    uint32_t pk[32];
    float gs = 0.f;
    const int grow = c1 * 16 + (tid >> 5);
    auto stage = [&](uint32_t stg, int e0) {
#pragma unroll
      for (int e = 0; e < 16; e += 4) stsm4(stg + (w * 16 + (lane & 15)) * 16 + (lane >> 4) * 1024 + e * 512, pk[e0 + e], pk[e0 + e + 1], pk[e0 + e + 2], pk[e0 + e + 3]);
    };
    auto duties = [&](auto BR, int it, int ga0, bool narrow_a) {
      constexpr int br = decltype(BR)::value;
      if (wg == (it & 3) && it >= 1 && it <= 16) {
        mbar_wait(bar + 8 * (B_EMPTY + ((it - 1) & 3)), ((it - 1) >> 2) & 1);
        p1_load(wt == 0, it + 3);
      }
      if (br == 0 && wg == 0 && it >= 1 && it <= 4) {
        const bool p = wt == 0;
        if (it < 4) bulk_s2g_if(p, reinterpret_cast<uint8_t*>(out) + bid * 20480 + (it - 1) * 8192, sb + SM_X, it == 3 ? 4096 : 8192);
        else bulk_s2g_if(p, g_kv + bid * 240, sb + SM_X, 960);
        bulk_s2g_if(p, g_o + rb1 * ORB + ((c1 * 4 + it - 1) * 5 + 2) * 2048, sb + SM_X, 2048);
        BULK_COMMIT();
      }
      if (br == 0 && it == 2 && wg == 1 && wt < 3) {
        const int bytes = wt == 0 ? 19200 : 6400;
        const uint8_t* p = reinterpret_cast<const uint8_t*>(wt == 0 ? wqkv_b : wt == 1 ? wo_a : wo_b) + bid * bytes;
        asm volatile("cp.async.bulk.prefetch.L2.global [%0], %1;" ::"l"(p), "r"(bytes) : "memory");
      }
      if (br == 0 && it == 3) {
        epoch = (lds32(sb + SM_EP) >> 7) + 1;
#pragma unroll
        for (int u = 0; u < 2; u++) {
          const int i = tid + u * 512, k = i / 24, n = i % 24, ii = 2 * (n >> 3) + (n & 1), f = 4 * ii + ((n & 7) >> 1), d = k - (odd ? 4 : 0);
          uint16_t v = 0;
          if (d >= 0 && d < 20 && ii < 5) asm volatile("ld.shared.u16 %0, [%1];" : "=h"(v) : "r"(sb + SM_WRAW + (d * 20 + f) * 2) : "memory");
          if (i < 768) sts16(sb + SM_WPHI + (k >> 3) * 384 + n * 16 + (k & 7) * 2, v);
        }
      }
      if (br == 0 && it == 6 && wg == 0) BULK_WAIT_READ();
      if (br == 1 && (it == 10 || it == 12)) {
        const int u = it == 12;
        if (!u) {
#pragma unroll
          for (int o = 16; o; o >>= 1) gs += __shfl_xor_sync(0xffffffffu, gs, o);
          if (lane == 0) sts32(sb + SM_BAR + 448 + (tid >> 5) * 4, __float_as_uint(1.f / (1.f + __expf(-gs))));
          mbar_wait(bar + 8 * B_ZERO, 0);
          stage(sb + SM_X + wg * 8192, 0);
        } else {
          BULK_WAIT_READ();
          bar_sync(1 + wg, 128);
          stage(sb + SM_X + wg * 8192, 16);
        }
        PROXY_FENCE();
        bar_sync(1 + wg, 128);
        tma5d_store_if(wt == 0 && !(u && narrow_a), &maps.qst, sb + SM_X + wg * 8192, ((ga0 + u) % 10) * 8, (ga0 + u) / 10, wg & 1, rb1);
        bulk_s2g_if(wt == 0 && !u, g_gate + rb1 * 128 + c1 * 16 + wg * 4, sb + SM_BAR + 448 + wg * 16, 16);
        BULK_COMMIT();
      }
      if (br == 1 && it == 15) signal_bulk_if(wt == 0, &g_cnt[C_TA]);
      if (br == 1 && it >= 17 && it <= 18 && wg == (it & 3)) {
        wait_count(&g_cnt[C_TA], epoch * 512);
        mbar_wait(bar + 8 * (B_EMPTY + (it - 17)), 0);
        mbar_expect_if(wt == 0, bar + 8 * (B_KVFULL + it - 17), P1_STB);
        tma5d_if(wt == 0, sb + (it - 17) * P1_STB, &maps.qld, c0, 1, (it - 17) * 4, bar + 8 * (B_KVFULL + it - 17));
      }
      if (br == 1 && it == 19) {
        mbar_wait(bar + 8 * (B_KVFULL + 0), 0);
        const uint8_t* qp = g_qkv + rb * QRB + c0 * 2048 + orow;
        load_frag(q[0], qp);
        load_frag(q[1], qp + 1024);
        bad = ldcg32(&g_kbad);
        sts16(sb + wg * 12288 + onepos, 0x3c00);
        PROXY_FENCE();
        mbar_arrive(bar + 8 * (B_READY + 0));
      }
    };
    const int ga_a = tile_atom(c1) + 2 * ch + (((c1 & 3) == 2 && wg == 0) ? 1 : 0);
    const bool narrow_a = ((c1 & 3) == 1 && wg == 3) || ((c1 & 3) == 2 && wg == 0);
    auto gate_step = [&](uint32_t dst, int ks) {
      if (ks == 0) mbar_wait(bar + 8 * B_AUX, 0);
      const uint32_t a = lds32(dst + grow * 128 + (((lane >> 2) ^ (grow & 7)) << 4) + t * 4), b = lds32(sb + SM_GW + ks * 128 + lane * 4);
      gs = fmaf(__uint_as_float(a << 16), __uint_as_float(b << 16), gs);
      gs = fmaf(__uint_as_float(a & 0xffff0000u), __uint_as_float(b & 0xffff0000u), gs);
      __syncwarp();
      mbar_arrive_if(ks == 9 && lane == 0, bar + 8 * B_ZERO);
    };
    auto tile = [&](auto BR) {
      constexpr int br = decltype(BR)::value;
      const int tl = c1 ^ br, k4 = tl & 3;
      const bool narrow = (k4 == 1 && wg == 3) || (k4 == 2 && wg == 0);
      const int a0 = 2 * ch + ((k4 == 2 && wg == 0) ? 1 : 0);
      if (!narrow) {
#pragma unroll 1
        for (int ks = 0; ks < 10; ks++) {
          const int it = br * 10 + ks, st = it & 3;
          mbar_wait(bar + 8 * (B_FULL + st), (it >> 2) & 1);
          TS_MARK(20 + it);
          const uint32_t dst = sb + st * P1_STB;
          const uint64_t da = mkdesc(dst + r * 8192, 16, 1024, 1), db = mkdesc(dst + 16384 + a0 * 8192, 8192, 1024, 1);
          WG_FENCE();
#pragma unroll
          for (int k = 0; k < 4; k++) wg128_ss(acc, da + k * 2, db + k * 128, (ks | k) != 0);
          WG_COMMIT();
          if (br == 0) gate_step(dst, ks);
          WG_WAIT(1);
          mbar_arrive_if(ks > 0 && wt == 0, bar + 8 * (B_EMPTY + ((it - 1) & 3)));
          duties(BR, it, ga_a, narrow_a);
        }
        WG_WAIT(0);
      } else {
#pragma unroll 1
        for (int ks = 0; ks < 10; ks++) {
          const int it = br * 10 + ks, st = it & 3;
          mbar_wait(bar + 8 * (B_FULL + st), (it >> 2) & 1);
          TS_MARK(20 + it);
          const uint32_t dst = sb + st * P1_STB;
          const uint64_t da = mkdesc(dst + r * 8192, 16, 1024, 1), db = mkdesc(dst + 16384 + a0 * 8192, 8192, 1024, 1);
          WG_FENCE();
#pragma unroll
          for (int k = 0; k < 4; k++) wg64_ss_of64(acc, da + k * 2, db + k * 128, (ks | k) != 0);
          WG_COMMIT();
          if (br == 0) gate_step(dst, ks);
          WG_WAIT(1);
          mbar_arrive_if(ks > 0 && wt == 0, bar + 8 * (B_EMPTY + ((it - 1) & 3)));
          duties(BR, it, ga_a, narrow_a);
        }
        WG_WAIT(0);
      }
      pin(acc);
      TS_MARK(2 + 2 * br);
      mbar_arrive_if(wt == 0, bar + 8 * (B_EMPTY + ((br * 10 + 9) & 3)));
      const int ga0 = tile_atom(tl) + a0;
      uint32_t m0 = 0, m1 = 0;
      if (br == 0) {
        const float sk0 = __uint_as_float(mufu0 ? (127u + 70u) << 23 : (127u - 69u) << 23);
        const float sk1 = __uint_as_float(mufu1 ? (127u + 70u) << 23 : (127u - 69u) << 23);
        pack_atom_a<0>(acc, pk, ga0, sk0, sk1, m0, m1);
        if (!narrow) pack_atom_a<1>(acc, pk, ga0 + 1, sk0, sk1, m0, m1);
        const uint32_t lim0 = (mufu0 ? 127u + 110u : 127u - 29u) << 7, lim1 = (mufu1 ? 127u + 110u : 127u - 29u) << 7;
        if ((m0 & 0x7fffu) >= lim0 || ((m0 >> 16) & 0x7fffu) >= lim0 || (m1 & 0x7fffu) >= lim1 || ((m1 >> 16) & 0x7fffu) >= lim1) { g_kbad = epoch; __threadfence(); }
      } else {
        pack_atom<0, 0>(acc, pk, 0.f, 0.f, m0, m1);
        pack_atom<0, 1>(acc, pk, 0.f, 0.f, m0, m1);
        if (ch) mbar_wait(bar + 8 * (B_EMPTY + 2), 0);
        const uint32_t stg = sb + (ch ? 2 * P1_STB : SM_X) + r * 16384;
        stage(stg, 0);
        stage(stg + 8192, 16);
        mbar_wait(bar + 8 * (B_KVFULL + 1), 0);
        sts16(sb + P1_STB + wg * 12288 + onepos, 0x3c00);
        PROXY_FENCE();
        mbar_arrive(bar + 8 * (B_READY + 1));
        bar_sync(1 + wg, 128);
        tma5d_store_if(wt == 0, &maps.qst, stg, (ga0 % 10) * 8, ga0 / 10, r, 16 + rb1);
        tma5d_store_if(wt == 32 * 0 && !narrow, &maps.qst, stg + 8192, ((ga0 + 1) % 10) * 8, (ga0 + 1) / 10, r, 16 + rb1);
        BULK_COMMIT();
      }
      TS_MARK(3 + 2 * br);
    };
    tile(Int<0>{});
    tile(Int<1>{});
  }

  if (odd ? t < 2 : t >= 2) {
    if (odd) { q[0][0] = 0; q[0][1] = 0; q[1][0] = 0; q[1][1] = 0; }
    else { q[0][4] = 0; q[0][5] = 0; q[1][4] = 0; q[1][5] = 0; }
  }
  {
    uint32_t m = 0;
#pragma unroll
    for (int i = 0; i < 6; i++) m = maxabs_bf16x2(m, maxabs_bf16x2(q[0][i], q[1][i]));
    bad = bad == (int)epoch || (m & 0x7fffu) >= ((127u - 50u) << 7) || ((m >> 16) & 0x7fffu) >= ((127u - 50u) << 7);
  }
#pragma unroll
  for (int i = 0; i < 4; i++) { qc[i] = t == 0 ? 0x1c801c80u : 0u; asm volatile("" : "+r"(qc[i])); }
  events = 0x01010110u | (0x2008000u >> (2 * wg)) | (wg == 0 ? 0x8000440u : wg == 1 ? 0x40000u : wg == 2 ? 0x20000000u : 0x420000u);
  mbar_wait(bar + 8 * (B_READY + 0), 0);
  }
  float o[2][12];
#pragma unroll
  for (int i = 0; i < 12; i++) { o[0][i] = 0.f; o[1][i] = 0.f; }
  {
    uint32_t dk0 = (uint32_t)mkdesc(sb, 1024, 0, 0), dk1 = (uint32_t)mkdesc(sb + 2048, SM_CONST - 2048, 0, 0), dv = (uint32_t)mkdesc(sb + 3072, 128, 0, 0);
    TS_MARK(6);
#pragma unroll 1
    for (int i = 0; i < 32; i++) {
      if ((events >> i) & 1) {
        if ((i & 3) == 0 || i == 27) {
          COORDS();
          const bool p = wt == 0;
          signal_bulk_if(p && i != 8 && (i != 24 || wg != 0), &g_cnt[i == 4 ? C_TB : i == 16 ? C_KV + h : C_OB + rb * 2 + (h >> 4)]);
          if (i == 4) mbar_arrive_if(p, bar + 8 * B_STG);
          if ((i & 7) == 0) {
            WG_WAIT(0);
            mbar_arrive_if(p, bar + 8 * (B_FREE - 1) + i);
            mbar_wait(bar + 8 * B_READY + i, 0);
          }
        } else if (i == 6 || i == 10 || i == 17 || i == 22 || i == 29) {
          COORDS();
          const bool p = lane == 0;
          if (i == 6) {
            mbar_wait(bar + 8 * B_STG, 0);
            if (w == 1) wait_count(&g_cnt[C_TB], epoch * 512);
            const uint32_t fb = bar + 8 * (w ? B_KB : B_KVFULL + 2);
            mbar_expect_if(p && w < 2, fb, P1_STB);
            tma5d_if(p && w < 2, sb + (2 + w) * P1_STB, &maps.qld, c0, 1, w ? 16 + qt * 4 : 8, fb);
          } else if (i == 29) {
            mbar_wait(bar + 8 * (B_FREE + 2), 0);
            mbar_wait(bar + 8 * B_B2, 0);
            p3_load_w(p && w < 3, w);
            wait_count(&g_cnt[C_OB + rb1 * 2 + kh], epoch * 16);
            p3_load_a(p && w < 3, w);
          } else {
            if (i != 22) {
              const int u = i == 17;
              const uint32_t fb = bar + 8 * (u ? B_KVFULL + 3 : B_QB);
              mbar_wait(bar + 8 * (B_FREE + u), 0);
              mbar_expect_if(wt == 0, fb, P1_STB);
              tma5d_if(wt == 0, sb + u * 3 * P1_STB, &maps.qld, c0, u, u ? 12 : 16 + qt * 4, fb);
            }
            if (i != 17) {
              const int u = i == 10 ? 2 : 3;
              mbar_wait(bar + 8 * (B_KVFULL + u), 0);
#pragma unroll
              for (int e = 0; e < 4; e++) sts16(sb + u * P1_STB + e * 12288 + onepos, 0x3c00);
              PROXY_FENCE();
              mbar_arrive(bar + 8 * (B_READY + u));
            }
          }
        } else if (i < 16) {
          WG_WAIT(0);
          COORDS();
          const uint64_t dw = mkdesc(sb + SM_WPHI, 384, 128, 0);
          TS_MARK(7);
          const uint32_t kb = sb + 3 * P1_STB + wg * 12288, ph = sb + SM_X + (wg & 1) * 10240;
          mbar_wait(bar + 8 * B_KB, 0);
          sts16(kb + onepos, 0x3f80);
          float p0[12], p1[12];
          phi_proj(p0, p1, kb, dw);
          if (wg < 2) mbar_wait(bar + 8 * (B_LINK + wg), 0);
          uint32_t phi[10];
          feature_map(phi, p0);
#pragma unroll
          for (int u = 0; u < 10; u++) sts32(ph + (u % 5) * 2048 + orow + (u / 5) * 128, phi[u]);
          feature_map(phi, p1);
#pragma unroll
          for (int u = 0; u < 10; u++) sts32(ph + (u % 5) * 2048 + orow + (u / 5) * 128 + 1024, phi[u]);
          PROXY_FENCE();
          bar_sync(1 + wg, 128);
          const uint64_t da = mkdesc(ph, 128, 2048, 0), db = mkdesc(kb + 3072, 128, 1024, 0);
          WG_FENCE();
#pragma unroll
          for (int kk = 0; kk < 8; kk++) {
            if (kk == 0) wg24_ss_bf16_tt_i(p0, da, db);
            else wg24_ss_bf16_tt(p0, da + kk * 16, db + (kk & 3) * 16 + (kk >> 2) * 384, 1);
          }
          WG_COMMIT();
          WG_WAIT(0);
          pin(p0);
          mbar_arrive_if(lane == 0 && wg >= 2, bar + 8 * (B_LINK + (wg & 1)));
          bar_sync(1 + wg, 128);
          const uint32_t ks = kb + ((w * 16 + g) * 24 + 2 * t) * 4;
#pragma unroll
          for (int j = 0; j < 3; j++) {
            if (w < 3) asm volatile("st.shared.v2.f32 [%0], {%1, %2};" ::"r"(ks + 32 * j), "f"(p0[4 * j]), "f"(p0[4 * j + 1]) : "memory");
            if (w < 2) asm volatile("st.shared.v2.f32 [%0], {%1, %2};" ::"r"(ks + 768 + 32 * j), "f"(p0[4 * j + 2]), "f"(p0[4 * j + 3]) : "memory");
          }
          PROXY_FENCE();
          bar_sync(1 + wg, 128);
          bulk_addf_if(wt == 0, g_kv + h * 960, kb, 3840);
          BULK_COMMIT();
          TS_MARK(8);
        } else if (i == 18) {
          COORDS();
          wait_count(&g_cnt[C_KV + h], epoch * 16);
          float v[8];
#pragma unroll
          for (int u = 0; u < 8; u++) v[u] = (u < 7 || wt < 64) ? __ldcg(&g_kv[h * 960 + u * 128 + wt]) : 0.f;
#pragma unroll
          for (int u = 0; u < 9; u++) {
            const int e = u * 128 + wt, f = e / 24, d = e % 24;
            sts16(sb + SM_KVB + (f >> 3) * 384 + d * 16 + (f & 7) * 2, u < 8 ? __bfloat16_as_ushort(__float2bfloat16(v[u < 8 ? u : 0])) : (uint16_t)0);
          }
          PROXY_FENCE();
          mbar_arrive(bar + 8 * B_KVB);
        } else {
          WG_WAIT(0);
          COORDS();
          const uint64_t dw = mkdesc(sb + SM_WPHI, 384, 128, 0);
          TS_MARK(9);
          float gt[4];
#pragma unroll
          for (int u = 0; u < 4; u++) gt[u] = 1.f - __ldcg(&g_gate[rb * 128 + (u >> 1) * 64 + w * 16 + g + (u & 1) * 8]);
          mbar_wait(bar + 8 * B_QB, 0);
          float p0[12], p1[12];
          phi_proj(p0, p1, sb + wg * 12288, dw);
          const uint64_t dkv = mkdesc(sb + SM_KVB, 384, 128, 0);
          auto readout = [&](float (&p)[12], float g0, float g1, uint32_t a) {
            uint32_t phi[10];
            feature_map(phi, p);
            WG_FENCE();
            wg24_rs_bf16_i(p, phi[0], phi[5], phi[1], phi[6], dkv);
            wg24_rs_bf16(p, phi[2], phi[7], phi[3], phi[8], dkv + 48, 1);
            wg24_rs_bf16(p, phi[4], phi[9], 0u, 0u, dkv + 96, 1);
            WG_COMMIT();
            WG_WAIT(0);
            pin(p);
            const float l0 = __shfl_sync(0xffffffffu, odd ? p[0] : p[8], lsrc), l1 = __shfl_sync(0xffffffffu, odd ? p[2] : p[10], lsrc);
            stage_o(p, __fdividef(g0, l0 + 1e-6f), __fdividef(g1, l1 + 1e-6f), a, v0, v2);
          };
          mbar_wait(bar + 8 * B_KVB, 0);
          readout(p0, gt[0], gt[1], ostg + orow);
          readout(p1, gt[2], gt[3], ostg + orow + 1024);
          PROXY_FENCE();
          bar_sync(1 + wg, 128);
          mbar_arrive_if(wt == 0, bar + 8 * B_B2);
          flush_o(wt == 0, g_o + rb * ORB + (80 + c0) * 2048, ostg, odd);
          TS_MARK(10);
        }
      }
      if (!(i & 3)) TS_MARK(40 + (i >> 2));
#pragma unroll
      for (int m = 0; m < 2; m++) {
        float s[32];
        uint32_t p[16];
        WG_FENCE();
        wg64_rs_bf16_i(s, q[m][0], q[m][1], q[m][2], q[m][3], desc_lohi(dk0, 8));
        wg64_rs_bf16(s, q[m][4], q[m][5], qc[2 * m], qc[2 * m + 1], desc_lohi(dk1, 8), 1);
        WG_COMMIT();
        WG_WAIT(0);
        constexpr int A = 2 * NMB, B = 16 - A;
#pragma unroll
        for (int j = 0; j < B; j++) {
          if ((j * A) % B < A) { const int a = j * A / B; p[a] = exp2_pair_mufu(s[2 * a], s[2 * a + 1]); }
          p[A + j] = exp2_pair(s[2 * (A + j)], s[2 * (A + j) + 1]);
        }
        WG_FENCE();
#pragma unroll
        for (int kk = 0; kk < 4; kk++) wg24_rs_f16_t(o[m], p[4 * kk], p[4 * kk + 1], p[4 * kk + 2], p[4 * kk + 3], desc_lohi(dv + kk * 16, 64), 1);
        WG_COMMIT();
      }
      dk0 += 384; dk1 += 384u - (384u << 16); dv += 384;
    }
  }
  {
    COORDS();
    float gt[4];
#pragma unroll
    for (int u = 0; u < 4; u++) gt[u] = __ldcg(&g_gate[rb * 128 + (u >> 1) * 64 + w * 16 + g + (u & 1) * 8]);
    WG_WAIT(0);
    pin(o[0]); pin(o[1]);
    TS_MARK(11);
    int big = 0;
#pragma unroll
    for (int m = 0; m < 2; m++) {
      const float l0 = __shfl_sync(0xffffffffu, odd ? o[m][0] : o[m][8], lsrc), l1 = __shfl_sync(0xffffffffu, odd ? o[m][2] : o[m][10], lsrc);
      const float r0 = rcp(l0), r1 = rcp(l1);
      float chk = 0.f, mx0 = 0.f, mx1 = 0.f;
#pragma unroll
      for (int i = 0; i < 12; i++) chk = fmaf(o[m][i], 0.f, chk);
#pragma unroll
      for (int i = 4; i < 6; i++) { mx0 = fmaxf(mx0, fabsf(o[m][i])); mx1 = fmaxf(mx1, fabsf(o[m][i + 2])); }
      bad |= !(chk == 0.f) || !(l0 >= 32.f) || !(l1 >= 32.f);
      big |= fmaxf(mx0 * r0, mx1 * r1) >= 1.220703125e-4f;
      stage_o(o[m], r0 * gt[2 * m], r1 * gt[2 * m + 1], ostg + orow + m * 1024, v0, v2);
    }
    PROXY_FENCE();
    const int anybad = __syncthreads_or(bad), anybig = __syncthreads_or(big);
    if (anybad || !anybig) attn_exact(x, wqkv, h, qt, sb + SM_X);
  }
  TS_MARK(12);

  COORDS();
  if (wg == 3) {
    flush_o(lane == 0, g_o + (qt * 4 + w) * ORB + c0 * 2048, sb + SM_X + w * 6144, odd);
    signal_bulk_if(lane == 0, &g_cnt[C_OA + (qt * 4 + w) * 2 + (h >> 4)]);
    if (wt == 0) atomicAdd(&g_cnt[C_EPOCH], 1);
  } else if (wg == 2) {
    const bool p = lane == 0;
    if (w == 3) { p3_load_w(p, 3); p3_load_a(p, 3); }
    mbar_wait(bar + 8 * (B_P3EMPTY + w), 0);
    p3_load_w(p, 4 + w);
    if (w > 0) wait_count(&g_cnt[C_OA + rb1 * 2 + kh], epoch * 16);
    p3_load_a(p, 4 + w);
    if (w < 2) {
      mbar_wait(bar + 8 * (B_P3EMPTY + w), 1);
      p3_load_w(p, 8 + w);
      if (w == 0) wait_count(&g_cnt[C_OA + rb1 * 2 + kh], epoch * 16);
      p3_load_a(p, 8 + w);
    }
  } else {
    float acc[96];
    const bool wide = (cg & 1) == wg;
    const int skip = (!wide && (cg & 1)) ? 1 : 0;
    if (wide) {
#pragma unroll 1
      for (int j = 0; j < 10; j++) {
        mbar_wait(bar + 8 * (B_P3FULL + (j & 3)), (j >> 2) & 1);
        if (j == 5) TS_MARK(13);
        const uint32_t dst = sb + (j & 3) * P3_STB;
        const uint64_t da = mkdesc(dst + wg * 1024, 2048, 128, 0), db = mkdesc(dst + 16384, 8192, 1024, 1);
        WG_FENCE();
#pragma unroll
        for (int k = 0; k < 4; k++) wg192_ss(acc, da + k * 256, db + k * 128, (j | k) != 0);
        WG_COMMIT();
        WG_WAIT(1);
        mbar_arrive_if(j > 0 && wt == 0, bar + 8 * (B_P3EMPTY + ((j - 1) & 3)));
      }
      WG_WAIT(0);
    } else {
#pragma unroll 1
      for (int j = 0; j < 10; j++) {
        mbar_wait(bar + 8 * (B_P3FULL + (j & 3)), (j >> 2) & 1);
        if (j == 5) TS_MARK(13);
        const uint32_t dst = sb + (j & 3) * P3_STB;
        const uint64_t da = mkdesc(dst + wg * 1024, 2048, 128, 0), db = mkdesc(dst + 16384 + skip * 8192, 8192, 1024, 1);
        WG_FENCE();
#pragma unroll
        for (int k = 0; k < 4; k++) wg128_ss_of96(acc, da + k * 256, db + k * 128, (j | k) != 0);
        WG_COMMIT();
        WG_WAIT(1);
        mbar_arrive_if(j > 0 && wt == 0, bar + 8 * (B_P3EMPTY + ((j - 1) & 3)));
      }
      WG_WAIT(0);
    }
    pin(acc);
    TS_MARK(14);
    if (!wide) mbar_wait(bar + 8 * (B_P3EMPTY + 2), 1);
    const uint32_t stg = sb + (wide ? 4 : 2) * P3_STB;
    const int r = w * 16 + (lane & 15);
#pragma unroll
    for (int i = 0; i < 24; i += 2)
      if (i < 16 || wide) {
        const int ch = (i & 7) + (lane >> 4);
        stsm4(stg + (i >> 3) * 8192 + r * 128 + ((ch ^ (r & 7)) << 4), pack_bf16(acc[4 * i], acc[4 * i + 1]), pack_bf16(acc[4 * i + 2], acc[4 * i + 3]),
              pack_bf16(acc[4 * i + 4], acc[4 * i + 5]), pack_bf16(acc[4 * i + 6], acc[4 * i + 7]));
      }
    PROXY_FENCE();
    bar_sync(1 + wg, 128);
    if (wt < (wide ? 3 : 2)) {
      PROXY_FENCE_G();
      asm volatile("cp.reduce.async.bulk.tensor.2d.global.shared::cta.add.bulk_group [%0, {%2, %3}], [%1];" ::"l"(&maps.out), "r"(stg + wt * 8192),
                   "r"((atom3 + skip + wt) * 64), "r"(rb1 * 128 + wg * 64) : "memory");
      asm volatile("cp.async.bulk.commit_group;" ::: "memory");
      asm volatile("cp.async.bulk.wait_group 0;" ::: "memory");
    }
    TS_MARK(15);
  }
  TS_DUMP();
}

typedef CUresult (*EncodeFn)(CUtensorMap*, CUtensorMapDataType, cuuint32_t, void*, const cuuint64_t*, const cuuint64_t*, const cuuint32_t*, const cuuint32_t*,
                             CUtensorMapInterleave, CUtensorMapSwizzle, CUtensorMapL2promotion, CUtensorMapFloatOOBfill);
void encode(EncodeFn enc, CUtensorMap* m, void* p, int rank, const cuuint64_t* gd, const cuuint64_t* gs, const cuuint32_t* bd) {
  const cuuint32_t es[3] = {1, 1, 1};
  enc(m, CU_TENSOR_MAP_DATA_TYPE_BFLOAT16, rank, p, gd, gs, bd, es, CU_TENSOR_MAP_INTERLEAVE_NONE, CU_TENSOR_MAP_SWIZZLE_128B,
      CU_TENSOR_MAP_L2_PROMOTION_L2_128B, CU_TENSOR_MAP_FLOAT_OOB_FILL_NONE);
}

}

extern "C" void kernel_launch(void* const* d_in, const int* in_sizes, int n_in, void* d_out, int out_size) {
  static EncodeFn enc = nullptr;
  if (!enc) {
    cudaDriverEntryPointQueryResult qr;
    cudaGetDriverEntryPoint("cuTensorMapEncodeTiled", (void**)&enc, cudaEnableDefault, &qr);
    cudaFuncSetAttribute(gated_mix_kernel, cudaFuncAttributeMaxDynamicSharedMemorySize, SMEM_BYTES);
  }
  Maps m;
  {
    const cuuint64_t gd[2] = {640, 2048}, gs[1] = {1280};
    const cuuint32_t bx[2] = {64, 128}, bo[2] = {64, 64};
    encode(enc, &m.x, d_in[0], 2, gd, gs, bx);
    encode(enc, &m.out, d_out, 2, gd, gs, bo);
  }
  for (int b = 0; b < 2; b++) {
    const cuuint64_t gd[3] = {64, 640, 30}, gs[2] = {3840, 128}, gd3[3] = {64, 640, 10}, gs3[2] = {1280, 128};
    const cuuint32_t bd[3] = {64, 64, 4}, bd3[3] = {64, 64, 3};
    encode(enc, &m.w[b], d_in[b ? 4 : 1], 3, gd, gs, bd);
    encode(enc, &m.wo[b], d_in[b ? 6 : 2], 3, gd3, gs3, bd3);
  }
  {
    void* qp = nullptr;
    cudaGetSymbolAddress(&qp, g_qkv);
    const cuuint64_t gd[5] = {128, 80, 3, 2, 32}, gs[4] = {2048, QTY, 1024, QRB};
    const cuuint32_t bl[5] = {128, 3, 2, 2, 4}, bs[5] = {128, 8, 1, 1, 1}, es[5] = {1, 1, 1, 1, 1};
    enc(&m.qld, CU_TENSOR_MAP_DATA_TYPE_UINT64, 5, qp, gd, gs, bl, es, CU_TENSOR_MAP_INTERLEAVE_NONE, CU_TENSOR_MAP_SWIZZLE_NONE, CU_TENSOR_MAP_L2_PROMOTION_L2_128B, CU_TENSOR_MAP_FLOAT_OOB_FILL_NONE);
    enc(&m.qst, CU_TENSOR_MAP_DATA_TYPE_UINT64, 5, qp, gd, gs, bs, es, CU_TENSOR_MAP_INTERLEAVE_NONE, CU_TENSOR_MAP_SWIZZLE_NONE, CU_TENSOR_MAP_L2_PROMOTION_NONE, CU_TENSOR_MAP_FLOAT_OOB_FILL_NONE);
  }
  gated_mix_kernel<<<128, 512, SMEM_BYTES, cudaStreamPerThread>>>(m, (const __nv_bfloat16*)d_in[0], (const __nv_bfloat16*)d_in[1], (const __nv_bfloat16*)d_in[5],
                                                                 (const __nv_bfloat16*)d_in[7], d_in[4], d_in[2], d_in[6], (uint4*)d_out);
}
```

```cpp
#include <cuda_runtime.h>
#include <cuda.h>
#include <cuda_bf16.h>
#include <cuda_fp16.h>
#include <stdint.h>
#pragma nv_diag_suppress 550

namespace {

constexpr int QRB = 240 * 2048;
constexpr int QBR = 16 * QRB;
constexpr int QTY = 80 * 2048;
constexpr int ORB = 160 * 2048;
constexpr int NMB = 3;

__device__ __align__(1024) uint8_t g_qkv[2 * QBR];
__device__ __align__(1024) uint8_t g_o[16 * ORB];
__device__ float g_gate[2048];
__device__ __align__(16) float g_kv[32 * 960];
__device__ uint32_t g_kbad;
__device__ uint32_t g_fb[128 * 2048 * 20];
__device__ uint32_t g_cnt[192];
constexpr int C_EPOCH = 0, C_TA = 32, C_TB = 64, C_KV = 96, C_OB = 128, C_OA = 160;

#define TS_MARK(i)
#define TS_INIT()
#define TS_REG(x)
#define TS_PUT(i, x, th)
#define TS_FIRST()
#define TS_DUMP()

__device__ __forceinline__ uint64_t mkdesc(uint32_t addr, uint32_t lbo, uint32_t sbo, int mode) {
  return (uint64_t)((addr & 0x3FFFF) >> 4) | ((uint64_t)(lbo >> 4) << 16) | ((uint64_t)(sbo >> 4) << 32) | ((uint64_t)mode << 62);
}
__device__ __forceinline__ uint64_t desc_lohi(uint32_t lo, uint32_t hi) { return ((uint64_t)hi << 32) | lo; }
#define WG_FENCE() asm volatile("wgmma.fence.sync.aligned;" ::: "memory")
#define WG_COMMIT() asm volatile("wgmma.commit_group.sync.aligned;" ::: "memory")
#define WG_WAIT(n) asm volatile("wgmma.wait_group.sync.aligned %0;" ::"n"(n) : "memory")
#define PROXY_FENCE() asm volatile("fence.proxy.async.shared::cta;" ::: "memory")
#define PROXY_FENCE_G() asm volatile("fence.proxy.async.global;" ::: "memory")
__device__ __forceinline__ void bar_sync(int id, int n) { asm volatile("bar.sync %0, %1;" ::"r"(id), "r"(n) : "memory"); }
__device__ __forceinline__ void mbar_init(uint32_t a, int c) { asm volatile("mbarrier.init.shared::cta.b64 [%0], %1;" ::"r"(a), "r"(c)); }
__device__ __forceinline__ uint32_t mbar_try(uint32_t a, int par) {
  uint32_t ok;
  asm volatile("{.reg .pred p; mbarrier.try_wait.parity.shared::cta.b64 p, [%1], %2; selp.b32 %0, 1, 0, p;}" : "=r"(ok) : "r"(a), "r"(par) : "memory");
  return ok;
}
__device__ __forceinline__ void mbar_wait(uint32_t a, int par) {
  for (int i = 0; !mbar_try(a, par); i++)
    if (i > (1 << 22)) break;
}
__device__ __forceinline__ void mbar_arrive(uint32_t a) { asm volatile("mbarrier.arrive.shared::cta.b64 _, [%0];" ::"r"(a) : "memory"); }
__device__ __forceinline__ void mbar_arrive_if(bool p, uint32_t a) {
  asm volatile("{.reg .pred p; setp.ne.b32 p, %0, 0; @p mbarrier.arrive.shared::cta.b64 _, [%1];}" ::"r"((int)p), "r"(a) : "memory");
}
__device__ __forceinline__ void mbar_expect_if(bool p, uint32_t a, int bytes) {
  asm volatile("{.reg .pred p; setp.ne.b32 p, %0, 0; @p mbarrier.arrive.expect_tx.shared::cta.b64 _, [%1], %2;}" ::"r"((int)p), "r"(a), "r"(bytes) : "memory");
}
__device__ __forceinline__ void tma2d_if(bool p, uint32_t dst, const CUtensorMap* m, int c0, int c1, uint32_t bar) {
  asm volatile("{.reg .pred p; setp.ne.b32 p, %0, 0; @p cp.async.bulk.tensor.2d.shared::cluster.global.mbarrier::complete_tx::bytes [%1], [%2, {%4, %5}], [%3];}"
               ::"r"((int)p), "r"(dst), "l"(m), "r"(bar), "r"(c0), "r"(c1) : "memory");
}
__device__ __forceinline__ void tma3d_if(bool p, uint32_t dst, const CUtensorMap* m, int c1, int c2, uint32_t bar) {
  asm volatile("{.reg .pred p; setp.ne.b32 p, %0, 0; @p cp.async.bulk.tensor.3d.shared::cluster.global.mbarrier::complete_tx::bytes [%1], [%2, {%6, %4, %5}], [%3];}"
               ::"r"((int)p), "r"(dst), "l"(m), "r"(bar), "r"(c1), "r"(c2), "r"(0) : "memory");
}
__device__ __forceinline__ void bulk_g2s_if(bool p, uint32_t dst, const void* src, int bytes, uint32_t bar) {
  asm volatile("{.reg .pred p; setp.ne.b32 p, %0, 0; @p cp.async.bulk.shared::cluster.global.mbarrier::complete_tx::bytes [%1], [%2], %3, [%4];}"
               ::"r"((int)p), "r"(dst), "l"(src), "r"(bytes), "r"(bar) : "memory");
}
__device__ __forceinline__ void tma5d_if(bool p, uint32_t dst, const CUtensorMap* m, int c1, int c2, int c4, uint32_t bar) {
  asm volatile("{.reg .pred p; setp.ne.b32 p, %0, 0; @p cp.async.bulk.tensor.5d.shared::cluster.global.mbarrier::complete_tx::bytes [%1], [%2, {%7, %4, %5, %7, %6}], [%3];}"
               ::"r"((int)p), "r"(dst), "l"(m), "r"(bar), "r"(c1), "r"(c2), "r"(c4), "r"(0) : "memory");
}
__device__ __forceinline__ void tma5d_store_if(bool p, const CUtensorMap* m, uint32_t src, int c1, int c2, int c3, int c4) {
  asm volatile("{.reg .pred p; setp.ne.b32 p, %0, 0; @p cp.async.bulk.tensor.5d.global.shared::cta.bulk_group [%1, {%7, %3, %4, %5, %6}], [%2];}"
               ::"r"((int)p), "l"(m), "r"(src), "r"(c1), "r"(c2), "r"(c3), "r"(c4), "r"(0) : "memory");
}
__device__ __forceinline__ void bulk_s2g_if(bool p, void* dst, uint32_t src, int bytes) {
  asm volatile("{.reg .pred p; setp.ne.b32 p, %0, 0; @p cp.async.bulk.global.shared::cta.bulk_group [%1], [%2], %3;}" ::"r"((int)p), "l"(dst), "r"(src), "r"(bytes) : "memory");
}
__device__ __forceinline__ void bulk_or_if(bool p, void* dst, uint32_t src, int bytes) {
  asm volatile("{.reg .pred p; setp.ne.b32 p, %0, 0; @p cp.reduce.async.bulk.global.shared::cta.bulk_group.or.b32 [%1], [%2], %3;}" ::"r"((int)p), "l"(dst), "r"(src), "r"(bytes) : "memory");
}
__device__ __forceinline__ void bulk_addf_if(bool p, void* dst, uint32_t src, int bytes) {
  asm volatile("{.reg .pred p; setp.ne.b32 p, %0, 0; @p cp.reduce.async.bulk.global.shared::cta.bulk_group.add.f32 [%1], [%2], %3;}" ::"r"((int)p), "l"(dst), "r"(src), "r"(bytes) : "memory");
}
#define BULK_COMMIT() asm volatile("cp.async.bulk.commit_group;" ::: "memory")
#define BULK_WAIT() asm volatile("cp.async.bulk.wait_group 0;" ::: "memory")
#define BULK_WAIT_READ() asm volatile("cp.async.bulk.wait_group.read 0;" ::: "memory")
__device__ __forceinline__ void signal_bulk_if(bool p, uint32_t* c) {
  asm volatile("{.reg .pred p; setp.ne.b32 p, %0, 0; cp.async.bulk.wait_group 0; @p red.relaxed.gpu.global.add.u32 [%1], 1;}" ::"r"((int)p), "l"(c) : "memory");
}
__device__ __forceinline__ void wait_count(const uint32_t* c, uint32_t target) {
  for (int i = 0;; i++) {
    uint32_t v;
    asm volatile("ld.relaxed.gpu.global.u32 %0, [%1];" : "=r"(v) : "l"(c) : "memory");
    if ((int)(v - target) >= 0) break;
    if (i > (1 << 20)) break;
  }
  PROXY_FENCE_G();
}
__device__ __forceinline__ uint32_t pack_bf16(float lo, float hi) { uint32_t r; asm("cvt.rn.bf16x2.f32 %0, %1, %2;" : "=r"(r) : "f"(hi), "f"(lo)); return r; }
__device__ __forceinline__ uint32_t pack_f16(float lo, float hi) { uint32_t r; asm("cvt.rn.f16x2.f32 %0, %1, %2;" : "=r"(r) : "f"(hi), "f"(lo)); return r; }
__device__ __forceinline__ float ex2(float a) { float r; asm("ex2.approx.ftz.f32 %0, %1;" : "=f"(r) : "f"(a)); return r; }
__device__ __forceinline__ float rcp(float a) { float r; asm("rcp.approx.ftz.f32 %0, %1;" : "=f"(r) : "f"(a)); return r; }
__device__ __forceinline__ uint32_t maxabs_bf16x2(uint32_t a, uint32_t b) { uint32_t r; asm("max.NaN.xorsign.abs.bf16x2 %0, %1, %2;" : "=r"(r) : "r"(a), "r"(b)); return r; }
__device__ __forceinline__ uint32_t ldg32(const void* p) { return __ldg(reinterpret_cast<const uint32_t*>(p)); }
__device__ __forceinline__ uint32_t ldcg32(const void* p) { uint32_t v; asm volatile("ld.global.cg.u32 %0, [%1];" : "=r"(v) : "l"(p) : "memory"); return v; }
__device__ __forceinline__ uint32_t lds32(uint32_t a) { uint32_t v; asm volatile("ld.shared.b32 %0, [%1];" : "=r"(v) : "r"(a) : "memory"); return v; }
__device__ __forceinline__ void sts32(uint32_t a, uint32_t v) { asm volatile("st.shared.b32 [%0], %1;" ::"r"(a), "r"(v) : "memory"); }
__device__ __forceinline__ void sts16(uint32_t a, uint16_t v) { asm volatile("st.shared.b16 [%0], %1;" ::"r"(a), "h"(v) : "memory"); }
__device__ __forceinline__ void stsm4(uint32_t a, uint32_t r0, uint32_t r1, uint32_t r2, uint32_t r3) {
  asm volatile("stmatrix.sync.aligned.m8n8.x4.shared.b16 [%0], {%1, %2, %3, %4};" ::"r"(a), "r"(r0), "r"(r1), "r"(r2), "r"(r3) : "memory");
}
template <int N> __device__ __forceinline__ void pin(float (&d)[N]) {
#pragma unroll
  for (int i = 0; i < N; i++) asm volatile("" : "+f"(d[i])::"memory");
}

__device__ __forceinline__ void wg128_ss(float (&d)[64], uint64_t da, uint64_t db, int scale_d) {
  asm volatile("{\n.reg .pred p;\nsetp.ne.b32 p, %66, 0;\n"
    "wgmma.mma_async.sync.aligned.m64n128k16.f32.bf16.bf16 "
    "{%0, %1, %2, %3, %4, %5, %6, %7, %8, %9, %10, %11, %12, %13, %14, %15,"
    "%16, %17, %18, %19, %20, %21, %22, %23, %24, %25, %26, %27, %28, %29, %30, %31,"
    "%32, %33, %34, %35, %36, %37, %38, %39, %40, %41, %42, %43, %44, %45, %46, %47,"
    "%48, %49, %50, %51, %52, %53, %54, %55, %56, %57, %58, %59, %60, %61, %62, %63}, "
    "%64, %65, p, 1, 1, 0, 1;\n}\n"
    : "+f"(d[0]), "+f"(d[1]), "+f"(d[2]), "+f"(d[3]), "+f"(d[4]), "+f"(d[5]), "+f"(d[6]), "+f"(d[7]),
      "+f"(d[8]), "+f"(d[9]), "+f"(d[10]), "+f"(d[11]), "+f"(d[12]), "+f"(d[13]), "+f"(d[14]), "+f"(d[15]),
      "+f"(d[16]), "+f"(d[17]), "+f"(d[18]), "+f"(d[19]), "+f"(d[20]), "+f"(d[21]), "+f"(d[22]), "+f"(d[23]),
      "+f"(d[24]), "+f"(d[25]), "+f"(d[26]), "+f"(d[27]), "+f"(d[28]), "+f"(d[29]), "+f"(d[30]), "+f"(d[31]),
      "+f"(d[32]), "+f"(d[33]), "+f"(d[34]), "+f"(d[35]), "+f"(d[36]), "+f"(d[37]), "+f"(d[38]), "+f"(d[39]),
      "+f"(d[40]), "+f"(d[41]), "+f"(d[42]), "+f"(d[43]), "+f"(d[44]), "+f"(d[45]), "+f"(d[46]), "+f"(d[47]),
      "+f"(d[48]), "+f"(d[49]), "+f"(d[50]), "+f"(d[51]), "+f"(d[52]), "+f"(d[53]), "+f"(d[54]), "+f"(d[55]),
      "+f"(d[56]), "+f"(d[57]), "+f"(d[58]), "+f"(d[59]), "+f"(d[60]), "+f"(d[61]), "+f"(d[62]), "+f"(d[63])
    : "l"(da), "l"(db), "r"(scale_d));
}

__device__ __forceinline__ void wg64_ss_of64(float (&d)[64], uint64_t da, uint64_t db, int scale_d) {
  asm volatile("{\n.reg .pred p;\nsetp.ne.b32 p, %34, 0;\n"
    "wgmma.mma_async.sync.aligned.m64n64k16.f32.bf16.bf16 "
    "{%0, %1, %2, %3, %4, %5, %6, %7, %8, %9, %10, %11, %12, %13, %14, %15,"
    "%16, %17, %18, %19, %20, %21, %22, %23, %24, %25, %26, %27, %28, %29, %30, %31}, "
    "%32, %33, p, 1, 1, 0, 1;\n}\n"
    : "+f"(d[0]), "+f"(d[1]), "+f"(d[2]), "+f"(d[3]), "+f"(d[4]), "+f"(d[5]), "+f"(d[6]), "+f"(d[7]),
      "+f"(d[8]), "+f"(d[9]), "+f"(d[10]), "+f"(d[11]), "+f"(d[12]), "+f"(d[13]), "+f"(d[14]), "+f"(d[15]),
      "+f"(d[16]), "+f"(d[17]), "+f"(d[18]), "+f"(d[19]), "+f"(d[20]), "+f"(d[21]), "+f"(d[22]), "+f"(d[23]),
      "+f"(d[24]), "+f"(d[25]), "+f"(d[26]), "+f"(d[27]), "+f"(d[28]), "+f"(d[29]), "+f"(d[30]), "+f"(d[31])
    : "l"(da), "l"(db), "r"(scale_d));
}

__device__ __forceinline__ void wg192_ss(float (&d)[96], uint64_t da, uint64_t db, int scale_d) {
  asm volatile("{\n.reg .pred p;\nsetp.ne.b32 p, %98, 0;\n"
    "wgmma.mma_async.sync.aligned.m64n192k16.f32.bf16.bf16 "
    "{%0, %1, %2, %3, %4, %5, %6, %7, %8, %9, %10, %11, %12, %13, %14, %15,"
    "%16, %17, %18, %19, %20, %21, %22, %23, %24, %25, %26, %27, %28, %29, %30, %31,"
    "%32, %33, %34, %35, %36, %37, %38, %39, %40, %41, %42, %43, %44, %45, %46, %47,"
    "%48, %49, %50, %51, %52, %53, %54, %55, %56, %57, %58, %59, %60, %61, %62, %63,"
    "%64, %65, %66, %67, %68, %69, %70, %71, %72, %73, %74, %75, %76, %77, %78, %79,"
    "%80, %81, %82, %83, %84, %85, %86, %87, %88, %89, %90, %91, %92, %93, %94, %95}, "
    "%96, %97, p, 1, 1, 0, 1;\n}\n"
    : "+f"(d[0]), "+f"(d[1]), "+f"(d[2]), "+f"(d[3]), "+f"(d[4]), "+f"(d[5]), "+f"(d[6]), "+f"(d[7]),
      "+f"(d[8]), "+f"(d[9]), "+f"(d[10]), "+f"(d[11]), "+f"(d[12]), "+f"(d[13]), "+f"(d[14]), "+f"(d[15]),
      "+f"(d[16]), "+f"(d[17]), "+f"(d[18]), "+f"(d[19]), "+f"(d[20]), "+f"(d[21]), "+f"(d[22]), "+f"(d[23]),
      "+f"(d[24]), "+f"(d[25]), "+f"(d[26]), "+f"(d[27]), "+f"(d[28]), "+f"(d[29]), "+f"(d[30]), "+f"(d[31]),
      "+f"(d[32]), "+f"(d[33]), "+f"(d[34]), "+f"(d[35]), "+f"(d[36]), "+f"(d[37]), "+f"(d[38]), "+f"(d[39]),
      "+f"(d[40]), "+f"(d[41]), "+f"(d[42]), "+f"(d[43]), "+f"(d[44]), "+f"(d[45]), "+f"(d[46]), "+f"(d[47]),
      "+f"(d[48]), "+f"(d[49]), "+f"(d[50]), "+f"(d[51]), "+f"(d[52]), "+f"(d[53]), "+f"(d[54]), "+f"(d[55]),
      "+f"(d[56]), "+f"(d[57]), "+f"(d[58]), "+f"(d[59]), "+f"(d[60]), "+f"(d[61]), "+f"(d[62]), "+f"(d[63]),
      "+f"(d[64]), "+f"(d[65]), "+f"(d[66]), "+f"(d[67]), "+f"(d[68]), "+f"(d[69]), "+f"(d[70]), "+f"(d[71]),
      "+f"(d[72]), "+f"(d[73]), "+f"(d[74]), "+f"(d[75]), "+f"(d[76]), "+f"(d[77]), "+f"(d[78]), "+f"(d[79]),
      "+f"(d[80]), "+f"(d[81]), "+f"(d[82]), "+f"(d[83]), "+f"(d[84]), "+f"(d[85]), "+f"(d[86]), "+f"(d[87]),
      "+f"(d[88]), "+f"(d[89]), "+f"(d[90]), "+f"(d[91]), "+f"(d[92]), "+f"(d[93]), "+f"(d[94]), "+f"(d[95])
    : "l"(da), "l"(db), "r"(scale_d));
}

__device__ __forceinline__ void wg128_ss_of96(float (&d)[96], uint64_t da, uint64_t db, int scale_d) {
  asm volatile("{\n.reg .pred p;\nsetp.ne.b32 p, %66, 0;\n"
    "wgmma.mma_async.sync.aligned.m64n128k16.f32.bf16.bf16 "
    "{%0, %1, %2, %3, %4, %5, %6, %7, %8, %9, %10, %11, %12, %13, %14, %15,"
    "%16, %17, %18, %19, %20, %21, %22, %23, %24, %25, %26, %27, %28, %29, %30, %31,"
    "%32, %33, %34, %35, %36, %37, %38, %39, %40, %41, %42, %43, %44, %45, %46, %47,"
    "%48, %49, %50, %51, %52, %53, %54, %55, %56, %57, %58, %59, %60, %61, %62, %63}, "
    "%64, %65, p, 1, 1, 0, 1;\n}\n"
    : "+f"(d[0]), "+f"(d[1]), "+f"(d[2]), "+f"(d[3]), "+f"(d[4]), "+f"(d[5]), "+f"(d[6]), "+f"(d[7]),
      "+f"(d[8]), "+f"(d[9]), "+f"(d[10]), "+f"(d[11]), "+f"(d[12]), "+f"(d[13]), "+f"(d[14]), "+f"(d[15]),
      "+f"(d[16]), "+f"(d[17]), "+f"(d[18]), "+f"(d[19]), "+f"(d[20]), "+f"(d[21]), "+f"(d[22]), "+f"(d[23]),
      "+f"(d[24]), "+f"(d[25]), "+f"(d[26]), "+f"(d[27]), "+f"(d[28]), "+f"(d[29]), "+f"(d[30]), "+f"(d[31]),
      "+f"(d[32]), "+f"(d[33]), "+f"(d[34]), "+f"(d[35]), "+f"(d[36]), "+f"(d[37]), "+f"(d[38]), "+f"(d[39]),
      "+f"(d[40]), "+f"(d[41]), "+f"(d[42]), "+f"(d[43]), "+f"(d[44]), "+f"(d[45]), "+f"(d[46]), "+f"(d[47]),
      "+f"(d[48]), "+f"(d[49]), "+f"(d[50]), "+f"(d[51]), "+f"(d[52]), "+f"(d[53]), "+f"(d[54]), "+f"(d[55]),
      "+f"(d[56]), "+f"(d[57]), "+f"(d[58]), "+f"(d[59]), "+f"(d[60]), "+f"(d[61]), "+f"(d[62]), "+f"(d[63])
    : "l"(da), "l"(db), "r"(scale_d));
}

__device__ __forceinline__ void wg64_rs_bf16(float (&d)[32], uint32_t a0, uint32_t a1, uint32_t a2, uint32_t a3, uint64_t db, int scale_d) {
  asm volatile("{\n.reg .pred p;\nsetp.ne.b32 p, %37, 0;\n"
    "wgmma.mma_async.sync.aligned.m64n64k16.f32.bf16.bf16 "
    "{%0, %1, %2, %3, %4, %5, %6, %7, %8, %9, %10, %11, %12, %13, %14, %15,"
    "%16, %17, %18, %19, %20, %21, %22, %23, %24, %25, %26, %27, %28, %29, %30, %31}, "
    "{%32, %33, %34, %35}, %36, p, 1, 1, 0;\n}\n"
    : "+f"(d[0]), "+f"(d[1]), "+f"(d[2]), "+f"(d[3]), "+f"(d[4]), "+f"(d[5]), "+f"(d[6]), "+f"(d[7]),
      "+f"(d[8]), "+f"(d[9]), "+f"(d[10]), "+f"(d[11]), "+f"(d[12]), "+f"(d[13]), "+f"(d[14]), "+f"(d[15]),
      "+f"(d[16]), "+f"(d[17]), "+f"(d[18]), "+f"(d[19]), "+f"(d[20]), "+f"(d[21]), "+f"(d[22]), "+f"(d[23]),
      "+f"(d[24]), "+f"(d[25]), "+f"(d[26]), "+f"(d[27]), "+f"(d[28]), "+f"(d[29]), "+f"(d[30]), "+f"(d[31])
    : "r"(a0), "r"(a1), "r"(a2), "r"(a3), "l"(db), "r"(scale_d));
}

__device__ __forceinline__ void wg24_rs_f16_t(float (&d)[12], uint32_t a0, uint32_t a1, uint32_t a2, uint32_t a3, uint64_t db, int scale_d) {
  asm volatile("{\n.reg .pred p;\nsetp.ne.b32 p, %17, 0;\n"
    "wgmma.mma_async.sync.aligned.m64n24k16.f32.f16.f16 "
    "{%0, %1, %2, %3, %4, %5, %6, %7, %8, %9, %10, %11}, "
    "{%12, %13, %14, %15}, %16, p, 1, 1, 1;\n}\n"
    : "+f"(d[0]), "+f"(d[1]), "+f"(d[2]), "+f"(d[3]), "+f"(d[4]), "+f"(d[5]), "+f"(d[6]), "+f"(d[7]),
      "+f"(d[8]), "+f"(d[9]), "+f"(d[10]), "+f"(d[11])
    : "r"(a0), "r"(a1), "r"(a2), "r"(a3), "l"(db), "r"(scale_d));
}

__device__ __forceinline__ void wg24_rs_bf16(float (&d)[12], uint32_t a0, uint32_t a1, uint32_t a2, uint32_t a3, uint64_t db, int scale_d) {
  asm volatile("{\n.reg .pred p;\nsetp.ne.b32 p, %17, 0;\n"
    "wgmma.mma_async.sync.aligned.m64n24k16.f32.bf16.bf16 "
    "{%0, %1, %2, %3, %4, %5, %6, %7, %8, %9, %10, %11}, "
    "{%12, %13, %14, %15}, %16, p, 1, 1, 0;\n}\n"
    : "+f"(d[0]), "+f"(d[1]), "+f"(d[2]), "+f"(d[3]), "+f"(d[4]), "+f"(d[5]), "+f"(d[6]), "+f"(d[7]),
      "+f"(d[8]), "+f"(d[9]), "+f"(d[10]), "+f"(d[11])
    : "r"(a0), "r"(a1), "r"(a2), "r"(a3), "l"(db), "r"(scale_d));
}

__device__ __forceinline__ void wg24_ss_bf16_tt(float (&d)[12], uint64_t da, uint64_t db, int scale_d) {
  asm volatile("{\n.reg .pred p;\nsetp.ne.b32 p, %14, 0;\n"
    "wgmma.mma_async.sync.aligned.m64n24k16.f32.bf16.bf16 "
    "{%0, %1, %2, %3, %4, %5, %6, %7, %8, %9, %10, %11}, "
    "%12, %13, p, 1, 1, 1, 1;\n}\n"
    : "+f"(d[0]), "+f"(d[1]), "+f"(d[2]), "+f"(d[3]), "+f"(d[4]), "+f"(d[5]), "+f"(d[6]), "+f"(d[7]),
      "+f"(d[8]), "+f"(d[9]), "+f"(d[10]), "+f"(d[11])
    : "l"(da), "l"(db), "r"(scale_d));
}

__device__ __forceinline__ void wg64_rs_bf16_i(float (&d)[32], uint32_t a0, uint32_t a1, uint32_t a2, uint32_t a3, uint64_t db) {
  asm volatile("{\n.reg .pred p;\nsetp.ne.b32 p, 0, 0;\n"
    "wgmma.mma_async.sync.aligned.m64n64k16.f32.bf16.bf16 "
    "{%0, %1, %2, %3, %4, %5, %6, %7, %8, %9, %10, %11, %12, %13, %14, %15,"
    "%16, %17, %18, %19, %20, %21, %22, %23, %24, %25, %26, %27, %28, %29, %30, %31}, "
    "{%32, %33, %34, %35}, %36, p, 1, 1, 0;\n}\n"
    : "=f"(d[0]), "=f"(d[1]), "=f"(d[2]), "=f"(d[3]), "=f"(d[4]), "=f"(d[5]), "=f"(d[6]), "=f"(d[7]),
      "=f"(d[8]), "=f"(d[9]), "=f"(d[10]), "=f"(d[11]), "=f"(d[12]), "=f"(d[13]), "=f"(d[14]), "=f"(d[15]),
      "=f"(d[16]), "=f"(d[17]), "=f"(d[18]), "=f"(d[19]), "=f"(d[20]), "=f"(d[21]), "=f"(d[22]), "=f"(d[23]),
      "=f"(d[24]), "=f"(d[25]), "=f"(d[26]), "=f"(d[27]), "=f"(d[28]), "=f"(d[29]), "=f"(d[30]), "=f"(d[31])
    : "r"(a0), "r"(a1), "r"(a2), "r"(a3), "l"(db));
}

__device__ __forceinline__ void wg24_rs_bf16_i(float (&d)[12], uint32_t a0, uint32_t a1, uint32_t a2, uint32_t a3, uint64_t db) {
  asm volatile("{\n.reg .pred p;\nsetp.ne.b32 p, 0, 0;\n"
    "wgmma.mma_async.sync.aligned.m64n24k16.f32.bf16.bf16 "
    "{%0, %1, %2, %3, %4, %5, %6, %7, %8, %9, %10, %11}, "
    "{%12, %13, %14, %15}, %16, p, 1, 1, 0;\n}\n"
    : "=f"(d[0]), "=f"(d[1]), "=f"(d[2]), "=f"(d[3]), "=f"(d[4]), "=f"(d[5]), "=f"(d[6]), "=f"(d[7]),
      "=f"(d[8]), "=f"(d[9]), "=f"(d[10]), "=f"(d[11])
    : "r"(a0), "r"(a1), "r"(a2), "r"(a3), "l"(db));
}

__device__ __forceinline__ void wg24_ss_bf16_tt_i(float (&d)[12], uint64_t da, uint64_t db) {
  asm volatile("{\n.reg .pred p;\nsetp.ne.b32 p, 0, 0;\n"
    "wgmma.mma_async.sync.aligned.m64n24k16.f32.bf16.bf16 "
    "{%0, %1, %2, %3, %4, %5, %6, %7, %8, %9, %10, %11}, "
    "%12, %13, p, 1, 1, 1, 1;\n}\n"
    : "=f"(d[0]), "=f"(d[1]), "=f"(d[2]), "=f"(d[3]), "=f"(d[4]), "=f"(d[5]), "=f"(d[6]), "=f"(d[7]),
      "=f"(d[8]), "=f"(d[9]), "=f"(d[10]), "=f"(d[11])
    : "l"(da), "l"(db));
}

__device__ __forceinline__ void wg24_ss_bf16(float (&d)[12], uint64_t da, uint64_t db, int scale_d) {
  asm volatile("{\n.reg .pred p;\nsetp.ne.b32 p, %14, 0;\n"
    "wgmma.mma_async.sync.aligned.m64n24k16.f32.bf16.bf16 "
    "{%0, %1, %2, %3, %4, %5, %6, %7, %8, %9, %10, %11}, "
    "%12, %13, p, 1, 1, 0, 0;\n}\n"
    : "+f"(d[0]), "+f"(d[1]), "+f"(d[2]), "+f"(d[3]), "+f"(d[4]), "+f"(d[5]), "+f"(d[6]), "+f"(d[7]),
      "+f"(d[8]), "+f"(d[9]), "+f"(d[10]), "+f"(d[11])
    : "l"(da), "l"(db), "r"(scale_d));
}

__device__ __forceinline__ void wg24_ss_bf16_i(float (&d)[12], uint64_t da, uint64_t db) {
  asm volatile("{\n.reg .pred p;\nsetp.ne.b32 p, 0, 0;\n"
    "wgmma.mma_async.sync.aligned.m64n24k16.f32.bf16.bf16 "
    "{%0, %1, %2, %3, %4, %5, %6, %7, %8, %9, %10, %11}, "
    "%12, %13, p, 1, 1, 0, 0;\n}\n"
    : "=f"(d[0]), "=f"(d[1]), "=f"(d[2]), "=f"(d[3]), "=f"(d[4]), "=f"(d[5]), "=f"(d[6]), "=f"(d[7]),
      "=f"(d[8]), "=f"(d[9]), "=f"(d[10]), "=f"(d[11])
    : "l"(da), "l"(db));
}

constexpr int P1_STB = 49152, P3_STB = 40960;
constexpr int SM_X = 196608;
constexpr int SM_KVB = SM_X + 24576;
constexpr int SM_GW = SM_X + 8192, SM_WRAW = SM_GW + 1280, SM_EP = SM_WRAW + 800;
constexpr int SM_CONST = SM_X + 32768, SM_WPHI = SM_CONST + 1024, SM_BAR = SM_WPHI + 1536;
constexpr int SMEM_BYTES = SM_BAR + 512;
constexpr int B_FULL = 0, B_AUX = 4, B_KB = 5, B_QB = 6, B_KVFULL = 7, B_P3FULL = 11, B_P3EMPTY = 15, B_EMPTY = 19, B_LINK = 23, B_FREE = 25,
              B_STG = 28, B_B2 = 29, B_ZERO = 30, B_READY = 31, B_KVB = 35;

template <int V> struct Int { static constexpr int value = V; };
struct Maps { CUtensorMap x, w[2], wo[2], out, qld, qst; };

__device__ __forceinline__ int tile_atom(int t) { return (t >> 2) * 15 + ((0xB740 >> ((t & 3) * 4)) & 15); }

template <int MODE, int A>
__device__ __forceinline__ void pack_atom(const float (&acc)[64], uint32_t (&r)[32], float s0, float s1, uint32_t& m0, uint32_t& m1) {
#pragma unroll
  for (int e = A * 16; e < A * 16 + 16; e++) {
    const float s = (e & 1) ? s1 : s0;
    if (MODE == 0) r[e] = pack_bf16(acc[2 * e], acc[2 * e + 1]);
    else if (MODE == 3) r[e] = pack_f16(acc[2 * e], acc[2 * e + 1]);
    else r[e] = pack_bf16(acc[2 * e] * s, acc[2 * e + 1] * s);
    if (MODE == 2) { if (e & 1) m1 = maxabs_bf16x2(m1, r[e]); else m0 = maxabs_bf16x2(m0, r[e]); }
  }
}
template <int A>
__device__ __forceinline__ void pack_atom_a(const float (&acc)[64], uint32_t (&r)[32], int ga, float sk0, float sk1, uint32_t& m0, uint32_t& m1) {
  if (ga < 10) { const float cq = __uint_as_float(463809372u); pack_atom<1, A>(acc, r, cq, cq, m0, m1); }
  else if (ga < 20) pack_atom<2, A>(acc, r, sk0, sk1, m0, m1);
  else pack_atom<3, A>(acc, r, 0.f, 0.f, m0, m1);
}

__device__ __forceinline__ uint32_t exp2_pair(float a, float b) {
  uint32_t z, w, h;
  asm volatile("cvt.pack.sat.s16.s32 %0, %2, %1;" : "=r"(z) : "r"(__float_as_uint(a)), "r"(__float_as_uint(b)));
  asm volatile("lop3.b32 %0, %1, 0x03ff03ff, 0x34003400, 0xEA;" : "=r"(w) : "r"(z));
  asm volatile("fma.rn.f16x2 %0, %1, %1, %2;" : "=r"(h) : "r"(w), "r"(0x36203620));
  asm volatile("fma.rn.f16x2 %0, %0, %1, %2;" : "+r"(h) : "r"(w), "r"(0x2e012e01));
  return h + z - w;
}
__device__ __forceinline__ uint32_t exp2_pair_mufu(float a, float b) {
  float x, y; uint32_t r;
  asm volatile("ex2.approx.ftz.f32 %0, %1;" : "=f"(x) : "f"(a));
  asm volatile("ex2.approx.ftz.f32 %0, %1;" : "=f"(y) : "f"(b));
  asm volatile("cvt.rn.f16x2.f32 %0, %1, %2;" : "=r"(r) : "f"(y), "f"(x));
  return r;
}
__device__ __forceinline__ void load_frag(uint32_t (&a)[6], const uint8_t* p) {
  a[0] = ldcg32(p); a[1] = ldcg32(p + 128); a[2] = ldcg32(p + 2048); a[3] = ldcg32(p + 2048 + 128); a[4] = ldcg32(p + 4096); a[5] = ldcg32(p + 4096 + 128);
}
template <bool EXACT>
__device__ __forceinline__ bool feature_rows(uint32_t (&phi)[10], const float (&p)[12]) {
  const float L = 1.4426950408889634f;
  bool ok = true;
#pragma unroll
  for (int r = 0; r < 2; r++) {
    const float v[5] = {p[2 * r], p[2 * r + 1], p[4 + 2 * r], p[5 + 2 * r], p[8 + 2 * r]};
    float ep[5], en[5];
    if (EXACT) {
      float mx = fmaxf(fmaxf(fmaxf(v[0], v[1]), fmaxf(v[2], v[3])), v[4]);
      float mn = fminf(fminf(fminf(v[0], v[1]), fminf(v[2], v[3])), v[4]);
      mx = fmaxf(mx, __shfl_xor_sync(0xffffffffu, mx, 1)); mn = fminf(mn, __shfl_xor_sync(0xffffffffu, mn, 1));
      mx = fmaxf(mx, __shfl_xor_sync(0xffffffffu, mx, 2)); mn = fminf(mn, __shfl_xor_sync(0xffffffffu, mn, 2));
#pragma unroll
      for (int i = 0; i < 5; i++) { ep[i] = ex2((v[i] - mx) * L); en[i] = ex2((mn - v[i]) * L); }
    } else {
#pragma unroll
      for (int i = 0; i < 5; i++) { const float u = v[i] * L; ep[i] = ex2(u); en[i] = ex2(-u); }
    }
    float sp = (ep[0] + ep[1]) + (ep[2] + ep[3]) + ep[4], sn = (en[0] + en[1]) + (en[2] + en[3]) + en[4];
    sp += __shfl_xor_sync(0xffffffffu, sp, 1); sn += __shfl_xor_sync(0xffffffffu, sn, 1);
    sp += __shfl_xor_sync(0xffffffffu, sp, 2); sn += __shfl_xor_sync(0xffffffffu, sn, 2);
    ok = ok && sp + sn < 1.2676506e30f;
    const float rp = rcp(sp), rn = rcp(sn);
#pragma unroll
    for (int i = 0; i < 5; i++) phi[5 * r + i] = pack_bf16(ep[i] * rp, en[i] * rn);
  }
  return ok;
}
__device__ __forceinline__ void feature_map(uint32_t (&phi)[10], const float (&p)[12]) {
  if (!__all_sync(0xffffffffu, feature_rows<false>(phi, p))) feature_rows<true>(phi, p);
}
__device__ __forceinline__ void phi_proj(float (&p0)[12], float (&p1)[12], uint32_t a, uint64_t dw) {
  const uint64_t da = mkdesc(a, 1024, 128, 0), db = mkdesc(a + 2048, 0, 128, 0);
  WG_FENCE();
  wg24_ss_bf16_i(p0, da, dw);
  wg24_ss_bf16(p0, db, dw + 48, 1);
  wg24_ss_bf16_i(p1, da + 384, dw);
  wg24_ss_bf16(p1, db + 384, dw + 48, 1);
  WG_COMMIT();
  WG_WAIT(0);
  pin(p0); pin(p1);
}
__device__ __forceinline__ void stage_o(const float (&o)[12], float s0, float s1, uint32_t a, bool v0, bool v2) {
#pragma unroll
  for (int j = 0; j < 3; j++) {
    const bool v = j == 1 || (j == 0 ? v0 : v2);
    sts32(a + j * 2048, v ? pack_bf16(o[4 * j] * s0, o[4 * j + 1] * s0) : 0u);
    sts32(a + j * 2048 + 128, v ? pack_bf16(o[4 * j + 2] * s1, o[4 * j + 3] * s1) : 0u);
  }
}
__device__ __forceinline__ void flush_o(bool p, uint8_t* dst, uint32_t src, bool odd) {
  bulk_s2g_if(p, dst + (odd ? 2048 : 0), src + (odd ? 2048 : 0), 4096);
  bulk_or_if(p, dst + (odd ? 0 : 4096), src + (odd ? 0 : 4096), 2048);
  BULK_COMMIT();
}

__device__ __forceinline__ void proj20(float (&acc)[20], const __nv_bfloat16* __restrict__ xr, const __nv_bfloat16* __restrict__ wc) {
#pragma unroll
  for (int d = 0; d < 20; d++) acc[d] = 0.f;
#pragma unroll 2
  for (int k = 0; k < 640; k++) {
    const float xv = __bfloat162float(xr[k]);
#pragma unroll
    for (int d = 0; d < 10; d++) {
      const uint32_t u = ldg32(wc + k * 1920 + 2 * d);
      acc[2 * d] = fmaf(xv, __uint_as_float(u << 16), acc[2 * d]);
      acc[2 * d + 1] = fmaf(xv, __uint_as_float(u & 0xffff0000u), acc[2 * d + 1]);
    }
  }
}
__device__ __noinline__ void attn_exact(const __nv_bfloat16* __restrict__ x, const __nv_bfloat16* __restrict__ wqkv, int h, int qt, uint32_t stg) {
  const int tid = threadIdx.x;
  uint32_t* kvs = g_fb + blockIdx.x * (2048 * 20);
  float a[20];
  for (int i = 0; i < 8; i++) {
    const int key = (i >> 1) * 512 + tid, ty = 1 + (i & 1);
    proj20(a, x + key * 640, wqkv + ty * 640 + h * 20);
#pragma unroll
    for (int d = 0; d < 10; d++) kvs[key * 20 + (i & 1) * 10 + d] = pack_bf16(a[2 * d], a[2 * d + 1]);
  }
  const int row = qt * 512 + tid;
  proj20(a, x + row * 640, wqkv + h * 20);
#pragma unroll
  for (int d = 0; d < 20; d++) a[d] = __bfloat162float(__float2bfloat16(a[d]));
  __syncthreads();
  float o[20], m = -INFINITY, l = 0.f;
#pragma unroll
  for (int d = 0; d < 20; d++) o[d] = 0.f;
  for (int key = 0; key < 2048; key++) {
    uint32_t u[20];
#pragma unroll
    for (int d = 0; d < 5; d++) {
      const uint4 t4 = *reinterpret_cast<const uint4*>(kvs + key * 20 + 4 * d);
      u[4 * d] = t4.x; u[4 * d + 1] = t4.y; u[4 * d + 2] = t4.z; u[4 * d + 3] = t4.w;
    }
    float s = 0.f;
#pragma unroll
    for (int d = 0; d < 10; d++) {
      s = fmaf(a[2 * d], __uint_as_float(u[d] << 16), s);
      s = fmaf(a[2 * d + 1], __uint_as_float(u[d] & 0xffff0000u), s);
    }
    s *= 0.22360679774997896f;
    const float mn = fmaxf(m, s), cr = __expf(m - mn), p = __expf(s - mn);
    m = mn;
    l = l * cr + p;
#pragma unroll
    for (int d = 0; d < 10; d++) {
      o[2 * d] = fmaf(p, __uint_as_float(u[10 + d] << 16), o[2 * d] * cr);
      o[2 * d + 1] = fmaf(p, __uint_as_float(u[10 + d] & 0xffff0000u), o[2 * d + 1] * cr);
    }
  }
  const float sc = __ldcg(&g_gate[row]) / l;
#pragma unroll
  for (int d = 0; d < 10; d++) {
    const int col = (h & 1) * 4 + 2 * d;
    sts32(stg + (tid >> 7) * 6144 + (col >> 3) * 2048 + (tid & 127) * 16 + (col & 7) * 2, pack_bf16(o[2 * d] * sc, o[2 * d + 1] * sc));
  }
  PROXY_FENCE();
  __syncthreads();
}

#define COORDS()                                                                                                        \
  int tid, bid;                                                                                                         \
  asm volatile("mov.u32 %0, %%tid.x;" : "=r"(tid));                                                                     \
  asm volatile("mov.u32 %0, %%ctaid.x;" : "=r"(bid));                                                                   \
  const int wg = __shfl_sync(0xffffffffu, tid >> 7, 0);                                                                 \
  const int lane = tid & 31, w = (tid >> 5) & 3, g = lane >> 2, t = lane & 3, wt = tid & 127;                           \
  const int rb1 = bid >> 3, c1 = bid & 7;                                       \
  const int h = bid >> 2, qt = bid & 3, rb = qt * 4 + wg;                    \
  const bool odd = h & 1;                                                                                               \
  const int c0 = (h * 5) >> 1;                                               \
  const int lsrc = (lane & ~3) | (odd ? 0 : 2);                                                                         \
  const bool v0 = !odd || t >= 2, v2 = odd || t < 2;                                                                    \
  const uint32_t ostg = sb + SM_X + wg * 6144, orow = (w * 16 + g) * 16 + t * 4;                                        \
  const uint32_t onepos = (wt >> 6) * 6144 + 3072 + (odd ? 0 : 2048 + 8) + (wt & 63) * 16;                              \
  const int kh = bid & 1, cg = (bid >> 1) & 3, atom3 = (cg >> 1) * 5 + (cg & 1) * 2;                                    \
  auto p3_load_w = [&](bool p, int j) {                                                                                 \
    const uint32_t fb = bar + 8 * (B_P3FULL + (j & 3));                                                                 \
    mbar_expect_if(p, fb, P3_STB);                                                                                      \
    tma3d_if(p, sb + (j & 3) * P3_STB + 16384, &maps.wo[j < 5], (kh * 5 + (j < 5 ? j : j - 5)) * 64, atom3, fb);       \
  };                                                                                                                    \
  auto p3_load_a = [&](bool p, int j) {                                                                                 \
    bulk_g2s_if(p, sb + (j & 3) * P3_STB, g_o + rb1 * ORB + ((j < 5 ? 10 + j : j - 5) + kh * 5) * 16384, 16384,         \
                bar + 8 * (B_P3FULL + (j & 3)));                                                                        \
  };                                                                                                                    \
  (void)g; (void)t; (void)wt; (void)rb1; (void)c1; (void)rb; (void)c0; (void)lsrc; (void)v0; (void)v2; (void)ostg;      \
  (void)orow; (void)onepos; (void)atom3; (void)p3_load_w; (void)p3_load_a

__global__ void __launch_bounds__(512, 1)
gated_mix_kernel(const __grid_constant__ Maps maps, const __nv_bfloat16* __restrict__ x, const __nv_bfloat16* __restrict__ wqkv, const __nv_bfloat16* __restrict__ w_phi,
                 const __nv_bfloat16* __restrict__ gate_w, const void* wqkv_b, const void* wo_a, const void* wo_b, uint4* __restrict__ out) {
  extern __shared__ __align__(1024) uint8_t smem_raw[];
  const uint32_t sb = (uint32_t)__cvta_generic_to_shared(smem_raw);
  const uint32_t bar = sb + SM_BAR;
  uint32_t q[2][6], qc[4], epoch, events;
  int bad;
  {
  COORDS();
  TS_INIT();

  auto p1_load = [&](bool p, int it) {
    const int st = it & 3, br = it >= 10, ks = it - br * 10;
    const uint32_t dst = sb + st * P1_STB, fb = bar + 8 * (B_FULL + st);
    mbar_expect_if(p, fb, P1_STB);
    tma2d_if(p, dst, &maps.x, ks * 64, rb1 * 128, fb);
    tma3d_if(p, dst + 16384, &maps.w[br], ks * 64, tile_atom(c1 ^ br), fb);
  };
  if (wt == 0) {
    mbar_init(bar + 8 * (B_FULL + wg), 1);
    asm volatile("fence.mbarrier_init.release.cluster;" ::: "memory");
    if (wg == 0) p1_load(true, 0);
  }
  TS_REG(tsa_);
  if (wt == 32) {
#pragma unroll
    for (int u = 0; u < 4; u++)
      if (wg == u) {
#pragma unroll
        for (int i = B_AUX + u * 8; i < B_AUX + u * 8 + 8; i++)
          mbar_init(bar + 8 * i, i == B_AUX ? 3 : i < B_P3EMPTY ? 1 : i < B_EMPTY ? 2 : i < B_ZERO ? 4 : i == B_ZERO ? 16 : i < B_READY + 2 ? 512 : 128);
      }
    asm volatile("fence.mbarrier_init.release.cluster;" ::: "memory");
  }
  TS_REG(tsb_);
  TS_REG(tsc_);
  asm volatile("st.shared.v4.b32 [%0], {%1, %1, %1, %1};" ::"r"(sb + SM_X + tid * 16), "r"(0) : "memory");
  if (tid < 256) sts32(sb + SM_CONST + tid * 4, (tid & 3) ? 0u : ((tid >> 5) < NMB ? 0xdd02e192u : 0x00001ef0u));
  PROXY_FENCE();
  TS_REG(tsd_);
  __syncthreads();
  TS_PUT(16, tsa_, 0); TS_PUT(17, tsb_, 32); TS_PUT(18, tsc_, 32); TS_PUT(19, tsd_, 32);
  if (wg > 0) p1_load(wt == 0, wg);
  if (wt == 64) {
    if (wg == 1) { mbar_expect_if(true, bar + 8 * B_AUX, 1280); bulk_g2s_if(true, sb + SM_GW, gate_w, 1280, bar + 8 * B_AUX); }
    if (wg == 2) { mbar_expect_if(true, bar + 8 * B_AUX, 800); bulk_g2s_if(true, sb + SM_WRAW, w_phi + h * 400, 800, bar + 8 * B_AUX); }
    if (wg == 3) { mbar_expect_if(true, bar + 8 * B_AUX, 16); bulk_g2s_if(true, sb + SM_EP, &g_cnt[C_EPOCH], 16, bar + 8 * B_AUX); }
  }
  TS_FIRST();
  TS_MARK(1);

  {
    float acc[64];
    const int r = wg & 1, ch = wg >> 1;
    const bool mufu0 = 2 * w < NMB, mufu1 = 2 * w + 1 < NMB;
    uint32_t pk[32];
    float gs = 0.f;
    const int grow = c1 * 16 + (tid >> 5);
    auto stage = [&](uint32_t stg, int e0) {
#pragma unroll
      for (int e = 0; e < 16; e += 4) stsm4(stg + (w * 16 + (lane & 15)) * 16 + (lane >> 4) * 1024 + e * 512, pk[e0 + e], pk[e0 + e + 1], pk[e0 + e + 2], pk[e0 + e + 3]);
    };
    auto duties = [&](auto BR, int it, int ga0, bool narrow_a) {
      constexpr int br = decltype(BR)::value;
      if (wg == (it & 3) && it >= 1 && it <= 16) {
        mbar_wait(bar + 8 * (B_EMPTY + ((it - 1) & 3)), ((it - 1) >> 2) & 1);
        p1_load(wt == 0, it + 3);
      }
      if (br == 0 && wg == 0 && it >= 1 && it <= 4) {
        const bool p = wt == 0;
        if (it < 4) bulk_s2g_if(p, reinterpret_cast<uint8_t*>(out) + bid * 20480 + (it - 1) * 8192, sb + SM_X, it == 3 ? 4096 : 8192);
        else bulk_s2g_if(p, g_kv + bid * 240, sb + SM_X, 960);
        bulk_s2g_if(p, g_o + rb1 * ORB + ((c1 * 4 + it - 1) * 5 + 2) * 2048, sb + SM_X, 2048);
        BULK_COMMIT();
      }
      if (br == 0 && it == 2 && wg == 1 && wt < 3) {
        const int bytes = wt == 0 ? 19200 : 6400;
        const uint8_t* p = reinterpret_cast<const uint8_t*>(wt == 0 ? wqkv_b : wt == 1 ? wo_a : wo_b) + bid * bytes;
        asm volatile("cp.async.bulk.prefetch.L2.global [%0], %1;" ::"l"(p), "r"(bytes) : "memory");
      }
      if (br == 0 && it == 4) {
        epoch = (lds32(sb + SM_EP) >> 7) + 1;
#pragma unroll
        for (int u = 0; u < 2; u++) {
          const int i = tid + u * 512, k = i / 24, n = i % 24, ii = 2 * (n >> 3) + (n & 1), f = 4 * ii + ((n & 7) >> 1), d = k - (odd ? 4 : 0);
          uint16_t v = 0;
          if (d >= 0 && d < 20 && ii < 5) asm volatile("ld.shared.u16 %0, [%1];" : "=h"(v) : "r"(sb + SM_WRAW + (d * 20 + f) * 2) : "memory");
          if (i < 768) sts16(sb + SM_WPHI + (k >> 3) * 384 + n * 16 + (k & 7) * 2, v);
        }
      }
      if (br == 0 && it == 6 && wg == 0) BULK_WAIT_READ();
      if (br == 1 && (it == 10 || it == 12)) {
        const int u = it == 12;
        if (!u) {
#pragma unroll
          for (int o = 16; o; o >>= 1) gs += __shfl_xor_sync(0xffffffffu, gs, o);
          if (lane == 0) sts32(sb + SM_BAR + 448 + (tid >> 5) * 4, __float_as_uint(1.f / (1.f + __expf(-gs))));
          mbar_wait(bar + 8 * B_ZERO, 0);
          stage(sb + SM_X + wg * 8192, 0);
        } else {
          BULK_WAIT_READ();
          bar_sync(1 + wg, 128);
          stage(sb + SM_X + wg * 8192, 16);
        }
        PROXY_FENCE();
        bar_sync(1 + wg, 128);
        tma5d_store_if(wt == 0 && !(u && narrow_a), &maps.qst, sb + SM_X + wg * 8192, ((ga0 + u) % 10) * 8, (ga0 + u) / 10, wg & 1, rb1);
        bulk_s2g_if(wt == 0 && !u, g_gate + rb1 * 128 + c1 * 16 + wg * 4, sb + SM_BAR + 448 + wg * 16, 16);
        BULK_COMMIT();
      }
      if (br == 1 && it == 15) signal_bulk_if(wt == 0, &g_cnt[C_TA]);
      if (br == 1 && it >= 17 && it <= 18 && wg == (it & 3)) {
        wait_count(&g_cnt[C_TA], epoch * 512);
        mbar_wait(bar + 8 * (B_EMPTY + (it - 17)), 0);
        mbar_expect_if(wt == 0, bar + 8 * (B_KVFULL + it - 17), P1_STB);
        tma5d_if(wt == 0, sb + (it - 17) * P1_STB, &maps.qld, c0, 1, (it - 17) * 4, bar + 8 * (B_KVFULL + it - 17));
      }
      if (br == 1 && it == 19) {
        mbar_wait(bar + 8 * (B_KVFULL + 0), 0);
        const uint8_t* qp = g_qkv + rb * QRB + c0 * 2048 + orow;
        load_frag(q[0], qp);
        load_frag(q[1], qp + 1024);
        bad = ldcg32(&g_kbad);
        sts16(sb + wg * 12288 + onepos, 0x3c00);
        PROXY_FENCE();
        mbar_arrive(bar + 8 * (B_READY + 0));
      }
    };
    const int ga_a = tile_atom(c1) + 2 * ch + (((c1 & 3) == 2 && wg == 0) ? 1 : 0);
    const bool narrow_a = ((c1 & 3) == 1 && wg == 3) || ((c1 & 3) == 2 && wg == 0);
    uint32_t xh[3] = {0u, 0u, 0u};
    auto gate_fma = [&](uint32_t a, int ks) {
      const uint32_t b = lds32(sb + SM_GW + ks * 128 + lane * 4);
      gs = fmaf(__uint_as_float(a << 16), __uint_as_float(b << 16), gs);
      gs = fmaf(__uint_as_float(a & 0xffff0000u), __uint_as_float(b & 0xffff0000u), gs);
    };
    auto gate_step = [&](uint32_t dst, int ks) {
      const uint32_t a = lds32(dst + grow * 128 + (((lane >> 2) ^ (grow & 7)) << 4) + t * 4);
      if (ks < 3) { xh[0] = xh[1]; xh[1] = xh[2]; xh[2] = a; }
      else {
        if (ks == 3) { mbar_wait(bar + 8 * B_AUX, 0); gate_fma(xh[0], 0); gate_fma(xh[1], 1); gate_fma(xh[2], 2); }
        gate_fma(a, ks);
      }
      __syncwarp();
      mbar_arrive_if(ks == 9 && lane == 0, bar + 8 * B_ZERO);
    };
    auto tile = [&](auto BR) {
      constexpr int br = decltype(BR)::value;
      const int tl = c1 ^ br, k4 = tl & 3;
      const bool narrow = (k4 == 1 && wg == 3) || (k4 == 2 && wg == 0);
      const int a0 = 2 * ch + ((k4 == 2 && wg == 0) ? 1 : 0);
      if (!narrow) {
#pragma unroll 1
        for (int ks = 0; ks < 10; ks++) {
          const int it = br * 10 + ks, st = it & 3;
          mbar_wait(bar + 8 * (B_FULL + st), (it >> 2) & 1);
          TS_MARK(20 + it);
          const uint32_t dst = sb + st * P1_STB;
          const uint64_t da = mkdesc(dst + r * 8192, 16, 1024, 1), db = mkdesc(dst + 16384 + a0 * 8192, 8192, 1024, 1);
          WG_FENCE();
#pragma unroll
          for (int k = 0; k < 4; k++) wg128_ss(acc, da + k * 2, db + k * 128, (ks | k) != 0);
          WG_COMMIT();
          if (br == 0) gate_step(dst, ks);
          WG_WAIT(1);
          mbar_arrive_if(ks > 0 && wt == 0, bar + 8 * (B_EMPTY + ((it - 1) & 3)));
          duties(BR, it, ga_a, narrow_a);
        }
        WG_WAIT(0);
      } else {
#pragma unroll 1
        for (int ks = 0; ks < 10; ks++) {
          const int it = br * 10 + ks, st = it & 3;
          mbar_wait(bar + 8 * (B_FULL + st), (it >> 2) & 1);
          TS_MARK(20 + it);
          const uint32_t dst = sb + st * P1_STB;
          const uint64_t da = mkdesc(dst + r * 8192, 16, 1024, 1), db = mkdesc(dst + 16384 + a0 * 8192, 8192, 1024, 1);
          WG_FENCE();
#pragma unroll
          for (int k = 0; k < 4; k++) wg64_ss_of64(acc, da + k * 2, db + k * 128, (ks | k) != 0);
          WG_COMMIT();
          if (br == 0) gate_step(dst, ks);
          WG_WAIT(1);
          mbar_arrive_if(ks > 0 && wt == 0, bar + 8 * (B_EMPTY + ((it - 1) & 3)));
          duties(BR, it, ga_a, narrow_a);
        }
        WG_WAIT(0);
      }
      pin(acc);
      TS_MARK(2 + 2 * br);
      mbar_arrive_if(wt == 0, bar + 8 * (B_EMPTY + ((br * 10 + 9) & 3)));
      const int ga0 = tile_atom(tl) + a0;
      uint32_t m0 = 0, m1 = 0;
      if (br == 0) {
        const float sk0 = __uint_as_float(mufu0 ? (127u + 70u) << 23 : (127u - 69u) << 23);
        const float sk1 = __uint_as_float(mufu1 ? (127u + 70u) << 23 : (127u - 69u) << 23);
        pack_atom_a<0>(acc, pk, ga0, sk0, sk1, m0, m1);
        if (!narrow) pack_atom_a<1>(acc, pk, ga0 + 1, sk0, sk1, m0, m1);
        const uint32_t lim0 = (mufu0 ? 127u + 110u : 127u - 29u) << 7, lim1 = (mufu1 ? 127u + 110u : 127u - 29u) << 7;
        if ((m0 & 0x7fffu) >= lim0 || ((m0 >> 16) & 0x7fffu) >= lim0 || (m1 & 0x7fffu) >= lim1 || ((m1 >> 16) & 0x7fffu) >= lim1) { g_kbad = epoch; __threadfence(); }
      } else {
        pack_atom<0, 0>(acc, pk, 0.f, 0.f, m0, m1);
        pack_atom<0, 1>(acc, pk, 0.f, 0.f, m0, m1);
        if (ch) mbar_wait(bar + 8 * (B_EMPTY + 2), 0);
        const uint32_t stg = sb + (ch ? 2 * P1_STB : SM_X) + r * 16384;
        stage(stg, 0);
        stage(stg + 8192, 16);
        mbar_wait(bar + 8 * (B_KVFULL + 1), 0);
        sts16(sb + P1_STB + wg * 12288 + onepos, 0x3c00);
        PROXY_FENCE();
        mbar_arrive(bar + 8 * (B_READY + 1));
        bar_sync(1 + wg, 128);
        tma5d_store_if(wt == 0, &maps.qst, stg, (ga0 % 10) * 8, ga0 / 10, r, 16 + rb1);
        tma5d_store_if(wt == 32 * 0 && !narrow, &maps.qst, stg + 8192, ((ga0 + 1) % 10) * 8, (ga0 + 1) / 10, r, 16 + rb1);
        BULK_COMMIT();
      }
      TS_MARK(3 + 2 * br);
    };
    tile(Int<0>{});
    tile(Int<1>{});
  }

  if (odd ? t < 2 : t >= 2) {
    if (odd) { q[0][0] = 0; q[0][1] = 0; q[1][0] = 0; q[1][1] = 0; }
    else { q[0][4] = 0; q[0][5] = 0; q[1][4] = 0; q[1][5] = 0; }
  }
  {
    uint32_t m = 0;
#pragma unroll
    for (int i = 0; i < 6; i++) m = maxabs_bf16x2(m, maxabs_bf16x2(q[0][i], q[1][i]));
    bad = bad == (int)epoch || (m & 0x7fffu) >= ((127u - 50u) << 7) || ((m >> 16) & 0x7fffu) >= ((127u - 50u) << 7);
  }
#pragma unroll
  for (int i = 0; i < 4; i++) { qc[i] = t == 0 ? 0x1c801c80u : 0u; asm volatile("" : "+r"(qc[i])); }
  events = 0x01010110u | (0x2008000u >> (2 * wg)) | (wg == 0 ? 0x8000440u : wg == 1 ? 0x40000u : wg == 2 ? 0x20000000u : 0x420000u);
  mbar_wait(bar + 8 * (B_READY + 0), 0);
  }
  float o[2][12];
#pragma unroll
  for (int i = 0; i < 12; i++) { o[0][i] = 0.f; o[1][i] = 0.f; }
  {
    uint32_t dk0 = (uint32_t)mkdesc(sb, 1024, 0, 0), dk1 = (uint32_t)mkdesc(sb + 2048, SM_CONST - 2048, 0, 0), dv = (uint32_t)mkdesc(sb + 3072, 128, 0, 0);
    TS_MARK(6);
#pragma unroll 1
    for (int i = 0; i < 32; i++) {
      if ((events >> i) & 1) {
        if ((i & 3) == 0 || i == 27) {
          COORDS();
          const bool p = wt == 0;
          signal_bulk_if(p && i != 8 && (i != 24 || wg != 0), &g_cnt[i == 4 ? C_TB : i == 16 ? C_KV + h : C_OB + rb * 2 + (h >> 4)]);
          if (i == 4) mbar_arrive_if(p, bar + 8 * B_STG);
          if ((i & 7) == 0) {
            WG_WAIT(0);
            mbar_arrive_if(p, bar + 8 * (B_FREE - 1) + i);
            mbar_wait(bar + 8 * B_READY + i, 0);
          }
        } else if (i == 6 || i == 10 || i == 17 || i == 22 || i == 29) {
          COORDS();
          const bool p = lane == 0;
          if (i == 6) {
            mbar_wait(bar + 8 * B_STG, 0);
            if (w == 1) wait_count(&g_cnt[C_TB], epoch * 512);
            const uint32_t fb = bar + 8 * (w ? B_KB : B_KVFULL + 2);
            mbar_expect_if(p && w < 2, fb, P1_STB);
            tma5d_if(p && w < 2, sb + (2 + w) * P1_STB, &maps.qld, c0, 1, w ? 16 + qt * 4 : 8, fb);
          } else if (i == 29) {
            mbar_wait(bar + 8 * (B_FREE + 2), 0);
            mbar_wait(bar + 8 * B_B2, 0);
            p3_load_w(p && w < 3, w);
            wait_count(&g_cnt[C_OB + rb1 * 2 + kh], epoch * 16);
            p3_load_a(p && w < 3, w);
          } else {
            if (i != 22) {
              const int u = i == 17;
              const uint32_t fb = bar + 8 * (u ? B_KVFULL + 3 : B_QB);
              mbar_wait(bar + 8 * (B_FREE + u), 0);
              mbar_expect_if(wt == 0, fb, P1_STB);
              tma5d_if(wt == 0, sb + u * 3 * P1_STB, &maps.qld, c0, u, u ? 12 : 16 + qt * 4, fb);
            }
            if (i != 17) {
              const int u = i == 10 ? 2 : 3;
              mbar_wait(bar + 8 * (B_KVFULL + u), 0);
#pragma unroll
              for (int e = 0; e < 4; e++) sts16(sb + u * P1_STB + e * 12288 + onepos, 0x3c00);
              PROXY_FENCE();
              mbar_arrive(bar + 8 * (B_READY + u));
            }
          }
        } else if (i < 16) {
          WG_WAIT(0);
          COORDS();
          const uint64_t dw = mkdesc(sb + SM_WPHI, 384, 128, 0);
          TS_MARK(7);
          const uint32_t kb = sb + 3 * P1_STB + wg * 12288, ph = sb + SM_X + (wg & 1) * 10240;
          mbar_wait(bar + 8 * B_KB, 0);
          sts16(kb + onepos, 0x3f80);
          float p0[12], p1[12];
          phi_proj(p0, p1, kb, dw);
          if (wg < 2) mbar_wait(bar + 8 * (B_LINK + wg), 0);
          uint32_t phi[10];
          feature_map(phi, p0);
#pragma unroll
          for (int u = 0; u < 10; u++) sts32(ph + (u % 5) * 2048 + orow + (u / 5) * 128, phi[u]);
          feature_map(phi, p1);
#pragma unroll
          for (int u = 0; u < 10; u++) sts32(ph + (u % 5) * 2048 + orow + (u / 5) * 128 + 1024, phi[u]);
          PROXY_FENCE();
          bar_sync(1 + wg, 128);
          const uint64_t da = mkdesc(ph, 128, 2048, 0), db = mkdesc(kb + 3072, 128, 1024, 0);
          WG_FENCE();
#pragma unroll
          for (int kk = 0; kk < 8; kk++) {
            if (kk == 0) wg24_ss_bf16_tt_i(p0, da, db);
            else wg24_ss_bf16_tt(p0, da + kk * 16, db + (kk & 3) * 16 + (kk >> 2) * 384, 1);
          }
          WG_COMMIT();
          WG_WAIT(0);
          pin(p0);
          mbar_arrive_if(lane == 0 && wg >= 2, bar + 8 * (B_LINK + (wg & 1)));
          bar_sync(1 + wg, 128);
          const uint32_t ks = kb + ((w * 16 + g) * 24 + 2 * t) * 4;
#pragma unroll
          for (int j = 0; j < 3; j++) {
            if (w < 3) asm volatile("st.shared.v2.f32 [%0], {%1, %2};" ::"r"(ks + 32 * j), "f"(p0[4 * j]), "f"(p0[4 * j + 1]) : "memory");
            if (w < 2) asm volatile("st.shared.v2.f32 [%0], {%1, %2};" ::"r"(ks + 768 + 32 * j), "f"(p0[4 * j + 2]), "f"(p0[4 * j + 3]) : "memory");
          }
          PROXY_FENCE();
          bar_sync(1 + wg, 128);
          bulk_addf_if(wt == 0, g_kv + h * 960, kb, 3840);
          BULK_COMMIT();
          TS_MARK(8);
        } else if (i == 18) {
          COORDS();
          wait_count(&g_cnt[C_KV + h], epoch * 16);
          float v[8];
#pragma unroll
          for (int u = 0; u < 8; u++) v[u] = (u < 7 || wt < 64) ? __ldcg(&g_kv[h * 960 + u * 128 + wt]) : 0.f;
#pragma unroll
          for (int u = 0; u < 9; u++) {
            const int e = u * 128 + wt, f = e / 24, d = e % 24;
            sts16(sb + SM_KVB + (f >> 3) * 384 + d * 16 + (f & 7) * 2, u < 8 ? __bfloat16_as_ushort(__float2bfloat16(v[u < 8 ? u : 0])) : (uint16_t)0);
          }
          PROXY_FENCE();
          mbar_arrive(bar + 8 * B_KVB);
        } else {
          WG_WAIT(0);
          COORDS();
          const uint64_t dw = mkdesc(sb + SM_WPHI, 384, 128, 0);
          TS_MARK(9);
          float gt[4];
#pragma unroll
          for (int u = 0; u < 4; u++) gt[u] = 1.f - __ldcg(&g_gate[rb * 128 + (u >> 1) * 64 + w * 16 + g + (u & 1) * 8]);
          mbar_wait(bar + 8 * B_QB, 0);
          float p0[12], p1[12];
          phi_proj(p0, p1, sb + wg * 12288, dw);
          const uint64_t dkv = mkdesc(sb + SM_KVB, 384, 128, 0);
          auto readout = [&](float (&p)[12], float g0, float g1, uint32_t a) {
            uint32_t phi[10];
            feature_map(phi, p);
            WG_FENCE();
            wg24_rs_bf16_i(p, phi[0], phi[5], phi[1], phi[6], dkv);
            wg24_rs_bf16(p, phi[2], phi[7], phi[3], phi[8], dkv + 48, 1);
            wg24_rs_bf16(p, phi[4], phi[9], 0u, 0u, dkv + 96, 1);
            WG_COMMIT();
            WG_WAIT(0);
            pin(p);
            const float l0 = __shfl_sync(0xffffffffu, odd ? p[0] : p[8], lsrc), l1 = __shfl_sync(0xffffffffu, odd ? p[2] : p[10], lsrc);
            stage_o(p, __fdividef(g0, l0 + 1e-6f), __fdividef(g1, l1 + 1e-6f), a, v0, v2);
          };
          mbar_wait(bar + 8 * B_KVB, 0);
          readout(p0, gt[0], gt[1], ostg + orow);
          readout(p1, gt[2], gt[3], ostg + orow + 1024);
          PROXY_FENCE();
          bar_sync(1 + wg, 128);
          mbar_arrive_if(wt == 0, bar + 8 * B_B2);
          flush_o(wt == 0, g_o + rb * ORB + (80 + c0) * 2048, ostg, odd);
          TS_MARK(10);
        }
      }
      if (!(i & 3)) TS_MARK(40 + (i >> 2));
#pragma unroll
      for (int m = 0; m < 2; m++) {
        float s[32];
        uint32_t p[16];
        WG_FENCE();
        wg64_rs_bf16_i(s, q[m][0], q[m][1], q[m][2], q[m][3], desc_lohi(dk0, 8));
        wg64_rs_bf16(s, q[m][4], q[m][5], qc[2 * m], qc[2 * m + 1], desc_lohi(dk1, 8), 1);
        WG_COMMIT();
        WG_WAIT(0);
        constexpr int A = 2 * NMB, B = 16 - A;
#pragma unroll
        for (int j = 0; j < B; j++) {
          if ((j * A) % B < A) { const int a = j * A / B; p[a] = exp2_pair_mufu(s[2 * a], s[2 * a + 1]); }
          p[A + j] = exp2_pair(s[2 * (A + j)], s[2 * (A + j) + 1]);
        }
        WG_FENCE();
#pragma unroll
        for (int kk = 0; kk < 4; kk++) wg24_rs_f16_t(o[m], p[4 * kk], p[4 * kk + 1], p[4 * kk + 2], p[4 * kk + 3], desc_lohi(dv + kk * 16, 64), 1);
        WG_COMMIT();
      }
      dk0 += 384; dk1 += 384u - (384u << 16); dv += 384;
    }
  }
  {
    COORDS();
    float gt[4];
#pragma unroll
    for (int u = 0; u < 4; u++) gt[u] = __ldcg(&g_gate[rb * 128 + (u >> 1) * 64 + w * 16 + g + (u & 1) * 8]);
    WG_WAIT(0);
    pin(o[0]); pin(o[1]);
    TS_MARK(11);
    int big = 0;
#pragma unroll
    for (int m = 0; m < 2; m++) {
      const float l0 = __shfl_sync(0xffffffffu, odd ? o[m][0] : o[m][8], lsrc), l1 = __shfl_sync(0xffffffffu, odd ? o[m][2] : o[m][10], lsrc);
      const float r0 = rcp(l0), r1 = rcp(l1);
      float chk = 0.f, mx0 = 0.f, mx1 = 0.f;
#pragma unroll
      for (int i = 0; i < 12; i++) chk = fmaf(o[m][i], 0.f, chk);
#pragma unroll
      for (int i = 4; i < 6; i++) { mx0 = fmaxf(mx0, fabsf(o[m][i])); mx1 = fmaxf(mx1, fabsf(o[m][i + 2])); }
      bad |= !(chk == 0.f) || !(l0 >= 32.f) || !(l1 >= 32.f);
      big |= fmaxf(mx0 * r0, mx1 * r1) >= 1.220703125e-4f;
      stage_o(o[m], r0 * gt[2 * m], r1 * gt[2 * m + 1], ostg + orow + m * 1024, v0, v2);
    }
    PROXY_FENCE();
    const int anybad = __syncthreads_or(bad), anybig = __syncthreads_or(big);
    if (anybad || !anybig) attn_exact(x, wqkv, h, qt, sb + SM_X);
  }
  TS_MARK(12);

  COORDS();
  if (wg == 3) {
    flush_o(lane == 0, g_o + (qt * 4 + w) * ORB + c0 * 2048, sb + SM_X + w * 6144, odd);
    signal_bulk_if(lane == 0, &g_cnt[C_OA + (qt * 4 + w) * 2 + (h >> 4)]);
    if (wt == 0) atomicAdd(&g_cnt[C_EPOCH], 1);
  } else if (wg == 2) {
    const bool p = lane == 0;
    if (w == 3) { p3_load_w(p, 3); p3_load_a(p, 3); }
    mbar_wait(bar + 8 * (B_P3EMPTY + w), 0);
    p3_load_w(p, 4 + w);
    if (w > 0) wait_count(&g_cnt[C_OA + rb1 * 2 + kh], epoch * 16);
    p3_load_a(p, 4 + w);
    if (w < 2) {
      mbar_wait(bar + 8 * (B_P3EMPTY + w), 1);
      p3_load_w(p, 8 + w);
      if (w == 0) wait_count(&g_cnt[C_OA + rb1 * 2 + kh], epoch * 16);
      p3_load_a(p, 8 + w);
    }
  } else {
    float acc[96];
    const bool wide = (cg & 1) == wg;
    const int skip = (!wide && (cg & 1)) ? 1 : 0;
    if (wide) {
#pragma unroll 1
      for (int j = 0; j < 10; j++) {
        mbar_wait(bar + 8 * (B_P3FULL + (j & 3)), (j >> 2) & 1);
        if (j == 5) TS_MARK(13);
        const uint32_t dst = sb + (j & 3) * P3_STB;
        const uint64_t da = mkdesc(dst + wg * 1024, 2048, 128, 0), db = mkdesc(dst + 16384, 8192, 1024, 1);
        WG_FENCE();
#pragma unroll
        for (int k = 0; k < 4; k++) wg192_ss(acc, da + k * 256, db + k * 128, (j | k) != 0);
        WG_COMMIT();
        WG_WAIT(1);
        mbar_arrive_if(j > 0 && wt == 0, bar + 8 * (B_P3EMPTY + ((j - 1) & 3)));
      }
      WG_WAIT(0);
    } else {
#pragma unroll 1
      for (int j = 0; j < 10; j++) {
        mbar_wait(bar + 8 * (B_P3FULL + (j & 3)), (j >> 2) & 1);
        if (j == 5) TS_MARK(13);
        const uint32_t dst = sb + (j & 3) * P3_STB;
        const uint64_t da = mkdesc(dst + wg * 1024, 2048, 128, 0), db = mkdesc(dst + 16384 + skip * 8192, 8192, 1024, 1);
        WG_FENCE();
#pragma unroll
        for (int k = 0; k < 4; k++) wg128_ss_of96(acc, da + k * 256, db + k * 128, (j | k) != 0);
        WG_COMMIT();
        WG_WAIT(1);
        mbar_arrive_if(j > 0 && wt == 0, bar + 8 * (B_P3EMPTY + ((j - 1) & 3)));
      }
      WG_WAIT(0);
    }
    pin(acc);
    TS_MARK(14);
    if (!wide) mbar_wait(bar + 8 * (B_P3EMPTY + 2), 1);
    const uint32_t stg = sb + (wide ? 4 : 2) * P3_STB;
    const int r = w * 16 + (lane & 15);
#pragma unroll
    for (int i = 0; i < 24; i += 2)
      if (i < 16 || wide) {
        const int ch = (i & 7) + (lane >> 4);
        stsm4(stg + (i >> 3) * 8192 + r * 128 + ((ch ^ (r & 7)) << 4), pack_bf16(acc[4 * i], acc[4 * i + 1]), pack_bf16(acc[4 * i + 2], acc[4 * i + 3]),
              pack_bf16(acc[4 * i + 4], acc[4 * i + 5]), pack_bf16(acc[4 * i + 6], acc[4 * i + 7]));
      }
    PROXY_FENCE();
    bar_sync(1 + wg, 128);
    if (wt < (wide ? 3 : 2)) {
      PROXY_FENCE_G();
      asm volatile("cp.reduce.async.bulk.tensor.2d.global.shared::cta.add.bulk_group [%0, {%2, %3}], [%1];" ::"l"(&maps.out), "r"(stg + wt * 8192),
                   "r"((atom3 + skip + wt) * 64), "r"(rb1 * 128 + wg * 64) : "memory");
      asm volatile("cp.async.bulk.commit_group;" ::: "memory");
      asm volatile("cp.async.bulk.wait_group 0;" ::: "memory");
    }
    TS_MARK(15);
  }
  TS_DUMP();
}

typedef CUresult (*EncodeFn)(CUtensorMap*, CUtensorMapDataType, cuuint32_t, void*, const cuuint64_t*, const cuuint64_t*, const cuuint32_t*, const cuuint32_t*,
                             CUtensorMapInterleave, CUtensorMapSwizzle, CUtensorMapL2promotion, CUtensorMapFloatOOBfill);
void encode(EncodeFn enc, CUtensorMap* m, void* p, int rank, const cuuint64_t* gd, const cuuint64_t* gs, const cuuint32_t* bd) {
  const cuuint32_t es[3] = {1, 1, 1};
  enc(m, CU_TENSOR_MAP_DATA_TYPE_BFLOAT16, rank, p, gd, gs, bd, es, CU_TENSOR_MAP_INTERLEAVE_NONE, CU_TENSOR_MAP_SWIZZLE_128B,
      CU_TENSOR_MAP_L2_PROMOTION_L2_128B, CU_TENSOR_MAP_FLOAT_OOB_FILL_NONE);
}

}

extern "C" void kernel_launch(void* const* d_in, const int* in_sizes, int n_in, void* d_out, int out_size) {
  static EncodeFn enc = nullptr;
  if (!enc) {
    cudaDriverEntryPointQueryResult qr;
    cudaGetDriverEntryPoint("cuTensorMapEncodeTiled", (void**)&enc, cudaEnableDefault, &qr);
    cudaFuncSetAttribute(gated_mix_kernel, cudaFuncAttributeMaxDynamicSharedMemorySize, SMEM_BYTES);
  }
  Maps m;
  {
    const cuuint64_t gd[2] = {640, 2048}, gs[1] = {1280};
    const cuuint32_t bx[2] = {64, 128}, bo[2] = {64, 64};
    encode(enc, &m.x, d_in[0], 2, gd, gs, bx);
    encode(enc, &m.out, d_out, 2, gd, gs, bo);
  }
  for (int b = 0; b < 2; b++) {
    const cuuint64_t gd[3] = {64, 640, 30}, gs[2] = {3840, 128}, gd3[3] = {64, 640, 10}, gs3[2] = {1280, 128};
    const cuuint32_t bd[3] = {64, 64, 4}, bd3[3] = {64, 64, 3};
    encode(enc, &m.w[b], d_in[b ? 4 : 1], 3, gd, gs, bd);
    encode(enc, &m.wo[b], d_in[b ? 6 : 2], 3, gd3, gs3, bd3);
  }
  {
    void* qp = nullptr;
    cudaGetSymbolAddress(&qp, g_qkv);
    const cuuint64_t gd[5] = {128, 80, 3, 2, 32}, gs[4] = {2048, QTY, 1024, QRB};
    const cuuint32_t bl[5] = {128, 3, 2, 2, 4}, bs[5] = {128, 8, 1, 1, 1}, es[5] = {1, 1, 1, 1, 1};
    enc(&m.qld, CU_TENSOR_MAP_DATA_TYPE_UINT64, 5, qp, gd, gs, bl, es, CU_TENSOR_MAP_INTERLEAVE_NONE, CU_TENSOR_MAP_SWIZZLE_NONE, CU_TENSOR_MAP_L2_PROMOTION_L2_128B, CU_TENSOR_MAP_FLOAT_OOB_FILL_NONE);
    enc(&m.qst, CU_TENSOR_MAP_DATA_TYPE_UINT64, 5, qp, gd, gs, bs, es, CU_TENSOR_MAP_INTERLEAVE_NONE, CU_TENSOR_MAP_SWIZZLE_NONE, CU_TENSOR_MAP_L2_PROMOTION_NONE, CU_TENSOR_MAP_FLOAT_OOB_FILL_NONE);
  }
  gated_mix_kernel<<<128, 512, SMEM_BYTES, cudaStreamPerThread>>>(m, (const __nv_bfloat16*)d_in[0], (const __nv_bfloat16*)d_in[1], (const __nv_bfloat16*)d_in[5],
                                                                 (const __nv_bfloat16*)d_in[7], d_in[4], d_in[2], d_in[6], (uint4*)d_out);
}
```

```cpp
#include <cuda_runtime.h>
#include <cuda.h>
#include <cuda_bf16.h>
#include <cuda_fp16.h>
#include <stdint.h>
#pragma nv_diag_suppress 550

namespace {

constexpr int QRB = 240 * 2048;
constexpr int QBR = 16 * QRB;
constexpr int QTY = 80 * 2048;
constexpr int ORB = 160 * 2048;
constexpr int NMB = 3;

__device__ __align__(1024) uint8_t g_qkv[2 * QBR];
__device__ __align__(1024) uint8_t g_o[16 * ORB];
__device__ float g_gate[2048];
__device__ __align__(16) float g_kv[32 * 960];
__device__ uint32_t g_kbad;
__device__ uint32_t g_fb[128 * 2048 * 20];
__device__ uint32_t g_cnt[192];
constexpr int C_EPOCH = 0, C_TA = 32, C_TB = 64, C_KV = 96, C_OB = 128, C_OA = 160;

#define TS_MARK(i)
#define TS_INIT()
#define TS_REG(x)
#define TS_PUT(i, x, th)
#define TS_FIRST()
#define TS_DUMP()

__device__ __forceinline__ uint64_t mkdesc(uint32_t addr, uint32_t lbo, uint32_t sbo, int mode) {
  return (uint64_t)((addr & 0x3FFFF) >> 4) | ((uint64_t)(lbo >> 4) << 16) | ((uint64_t)(sbo >> 4) << 32) | ((uint64_t)mode << 62);
}
__device__ __forceinline__ uint64_t desc_lohi(uint32_t lo, uint32_t hi) { return ((uint64_t)hi << 32) | lo; }
#define WG_FENCE() asm volatile("wgmma.fence.sync.aligned;" ::: "memory")
#define WG_COMMIT() asm volatile("wgmma.commit_group.sync.aligned;" ::: "memory")
#define WG_WAIT(n) asm volatile("wgmma.wait_group.sync.aligned %0;" ::"n"(n) : "memory")
#define PROXY_FENCE() asm volatile("fence.proxy.async.shared::cta;" ::: "memory")
#define PROXY_FENCE_G() asm volatile("fence.proxy.async.global;" ::: "memory")
__device__ __forceinline__ void bar_sync(int id, int n) { asm volatile("bar.sync %0, %1;" ::"r"(id), "r"(n) : "memory"); }
__device__ __forceinline__ void mbar_init(uint32_t a, int c) { asm volatile("mbarrier.init.shared::cta.b64 [%0], %1;" ::"r"(a), "r"(c)); }
__device__ __forceinline__ uint32_t mbar_try(uint32_t a, int par) {
  uint32_t ok;
  asm volatile("{.reg .pred p; mbarrier.try_wait.parity.shared::cta.b64 p, [%1], %2; selp.b32 %0, 1, 0, p;}" : "=r"(ok) : "r"(a), "r"(par) : "memory");
  return ok;
}
__device__ __forceinline__ void mbar_wait(uint32_t a, int par) {
  for (int i = 0; !mbar_try(a, par); i++)
    if (i > (1 << 22)) break;
}
__device__ __forceinline__ void mbar_arrive(uint32_t a) { asm volatile("mbarrier.arrive.shared::cta.b64 _, [%0];" ::"r"(a) : "memory"); }
__device__ __forceinline__ void mbar_arrive_if(bool p, uint32_t a) {
  asm volatile("{.reg .pred p; setp.ne.b32 p, %0, 0; @p mbarrier.arrive.shared::cta.b64 _, [%1];}" ::"r"((int)p), "r"(a) : "memory");
}
__device__ __forceinline__ void mbar_expect_if(bool p, uint32_t a, int bytes) {
  asm volatile("{.reg .pred p; setp.ne.b32 p, %0, 0; @p mbarrier.arrive.expect_tx.shared::cta.b64 _, [%1], %2;}" ::"r"((int)p), "r"(a), "r"(bytes) : "memory");
}
__device__ __forceinline__ void tma2d_if(bool p, uint32_t dst, const CUtensorMap* m, int c0, int c1, uint32_t bar) {
  asm volatile("{.reg .pred p; setp.ne.b32 p, %0, 0; @p cp.async.bulk.tensor.2d.shared::cluster.global.mbarrier::complete_tx::bytes [%1], [%2, {%4, %5}], [%3];}"
               ::"r"((int)p), "r"(dst), "l"(m), "r"(bar), "r"(c0), "r"(c1) : "memory");
}
__device__ __forceinline__ void tma3d_if(bool p, uint32_t dst, const CUtensorMap* m, int c1, int c2, uint32_t bar) {
  asm volatile("{.reg .pred p; setp.ne.b32 p, %0, 0; @p cp.async.bulk.tensor.3d.shared::cluster.global.mbarrier::complete_tx::bytes [%1], [%2, {%6, %4, %5}], [%3];}"
               ::"r"((int)p), "r"(dst), "l"(m), "r"(bar), "r"(c1), "r"(c2), "r"(0) : "memory");
}
__device__ __forceinline__ void bulk_g2s_if(bool p, uint32_t dst, const void* src, int bytes, uint32_t bar) {
  asm volatile("{.reg .pred p; setp.ne.b32 p, %0, 0; @p cp.async.bulk.shared::cluster.global.mbarrier::complete_tx::bytes [%1], [%2], %3, [%4];}"
               ::"r"((int)p), "r"(dst), "l"(src), "r"(bytes), "r"(bar) : "memory");
}
__device__ __forceinline__ void tma5d_if(bool p, uint32_t dst, const CUtensorMap* m, int c1, int c2, int c4, uint32_t bar) {
  asm volatile("{.reg .pred p; setp.ne.b32 p, %0, 0; @p cp.async.bulk.tensor.5d.shared::cluster.global.mbarrier::complete_tx::bytes [%1], [%2, {%7, %4, %5, %7, %6}], [%3];}"
               ::"r"((int)p), "r"(dst), "l"(m), "r"(bar), "r"(c1), "r"(c2), "r"(c4), "r"(0) : "memory");
}
__device__ __forceinline__ void tma5d_store_if(bool p, const CUtensorMap* m, uint32_t src, int c1, int c2, int c3, int c4) {
  asm volatile("{.reg .pred p; setp.ne.b32 p, %0, 0; @p cp.async.bulk.tensor.5d.global.shared::cta.bulk_group [%1, {%7, %3, %4, %5, %6}], [%2];}"
               ::"r"((int)p), "l"(m), "r"(src), "r"(c1), "r"(c2), "r"(c3), "r"(c4), "r"(0) : "memory");
}
__device__ __forceinline__ void bulk_s2g_if(bool p, void* dst, uint32_t src, int bytes) {
  asm volatile("{.reg .pred p; setp.ne.b32 p, %0, 0; @p cp.async.bulk.global.shared::cta.bulk_group [%1], [%2], %3;}" ::"r"((int)p), "l"(dst), "r"(src), "r"(bytes) : "memory");
}
__device__ __forceinline__ void bulk_or_if(bool p, void* dst, uint32_t src, int bytes) {
  asm volatile("{.reg .pred p; setp.ne.b32 p, %0, 0; @p cp.reduce.async.bulk.global.shared::cta.bulk_group.or.b32 [%1], [%2], %3;}" ::"r"((int)p), "l"(dst), "r"(src), "r"(bytes) : "memory");
}
__device__ __forceinline__ void bulk_addf_if(bool p, void* dst, uint32_t src, int bytes) {
  asm volatile("{.reg .pred p; setp.ne.b32 p, %0, 0; @p cp.reduce.async.bulk.global.shared::cta.bulk_group.add.f32 [%1], [%2], %3;}" ::"r"((int)p), "l"(dst), "r"(src), "r"(bytes) : "memory");
}
#define BULK_COMMIT() asm volatile("cp.async.bulk.commit_group;" ::: "memory")
#define BULK_WAIT() asm volatile("cp.async.bulk.wait_group 0;" ::: "memory")
#define BULK_WAIT_READ() asm volatile("cp.async.bulk.wait_group.read 0;" ::: "memory")
__device__ __forceinline__ void signal_bulk_if(bool p, uint32_t* c) {
  asm volatile("{.reg .pred p; setp.ne.b32 p, %0, 0; cp.async.bulk.wait_group 0; @p red.relaxed.gpu.global.add.u32 [%1], 1;}" ::"r"((int)p), "l"(c) : "memory");
}
__device__ __forceinline__ void wait_count(const uint32_t* c, uint32_t target) {
  for (int i = 0;; i++) {
    uint32_t v;
    asm volatile("ld.relaxed.gpu.global.u32 %0, [%1];" : "=r"(v) : "l"(c) : "memory");
    if ((int)(v - target) >= 0) break;
    if (i > (1 << 20)) break;
  }
  PROXY_FENCE_G();
}
__device__ __forceinline__ uint32_t pack_bf16(float lo, float hi) { uint32_t r; asm("cvt.rn.bf16x2.f32 %0, %1, %2;" : "=r"(r) : "f"(hi), "f"(lo)); return r; }
__device__ __forceinline__ uint32_t pack_f16(float lo, float hi) { uint32_t r; asm("cvt.rn.f16x2.f32 %0, %1, %2;" : "=r"(r) : "f"(hi), "f"(lo)); return r; }
__device__ __forceinline__ float ex2(float a) { float r; asm("ex2.approx.ftz.f32 %0, %1;" : "=f"(r) : "f"(a)); return r; }
__device__ __forceinline__ float ex2n(float a) { float r; asm("{.reg .f32 t; neg.ftz.f32 t, %1; ex2.approx.ftz.f32 %0, t;}" : "=f"(r) : "f"(a)); return r; }
__device__ __forceinline__ float rcp(float a) { float r; asm("rcp.approx.ftz.f32 %0, %1;" : "=f"(r) : "f"(a)); return r; }
__device__ __forceinline__ uint32_t maxabs_bf16x2(uint32_t a, uint32_t b) { uint32_t r; asm("max.NaN.xorsign.abs.bf16x2 %0, %1, %2;" : "=r"(r) : "r"(a), "r"(b)); return r; }
__device__ __forceinline__ uint32_t ldg32(const void* p) { return __ldg(reinterpret_cast<const uint32_t*>(p)); }
__device__ __forceinline__ uint32_t ldcg32(const void* p) { uint32_t v; asm volatile("ld.global.cg.u32 %0, [%1];" : "=r"(v) : "l"(p) : "memory"); return v; }
__device__ __forceinline__ uint32_t lds32(uint32_t a) { uint32_t v; asm volatile("ld.shared.b32 %0, [%1];" : "=r"(v) : "r"(a) : "memory"); return v; }
__device__ __forceinline__ void sts32(uint32_t a, uint32_t v) { asm volatile("st.shared.b32 [%0], %1;" ::"r"(a), "r"(v) : "memory"); }
__device__ __forceinline__ void sts16(uint32_t a, uint16_t v) { asm volatile("st.shared.b16 [%0], %1;" ::"r"(a), "h"(v) : "memory"); }
__device__ __forceinline__ void stsm4(uint32_t a, uint32_t r0, uint32_t r1, uint32_t r2, uint32_t r3) {
  asm volatile("stmatrix.sync.aligned.m8n8.x4.shared.b16 [%0], {%1, %2, %3, %4};" ::"r"(a), "r"(r0), "r"(r1), "r"(r2), "r"(r3) : "memory");
}
template <int N> __device__ __forceinline__ void pin(float (&d)[N]) {
#pragma unroll
  for (int i = 0; i < N; i++) asm volatile("" : "+f"(d[i])::"memory");
}

__device__ __forceinline__ void wg128_ss(float (&d)[64], uint64_t da, uint64_t db, int scale_d) {
  asm volatile("{\n.reg .pred p;\nsetp.ne.b32 p, %66, 0;\n"
    "wgmma.mma_async.sync.aligned.m64n128k16.f32.bf16.bf16 "
    "{%0, %1, %2, %3, %4, %5, %6, %7, %8, %9, %10, %11, %12, %13, %14, %15,"
    "%16, %17, %18, %19, %20, %21, %22, %23, %24, %25, %26, %27, %28, %29, %30, %31,"
    "%32, %33, %34, %35, %36, %37, %38, %39, %40, %41, %42, %43, %44, %45, %46, %47,"
    "%48, %49, %50, %51, %52, %53, %54, %55, %56, %57, %58, %59, %60, %61, %62, %63}, "
    "%64, %65, p, 1, 1, 0, 1;\n}\n"
    : "+f"(d[0]), "+f"(d[1]), "+f"(d[2]), "+f"(d[3]), "+f"(d[4]), "+f"(d[5]), "+f"(d[6]), "+f"(d[7]),
      "+f"(d[8]), "+f"(d[9]), "+f"(d[10]), "+f"(d[11]), "+f"(d[12]), "+f"(d[13]), "+f"(d[14]), "+f"(d[15]),
      "+f"(d[16]), "+f"(d[17]), "+f"(d[18]), "+f"(d[19]), "+f"(d[20]), "+f"(d[21]), "+f"(d[22]), "+f"(d[23]),
      "+f"(d[24]), "+f"(d[25]), "+f"(d[26]), "+f"(d[27]), "+f"(d[28]), "+f"(d[29]), "+f"(d[30]), "+f"(d[31]),
      "+f"(d[32]), "+f"(d[33]), "+f"(d[34]), "+f"(d[35]), "+f"(d[36]), "+f"(d[37]), "+f"(d[38]), "+f"(d[39]),
      "+f"(d[40]), "+f"(d[41]), "+f"(d[42]), "+f"(d[43]), "+f"(d[44]), "+f"(d[45]), "+f"(d[46]), "+f"(d[47]),
      "+f"(d[48]), "+f"(d[49]), "+f"(d[50]), "+f"(d[51]), "+f"(d[52]), "+f"(d[53]), "+f"(d[54]), "+f"(d[55]),
      "+f"(d[56]), "+f"(d[57]), "+f"(d[58]), "+f"(d[59]), "+f"(d[60]), "+f"(d[61]), "+f"(d[62]), "+f"(d[63])
    : "l"(da), "l"(db), "r"(scale_d));
}

__device__ __forceinline__ void wg64_ss_of64(float (&d)[64], uint64_t da, uint64_t db, int scale_d) {
  asm volatile("{\n.reg .pred p;\nsetp.ne.b32 p, %34, 0;\n"
    "wgmma.mma_async.sync.aligned.m64n64k16.f32.bf16.bf16 "
    "{%0, %1, %2, %3, %4, %5, %6, %7, %8, %9, %10, %11, %12, %13, %14, %15,"
    "%16, %17, %18, %19, %20, %21, %22, %23, %24, %25, %26, %27, %28, %29, %30, %31}, "
    "%32, %33, p, 1, 1, 0, 1;\n}\n"
    : "+f"(d[0]), "+f"(d[1]), "+f"(d[2]), "+f"(d[3]), "+f"(d[4]), "+f"(d[5]), "+f"(d[6]), "+f"(d[7]),
      "+f"(d[8]), "+f"(d[9]), "+f"(d[10]), "+f"(d[11]), "+f"(d[12]), "+f"(d[13]), "+f"(d[14]), "+f"(d[15]),
      "+f"(d[16]), "+f"(d[17]), "+f"(d[18]), "+f"(d[19]), "+f"(d[20]), "+f"(d[21]), "+f"(d[22]), "+f"(d[23]),
      "+f"(d[24]), "+f"(d[25]), "+f"(d[26]), "+f"(d[27]), "+f"(d[28]), "+f"(d[29]), "+f"(d[30]), "+f"(d[31])
    : "l"(da), "l"(db), "r"(scale_d));
}

__device__ __forceinline__ void wg192_ss(float (&d)[96], uint64_t da, uint64_t db, int scale_d) {
  asm volatile("{\n.reg .pred p;\nsetp.ne.b32 p, %98, 0;\n"
    "wgmma.mma_async.sync.aligned.m64n192k16.f32.bf16.bf16 "
    "{%0, %1, %2, %3, %4, %5, %6, %7, %8, %9, %10, %11, %12, %13, %14, %15,"
    "%16, %17, %18, %19, %20, %21, %22, %23, %24, %25, %26, %27, %28, %29, %30, %31,"
    "%32, %33, %34, %35, %36, %37, %38, %39, %40, %41, %42, %43, %44, %45, %46, %47,"
    "%48, %49, %50, %51, %52, %53, %54, %55, %56, %57, %58, %59, %60, %61, %62, %63,"
    "%64, %65, %66, %67, %68, %69, %70, %71, %72, %73, %74, %75, %76, %77, %78, %79,"
    "%80, %81, %82, %83, %84, %85, %86, %87, %88, %89, %90, %91, %92, %93, %94, %95}, "
    "%96, %97, p, 1, 1, 0, 1;\n}\n"
    : "+f"(d[0]), "+f"(d[1]), "+f"(d[2]), "+f"(d[3]), "+f"(d[4]), "+f"(d[5]), "+f"(d[6]), "+f"(d[7]),
      "+f"(d[8]), "+f"(d[9]), "+f"(d[10]), "+f"(d[11]), "+f"(d[12]), "+f"(d[13]), "+f"(d[14]), "+f"(d[15]),
      "+f"(d[16]), "+f"(d[17]), "+f"(d[18]), "+f"(d[19]), "+f"(d[20]), "+f"(d[21]), "+f"(d[22]), "+f"(d[23]),
      "+f"(d[24]), "+f"(d[25]), "+f"(d[26]), "+f"(d[27]), "+f"(d[28]), "+f"(d[29]), "+f"(d[30]), "+f"(d[31]),
      "+f"(d[32]), "+f"(d[33]), "+f"(d[34]), "+f"(d[35]), "+f"(d[36]), "+f"(d[37]), "+f"(d[38]), "+f"(d[39]),
      "+f"(d[40]), "+f"(d[41]), "+f"(d[42]), "+f"(d[43]), "+f"(d[44]), "+f"(d[45]), "+f"(d[46]), "+f"(d[47]),
      "+f"(d[48]), "+f"(d[49]), "+f"(d[50]), "+f"(d[51]), "+f"(d[52]), "+f"(d[53]), "+f"(d[54]), "+f"(d[55]),
      "+f"(d[56]), "+f"(d[57]), "+f"(d[58]), "+f"(d[59]), "+f"(d[60]), "+f"(d[61]), "+f"(d[62]), "+f"(d[63]),
      "+f"(d[64]), "+f"(d[65]), "+f"(d[66]), "+f"(d[67]), "+f"(d[68]), "+f"(d[69]), "+f"(d[70]), "+f"(d[71]),
      "+f"(d[72]), "+f"(d[73]), "+f"(d[74]), "+f"(d[75]), "+f"(d[76]), "+f"(d[77]), "+f"(d[78]), "+f"(d[79]),
      "+f"(d[80]), "+f"(d[81]), "+f"(d[82]), "+f"(d[83]), "+f"(d[84]), "+f"(d[85]), "+f"(d[86]), "+f"(d[87]),
      "+f"(d[88]), "+f"(d[89]), "+f"(d[90]), "+f"(d[91]), "+f"(d[92]), "+f"(d[93]), "+f"(d[94]), "+f"(d[95])
    : "l"(da), "l"(db), "r"(scale_d));
}

__device__ __forceinline__ void wg128_ss_of96(float (&d)[96], uint64_t da, uint64_t db, int scale_d) {
  asm volatile("{\n.reg .pred p;\nsetp.ne.b32 p, %66, 0;\n"
    "wgmma.mma_async.sync.aligned.m64n128k16.f32.bf16.bf16 "
    "{%0, %1, %2, %3, %4, %5, %6, %7, %8, %9, %10, %11, %12, %13, %14, %15,"
    "%16, %17, %18, %19, %20, %21, %22, %23, %24, %25, %26, %27, %28, %29, %30, %31,"
    "%32, %33, %34, %35, %36, %37, %38, %39, %40, %41, %42, %43, %44, %45, %46, %47,"
    "%48, %49, %50, %51, %52, %53, %54, %55, %56, %57, %58, %59, %60, %61, %62, %63}, "
    "%64, %65, p, 1, 1, 0, 1;\n}\n"
    : "+f"(d[0]), "+f"(d[1]), "+f"(d[2]), "+f"(d[3]), "+f"(d[4]), "+f"(d[5]), "+f"(d[6]), "+f"(d[7]),
      "+f"(d[8]), "+f"(d[9]), "+f"(d[10]), "+f"(d[11]), "+f"(d[12]), "+f"(d[13]), "+f"(d[14]), "+f"(d[15]),
      "+f"(d[16]), "+f"(d[17]), "+f"(d[18]), "+f"(d[19]), "+f"(d[20]), "+f"(d[21]), "+f"(d[22]), "+f"(d[23]),
      "+f"(d[24]), "+f"(d[25]), "+f"(d[26]), "+f"(d[27]), "+f"(d[28]), "+f"(d[29]), "+f"(d[30]), "+f"(d[31]),
      "+f"(d[32]), "+f"(d[33]), "+f"(d[34]), "+f"(d[35]), "+f"(d[36]), "+f"(d[37]), "+f"(d[38]), "+f"(d[39]),
      "+f"(d[40]), "+f"(d[41]), "+f"(d[42]), "+f"(d[43]), "+f"(d[44]), "+f"(d[45]), "+f"(d[46]), "+f"(d[47]),
      "+f"(d[48]), "+f"(d[49]), "+f"(d[50]), "+f"(d[51]), "+f"(d[52]), "+f"(d[53]), "+f"(d[54]), "+f"(d[55]),
      "+f"(d[56]), "+f"(d[57]), "+f"(d[58]), "+f"(d[59]), "+f"(d[60]), "+f"(d[61]), "+f"(d[62]), "+f"(d[63])
    : "l"(da), "l"(db), "r"(scale_d));
}

__device__ __forceinline__ void wg64_rs_bf16(float (&d)[32], uint32_t a0, uint32_t a1, uint32_t a2, uint32_t a3, uint64_t db, int scale_d) {
  asm volatile("{\n.reg .pred p;\nsetp.ne.b32 p, %37, 0;\n"
    "wgmma.mma_async.sync.aligned.m64n64k16.f32.bf16.bf16 "
    "{%0, %1, %2, %3, %4, %5, %6, %7, %8, %9, %10, %11, %12, %13, %14, %15,"
    "%16, %17, %18, %19, %20, %21, %22, %23, %24, %25, %26, %27, %28, %29, %30, %31}, "
    "{%32, %33, %34, %35}, %36, p, 1, 1, 0;\n}\n"
    : "+f"(d[0]), "+f"(d[1]), "+f"(d[2]), "+f"(d[3]), "+f"(d[4]), "+f"(d[5]), "+f"(d[6]), "+f"(d[7]),
      "+f"(d[8]), "+f"(d[9]), "+f"(d[10]), "+f"(d[11]), "+f"(d[12]), "+f"(d[13]), "+f"(d[14]), "+f"(d[15]),
      "+f"(d[16]), "+f"(d[17]), "+f"(d[18]), "+f"(d[19]), "+f"(d[20]), "+f"(d[21]), "+f"(d[22]), "+f"(d[23]),
      "+f"(d[24]), "+f"(d[25]), "+f"(d[26]), "+f"(d[27]), "+f"(d[28]), "+f"(d[29]), "+f"(d[30]), "+f"(d[31])
    : "r"(a0), "r"(a1), "r"(a2), "r"(a3), "l"(db), "r"(scale_d));
}

__device__ __forceinline__ void wg24_rs_f16_t(float (&d)[12], uint32_t a0, uint32_t a1, uint32_t a2, uint32_t a3, uint64_t db, int scale_d) {
  asm volatile("{\n.reg .pred p;\nsetp.ne.b32 p, %17, 0;\n"
    "wgmma.mma_async.sync.aligned.m64n24k16.f32.f16.f16 "
    "{%0, %1, %2, %3, %4, %5, %6, %7, %8, %9, %10, %11}, "
    "{%12, %13, %14, %15}, %16, p, 1, 1, 1;\n}\n"
    : "+f"(d[0]), "+f"(d[1]), "+f"(d[2]), "+f"(d[3]), "+f"(d[4]), "+f"(d[5]), "+f"(d[6]), "+f"(d[7]),
      "+f"(d[8]), "+f"(d[9]), "+f"(d[10]), "+f"(d[11])
    : "r"(a0), "r"(a1), "r"(a2), "r"(a3), "l"(db), "r"(scale_d));
}

__device__ __forceinline__ void wg24_rs_bf16(float (&d)[12], uint32_t a0, uint32_t a1, uint32_t a2, uint32_t a3, uint64_t db, int scale_d) {
  asm volatile("{\n.reg .pred p;\nsetp.ne.b32 p, %17, 0;\n"
    "wgmma.mma_async.sync.aligned.m64n24k16.f32.bf16.bf16 "
    "{%0, %1, %2, %3, %4, %5, %6, %7, %8, %9, %10, %11}, "
    "{%12, %13, %14, %15}, %16, p, 1, 1, 0;\n}\n"
    : "+f"(d[0]), "+f"(d[1]), "+f"(d[2]), "+f"(d[3]), "+f"(d[4]), "+f"(d[5]), "+f"(d[6]), "+f"(d[7]),
      "+f"(d[8]), "+f"(d[9]), "+f"(d[10]), "+f"(d[11])
    : "r"(a0), "r"(a1), "r"(a2), "r"(a3), "l"(db), "r"(scale_d));
}

__device__ __forceinline__ void wg24_ss_bf16_tt(float (&d)[12], uint64_t da, uint64_t db, int scale_d) {
  asm volatile("{\n.reg .pred p;\nsetp.ne.b32 p, %14, 0;\n"
    "wgmma.mma_async.sync.aligned.m64n24k16.f32.bf16.bf16 "
    "{%0, %1, %2, %3, %4, %5, %6, %7, %8, %9, %10, %11}, "
    "%12, %13, p, 1, 1, 1, 1;\n}\n"
    : "+f"(d[0]), "+f"(d[1]), "+f"(d[2]), "+f"(d[3]), "+f"(d[4]), "+f"(d[5]), "+f"(d[6]), "+f"(d[7]),
      "+f"(d[8]), "+f"(d[9]), "+f"(d[10]), "+f"(d[11])
    : "l"(da), "l"(db), "r"(scale_d));
}

__device__ __forceinline__ void wg64_rs_bf16_i(float (&d)[32], uint32_t a0, uint32_t a1, uint32_t a2, uint32_t a3, uint64_t db) {
  asm volatile("{\n.reg .pred p;\nsetp.ne.b32 p, 0, 0;\n"
    "wgmma.mma_async.sync.aligned.m64n64k16.f32.bf16.bf16 "
    "{%0, %1, %2, %3, %4, %5, %6, %7, %8, %9, %10, %11, %12, %13, %14, %15,"
    "%16, %17, %18, %19, %20, %21, %22, %23, %24, %25, %26, %27, %28, %29, %30, %31}, "
    "{%32, %33, %34, %35}, %36, p, 1, 1, 0;\n}\n"
    : "=f"(d[0]), "=f"(d[1]), "=f"(d[2]), "=f"(d[3]), "=f"(d[4]), "=f"(d[5]), "=f"(d[6]), "=f"(d[7]),
      "=f"(d[8]), "=f"(d[9]), "=f"(d[10]), "=f"(d[11]), "=f"(d[12]), "=f"(d[13]), "=f"(d[14]), "=f"(d[15]),
      "=f"(d[16]), "=f"(d[17]), "=f"(d[18]), "=f"(d[19]), "=f"(d[20]), "=f"(d[21]), "=f"(d[22]), "=f"(d[23]),
      "=f"(d[24]), "=f"(d[25]), "=f"(d[26]), "=f"(d[27]), "=f"(d[28]), "=f"(d[29]), "=f"(d[30]), "=f"(d[31])
    : "r"(a0), "r"(a1), "r"(a2), "r"(a3), "l"(db));
}

__device__ __forceinline__ void wg24_rs_bf16_i(float (&d)[12], uint32_t a0, uint32_t a1, uint32_t a2, uint32_t a3, uint64_t db) {
  asm volatile("{\n.reg .pred p;\nsetp.ne.b32 p, 0, 0;\n"
    "wgmma.mma_async.sync.aligned.m64n24k16.f32.bf16.bf16 "
    "{%0, %1, %2, %3, %4, %5, %6, %7, %8, %9, %10, %11}, "
    "{%12, %13, %14, %15}, %16, p, 1, 1, 0;\n}\n"
    : "=f"(d[0]), "=f"(d[1]), "=f"(d[2]), "=f"(d[3]), "=f"(d[4]), "=f"(d[5]), "=f"(d[6]), "=f"(d[7]),
      "=f"(d[8]), "=f"(d[9]), "=f"(d[10]), "=f"(d[11])
    : "r"(a0), "r"(a1), "r"(a2), "r"(a3), "l"(db));
}

__device__ __forceinline__ void wg24_ss_bf16_tt_i(float (&d)[12], uint64_t da, uint64_t db) {
  asm volatile("{\n.reg .pred p;\nsetp.ne.b32 p, 0, 0;\n"
    "wgmma.mma_async.sync.aligned.m64n24k16.f32.bf16.bf16 "
    "{%0, %1, %2, %3, %4, %5, %6, %7, %8, %9, %10, %11}, "
    "%12, %13, p, 1, 1, 1, 1;\n}\n"
    : "=f"(d[0]), "=f"(d[1]), "=f"(d[2]), "=f"(d[3]), "=f"(d[4]), "=f"(d[5]), "=f"(d[6]), "=f"(d[7]),
      "=f"(d[8]), "=f"(d[9]), "=f"(d[10]), "=f"(d[11])
    : "l"(da), "l"(db));
}

__device__ __forceinline__ void wg24_ss_bf16(float (&d)[12], uint64_t da, uint64_t db, int scale_d) {
  asm volatile("{\n.reg .pred p;\nsetp.ne.b32 p, %14, 0;\n"
    "wgmma.mma_async.sync.aligned.m64n24k16.f32.bf16.bf16 "
    "{%0, %1, %2, %3, %4, %5, %6, %7, %8, %9, %10, %11}, "
    "%12, %13, p, 1, 1, 0, 0;\n}\n"
    : "+f"(d[0]), "+f"(d[1]), "+f"(d[2]), "+f"(d[3]), "+f"(d[4]), "+f"(d[5]), "+f"(d[6]), "+f"(d[7]),
      "+f"(d[8]), "+f"(d[9]), "+f"(d[10]), "+f"(d[11])
    : "l"(da), "l"(db), "r"(scale_d));
}

__device__ __forceinline__ void wg24_ss_bf16_i(float (&d)[12], uint64_t da, uint64_t db) {
  asm volatile("{\n.reg .pred p;\nsetp.ne.b32 p, 0, 0;\n"
    "wgmma.mma_async.sync.aligned.m64n24k16.f32.bf16.bf16 "
    "{%0, %1, %2, %3, %4, %5, %6, %7, %8, %9, %10, %11}, "
    "%12, %13, p, 1, 1, 0, 0;\n}\n"
    : "=f"(d[0]), "=f"(d[1]), "=f"(d[2]), "=f"(d[3]), "=f"(d[4]), "=f"(d[5]), "=f"(d[6]), "=f"(d[7]),
      "=f"(d[8]), "=f"(d[9]), "=f"(d[10]), "=f"(d[11])
    : "l"(da), "l"(db));
}

constexpr int P1_STB = 49152, P3_STB = 40960;
constexpr int SM_X = 196608;
constexpr int SM_KVB = SM_X + 24576;
constexpr int SM_GW = SM_X + 8192, SM_WRAW = SM_GW + 1280, SM_EP = SM_WRAW + 800;
constexpr int SM_CONST = SM_X + 32768, SM_WPHI = SM_CONST + 1024, SM_BAR = SM_WPHI + 1536;
constexpr int SMEM_BYTES = SM_BAR + 512;
constexpr int B_FULL = 0, B_AUX = 4, B_KB = 5, B_QB = 6, B_KVFULL = 7, B_P3FULL = 11, B_P3EMPTY = 15, B_EMPTY = 19, B_LINK = 23, B_FREE = 25,
              B_STG = 28, B_B2 = 29, B_ZERO = 30, B_READY = 31, B_KVB = 35;

template <int V> struct Int { static constexpr int value = V; };
struct Maps { CUtensorMap x, w[2], wo[2], out, qld, qst; };

__device__ __forceinline__ int tile_atom(int t) { return (t >> 2) * 15 + ((0xB740 >> ((t & 3) * 4)) & 15); }

template <int MODE, int A>
__device__ __forceinline__ void pack_atom(const float (&acc)[64], uint32_t (&r)[32], float s0, float s1, uint32_t& m0, uint32_t& m1) {
#pragma unroll
  for (int e = A * 16; e < A * 16 + 16; e++) {
    const float s = (e & 1) ? s1 : s0;
    if (MODE == 0) r[e] = pack_bf16(acc[2 * e], acc[2 * e + 1]);
    else if (MODE == 3) r[e] = pack_f16(acc[2 * e], acc[2 * e + 1]);
    else r[e] = pack_bf16(acc[2 * e] * s, acc[2 * e + 1] * s);
    if (MODE == 2) { if (e & 1) m1 = maxabs_bf16x2(m1, r[e]); else m0 = maxabs_bf16x2(m0, r[e]); }
  }
}
template <int A>
__device__ __forceinline__ void pack_atom_a(const float (&acc)[64], uint32_t (&r)[32], int ga, float sk0, float sk1, uint32_t& m0, uint32_t& m1) {
  if (ga < 10) { const float cq = __uint_as_float(463809372u); pack_atom<1, A>(acc, r, cq, cq, m0, m1); }
  else if (ga < 20) pack_atom<2, A>(acc, r, sk0, sk1, m0, m1);
  else pack_atom<3, A>(acc, r, 0.f, 0.f, m0, m1);
}

__device__ __forceinline__ uint32_t exp2_pair(float a, float b) {
  uint32_t z, w, h;
  asm volatile("cvt.pack.sat.s16.s32 %0, %2, %1;" : "=r"(z) : "r"(__float_as_uint(a)), "r"(__float_as_uint(b)));
  asm volatile("lop3.b32 %0, %1, 0x03ff03ff, 0x34003400, 0xEA;" : "=r"(w) : "r"(z));
  asm volatile("fma.rn.f16x2 %0, %1, %1, %2;" : "=r"(h) : "r"(w), "r"(0x36203620));
  asm volatile("fma.rn.f16x2 %0, %0, %1, %2;" : "+r"(h) : "r"(w), "r"(0x2e012e01));
  return h + z - w;
}
__device__ __forceinline__ uint32_t exp2_pair_mufu(float a, float b) {
  float x, y; uint32_t r;
  asm volatile("ex2.approx.ftz.f32 %0, %1;" : "=f"(x) : "f"(a));
  asm volatile("ex2.approx.ftz.f32 %0, %1;" : "=f"(y) : "f"(b));
  asm volatile("cvt.rn.f16x2.f32 %0, %1, %2;" : "=r"(r) : "f"(y), "f"(x));
  return r;
}
__device__ __forceinline__ void load_frag(uint32_t (&a)[6], const uint8_t* p) {
  a[0] = ldcg32(p); a[1] = ldcg32(p + 128); a[2] = ldcg32(p + 2048); a[3] = ldcg32(p + 2048 + 128); a[4] = ldcg32(p + 4096); a[5] = ldcg32(p + 4096 + 128);
}
template <bool EXACT>
__device__ __forceinline__ bool feature_rows(uint32_t (&phi)[10], const float (&p)[12]) {
  const float L = 1.4426950408889634f;
  bool ok = true;
#pragma unroll
  for (int r = 0; r < 2; r++) {
    const float v[5] = {p[2 * r], p[2 * r + 1], p[4 + 2 * r], p[5 + 2 * r], p[8 + 2 * r]};
    float ep[5], en[5];
    if (EXACT) {
      float mx = fmaxf(fmaxf(fmaxf(v[0], v[1]), fmaxf(v[2], v[3])), v[4]);
      float mn = fminf(fminf(fminf(v[0], v[1]), fminf(v[2], v[3])), v[4]);
      mx = fmaxf(mx, __shfl_xor_sync(0xffffffffu, mx, 1)); mn = fminf(mn, __shfl_xor_sync(0xffffffffu, mn, 1));
      mx = fmaxf(mx, __shfl_xor_sync(0xffffffffu, mx, 2)); mn = fminf(mn, __shfl_xor_sync(0xffffffffu, mn, 2));
#pragma unroll
      for (int i = 0; i < 5; i++) { ep[i] = ex2((v[i] - mx) * L); en[i] = ex2((mn - v[i]) * L); }
    } else {
#pragma unroll
      for (int i = 0; i < 5; i++) { const float u = v[i] * L; ep[i] = ex2(u); en[i] = ex2n(u); }
    }
    float sp = (ep[0] + ep[1]) + (ep[2] + ep[3]) + ep[4], sn = (en[0] + en[1]) + (en[2] + en[3]) + en[4];
    sp += __shfl_xor_sync(0xffffffffu, sp, 1); sn += __shfl_xor_sync(0xffffffffu, sn, 1);
    sp += __shfl_xor_sync(0xffffffffu, sp, 2); sn += __shfl_xor_sync(0xffffffffu, sn, 2);
    ok = ok && sp + sn < 1.2676506e30f;
    const float rp = rcp(sp), rn = rcp(sn);
#pragma unroll
    for (int i = 0; i < 5; i++) phi[5 * r + i] = pack_bf16(ep[i] * rp, en[i] * rn);
  }
  return ok;
}
__device__ __forceinline__ void feature_map(uint32_t (&phi)[10], const float (&p)[12]) {
  if (!__all_sync(0xffffffffu, feature_rows<false>(phi, p))) feature_rows<true>(phi, p);
}
__device__ __forceinline__ void phi_proj(float (&p0)[12], float (&p1)[12], uint32_t a, uint64_t dw) {
  const uint64_t da = mkdesc(a, 1024, 128, 0), db = mkdesc(a + 2048, 0, 128, 0);
  WG_FENCE();
  wg24_ss_bf16_i(p0, da, dw);
  wg24_ss_bf16(p0, db, dw + 48, 1);
  wg24_ss_bf16_i(p1, da + 384, dw);
  wg24_ss_bf16(p1, db + 384, dw + 48, 1);
  WG_COMMIT();
  WG_WAIT(0);
  pin(p0); pin(p1);
}
__device__ __forceinline__ void stage_o(const float (&o)[12], float s0, float s1, uint32_t a, bool v0, bool v2) {
#pragma unroll
  for (int j = 0; j < 3; j++) {
    const bool v = j == 1 || (j == 0 ? v0 : v2);
    sts32(a + j * 2048, v ? pack_bf16(o[4 * j] * s0, o[4 * j + 1] * s0) : 0u);
    sts32(a + j * 2048 + 128, v ? pack_bf16(o[4 * j + 2] * s1, o[4 * j + 3] * s1) : 0u);
  }
}
__device__ __forceinline__ void flush_o(bool p, uint8_t* dst, uint32_t src, bool odd) {
  bulk_s2g_if(p, dst + (odd ? 2048 : 0), src + (odd ? 2048 : 0), 4096);
  bulk_or_if(p, dst + (odd ? 0 : 4096), src + (odd ? 0 : 4096), 2048);
  BULK_COMMIT();
}

__device__ __forceinline__ void proj20(float (&acc)[20], const __nv_bfloat16* __restrict__ xr, const __nv_bfloat16* __restrict__ wc) {
#pragma unroll
  for (int d = 0; d < 20; d++) acc[d] = 0.f;
#pragma unroll 2
  for (int k = 0; k < 640; k++) {
    const float xv = __bfloat162float(xr[k]);
#pragma unroll
    for (int d = 0; d < 10; d++) {
      const uint32_t u = ldg32(wc + k * 1920 + 2 * d);
      acc[2 * d] = fmaf(xv, __uint_as_float(u << 16), acc[2 * d]);
      acc[2 * d + 1] = fmaf(xv, __uint_as_float(u & 0xffff0000u), acc[2 * d + 1]);
    }
  }
}
__device__ __noinline__ void attn_exact(const __nv_bfloat16* __restrict__ x, const __nv_bfloat16* __restrict__ wqkv, int h, int qt, uint32_t stg) {
  const int tid = threadIdx.x;
  uint32_t* kvs = g_fb + blockIdx.x * (2048 * 20);
  float a[20];
  for (int i = 0; i < 8; i++) {
    const int key = (i >> 1) * 512 + tid, ty = 1 + (i & 1);
    proj20(a, x + key * 640, wqkv + ty * 640 + h * 20);
#pragma unroll
    for (int d = 0; d < 10; d++) kvs[key * 20 + (i & 1) * 10 + d] = pack_bf16(a[2 * d], a[2 * d + 1]);
  }
  const int row = qt * 512 + tid;
  proj20(a, x + row * 640, wqkv + h * 20);
#pragma unroll
  for (int d = 0; d < 20; d++) a[d] = __bfloat162float(__float2bfloat16(a[d]));
  __syncthreads();
  float o[20], m = -INFINITY, l = 0.f;
#pragma unroll
  for (int d = 0; d < 20; d++) o[d] = 0.f;
  for (int key = 0; key < 2048; key++) {
    uint32_t u[20];
#pragma unroll
    for (int d = 0; d < 5; d++) {
      const uint4 t4 = *reinterpret_cast<const uint4*>(kvs + key * 20 + 4 * d);
      u[4 * d] = t4.x; u[4 * d + 1] = t4.y; u[4 * d + 2] = t4.z; u[4 * d + 3] = t4.w;
    }
    float s = 0.f;
#pragma unroll
    for (int d = 0; d < 10; d++) {
      s = fmaf(a[2 * d], __uint_as_float(u[d] << 16), s);
      s = fmaf(a[2 * d + 1], __uint_as_float(u[d] & 0xffff0000u), s);
    }
    s *= 0.22360679774997896f;
    const float mn = fmaxf(m, s), cr = __expf(m - mn), p = __expf(s - mn);
    m = mn;
    l = l * cr + p;
#pragma unroll
    for (int d = 0; d < 10; d++) {
      o[2 * d] = fmaf(p, __uint_as_float(u[10 + d] << 16), o[2 * d] * cr);
      o[2 * d + 1] = fmaf(p, __uint_as_float(u[10 + d] & 0xffff0000u), o[2 * d + 1] * cr);
    }
  }
  const float sc = __ldcg(&g_gate[row]) / l;
#pragma unroll
  for (int d = 0; d < 10; d++) {
    const int col = (h & 1) * 4 + 2 * d;
    sts32(stg + (tid >> 7) * 6144 + (col >> 3) * 2048 + (tid & 127) * 16 + (col & 7) * 2, pack_bf16(o[2 * d] * sc, o[2 * d + 1] * sc));
  }
  PROXY_FENCE();
  __syncthreads();
}

#define COORDS()                                                                                                        \
  int tid, bid;                                                                                                         \
  asm volatile("mov.u32 %0, %%tid.x;" : "=r"(tid));                                                                     \
  asm volatile("mov.u32 %0, %%ctaid.x;" : "=r"(bid));                                                                   \
  const int wg = __shfl_sync(0xffffffffu, tid >> 7, 0);                                                                 \
  const int lane = tid & 31, w = (tid >> 5) & 3, g = lane >> 2, t = lane & 3, wt = tid & 127;                           \
  const int rb1 = bid >> 3, c1 = bid & 7;                                       \
  const int h = bid >> 2, qt = bid & 3, rb = qt * 4 + wg;                    \
  const bool odd = h & 1;                                                                                               \
  const int c0 = (h * 5) >> 1;                                               \
  const int lsrc = (lane & ~3) | (odd ? 0 : 2);                                                                         \
  const bool v0 = !odd || t >= 2, v2 = odd || t < 2;                                                                    \
  const uint32_t ostg = sb + SM_X + wg * 6144, orow = (w * 16 + g) * 16 + t * 4;                                        \
  const uint32_t onepos = (wt >> 6) * 6144 + 3072 + (odd ? 0 : 2048 + 8) + (wt & 63) * 16;                              \
  const int kh = bid & 1, cg = (bid >> 1) & 3, atom3 = (cg >> 1) * 5 + (cg & 1) * 2;                                    \
  auto p3_load_w = [&](bool p, int j) {                                                                                 \
    const uint32_t fb = bar + 8 * (B_P3FULL + (j & 3));                                                                 \
    mbar_expect_if(p, fb, P3_STB);                                                                                      \
    tma3d_if(p, sb + (j & 3) * P3_STB + 16384, &maps.wo[j < 5], (kh * 5 + (j < 5 ? j : j - 5)) * 64, atom3, fb);       \
  };                                                                                                                    \
  auto p3_load_a = [&](bool p, int j) {                                                                                 \
    bulk_g2s_if(p, sb + (j & 3) * P3_STB, g_o + rb1 * ORB + ((j < 5 ? 10 + j : j - 5) + kh * 5) * 16384, 16384,         \
                bar + 8 * (B_P3FULL + (j & 3)));                                                                        \
  };                                                                                                                    \
  (void)g; (void)t; (void)wt; (void)rb1; (void)c1; (void)rb; (void)c0; (void)lsrc; (void)v0; (void)v2; (void)ostg;      \
  (void)orow; (void)onepos; (void)atom3; (void)p3_load_w; (void)p3_load_a

__global__ void __launch_bounds__(512, 1)
gated_mix_kernel(const __grid_constant__ Maps maps, const __nv_bfloat16* __restrict__ x, const __nv_bfloat16* __restrict__ wqkv, const __nv_bfloat16* __restrict__ w_phi,
                 const __nv_bfloat16* __restrict__ gate_w, const void* wqkv_b, const void* wo_a, const void* wo_b, uint4* __restrict__ out) {
  extern __shared__ __align__(1024) uint8_t smem_raw[];
  const uint32_t sb = (uint32_t)__cvta_generic_to_shared(smem_raw);
  const uint32_t bar = sb + SM_BAR;
  uint32_t q[2][6], qc[4], epoch, events;
  int bad;
  {
  COORDS();
  TS_INIT();

  auto p1_load = [&](bool p, int it) {
    const int st = it & 3, br = it >= 10, ks = it - br * 10;
    const uint32_t dst = sb + st * P1_STB, fb = bar + 8 * (B_FULL + st);
    mbar_expect_if(p, fb, P1_STB);
    tma2d_if(p, dst, &maps.x, ks * 64, rb1 * 128, fb);
    tma3d_if(p, dst + 16384, &maps.w[br], ks * 64, tile_atom(c1 ^ br), fb);
  };
  if (wt == 0) {
    mbar_init(bar + 8 * (B_FULL + wg), 1);
    asm volatile("fence.mbarrier_init.release.cluster;" ::: "memory");
    if (wg == 0) p1_load(true, 0);
  }
  TS_REG(tsa_);
  if (wt == 32) {
#pragma unroll
    for (int u = 0; u < 4; u++)
      if (wg == u) {
#pragma unroll
        for (int i = B_AUX + u * 8; i < B_AUX + u * 8 + 8; i++)
          mbar_init(bar + 8 * i, i == B_AUX ? 3 : i < B_P3EMPTY ? 1 : i < B_EMPTY ? 2 : i < B_ZERO ? 4 : i == B_ZERO ? 16 : i < B_READY + 2 ? 512 : 128);
      }
    asm volatile("fence.mbarrier_init.release.cluster;" ::: "memory");
  }
  if (tid >= 96 && tid < 100) sts32(sb + SM_BAR + 432 + (tid & 3) * 4, 0u);
  TS_REG(tsb_);
  TS_REG(tsc_);
  asm volatile("st.shared.v4.b32 [%0], {%1, %1, %1, %1};" ::"r"(sb + SM_X + tid * 16), "r"(0) : "memory");
  if (tid < 256) sts32(sb + SM_CONST + tid * 4, (tid & 3) ? 0u : ((tid >> 5) < NMB ? 0xdd02e192u : 0x00001ef0u));
  PROXY_FENCE();
  TS_REG(tsd_);
  __syncthreads();
  if (wg > 0) p1_load(wt == 0, wg);
  if (wt == 64) {
    if (wg == 1) { mbar_expect_if(true, bar + 8 * B_AUX, 1280); bulk_g2s_if(true, sb + SM_GW, gate_w, 1280, bar + 8 * B_AUX); }
    if (wg == 2) { mbar_expect_if(true, bar + 8 * B_AUX, 800); bulk_g2s_if(true, sb + SM_WRAW, w_phi + h * 400, 800, bar + 8 * B_AUX); }
    if (wg == 3) { mbar_expect_if(true, bar + 8 * B_AUX, 16); bulk_g2s_if(true, sb + SM_EP, &g_cnt[C_EPOCH], 16, bar + 8 * B_AUX); }
  }
  TS_FIRST();

  {
    float acc[64];
    const int r = wg & 1, ch = wg >> 1;
    const bool mufu0 = 2 * w < NMB, mufu1 = 2 * w + 1 < NMB;
    uint32_t pk[32];
    float gs = 0.f;
    const int grow = c1 * 16 + (tid >> 5);
    auto stage = [&](uint32_t stg, int e0) {
#pragma unroll
      for (int e = 0; e < 16; e += 4) stsm4(stg + (w * 16 + (lane & 15)) * 16 + (lane >> 4) * 1024 + e * 512, pk[e0 + e], pk[e0 + e + 1], pk[e0 + e + 2], pk[e0 + e + 3]);
    };
    auto release = [&](int it) {
      if (it < 16) {
        uint32_t old = 0;
        if (wt == 0) asm volatile("atom.shared.add.u32 %0, [%1], 1;" : "=r"(old) : "r"(sb + SM_BAR + 432 + (it & 3) * 4) : "memory");
        p1_load((old & 3) == 3, it + 4);
      } else {
        mbar_arrive_if(wt == 0, bar + 8 * (B_EMPTY + (it & 3)));
      }
    };
    auto duties = [&](auto BR, int it, int ga0, bool narrow_a) {
      constexpr int br = decltype(BR)::value;
      if (br == 0 && wg == 0 && it >= 1 && it <= 4) {
        const bool p = wt == 0;
        if (it < 4) bulk_s2g_if(p, reinterpret_cast<uint8_t*>(out) + bid * 20480 + (it - 1) * 8192, sb + SM_X, it == 3 ? 4096 : 8192);
        else bulk_s2g_if(p, g_kv + bid * 240, sb + SM_X, 960);
        bulk_s2g_if(p, g_o + rb1 * ORB + ((c1 * 4 + it - 1) * 5 + 2) * 2048, sb + SM_X, 2048);
        BULK_COMMIT();
      }
      if (br == 0 && it == 2 && wg == 1 && wt < 3) {
        const int bytes = wt == 0 ? 19200 : 6400;
        const uint8_t* p = reinterpret_cast<const uint8_t*>(wt == 0 ? wqkv_b : wt == 1 ? wo_a : wo_b) + bid * bytes;
        asm volatile("cp.async.bulk.prefetch.L2.global [%0], %1;" ::"l"(p), "r"(bytes) : "memory");
      }
      if (br == 0 && it == 4) {
        epoch = (lds32(sb + SM_EP) >> 7) + 1;
#pragma unroll
        for (int u = 0; u < 2; u++) {
          const int i = tid + u * 512, k = i / 24, n = i % 24, ii = 2 * (n >> 3) + (n & 1), f = 4 * ii + ((n & 7) >> 1), d = k - (odd ? 4 : 0);
          uint16_t v = 0;
          if (d >= 0 && d < 20 && ii < 5) asm volatile("ld.shared.u16 %0, [%1];" : "=h"(v) : "r"(sb + SM_WRAW + (d * 20 + f) * 2) : "memory");
          if (i < 768) sts16(sb + SM_WPHI + (k >> 3) * 384 + n * 16 + (k & 7) * 2, v);
        }
      }
      if (br == 0 && it == 6 && wg == 0) BULK_WAIT_READ();
      if (br == 1 && (it == 10 + ch || it == 12 + ch)) {
        const int u = it >= 12;
        if (!u) {
          mbar_wait(bar + 8 * B_ZERO, 0);
          stage(sb + SM_X + wg * 8192, 0);
        } else {
          BULK_WAIT_READ();
          bar_sync(1 + wg, 128);
          stage(sb + SM_X + wg * 8192, 16);
        }
        PROXY_FENCE();
        bar_sync(1 + wg, 128);
        tma5d_store_if(wt == 0 && !(u && narrow_a), &maps.qst, sb + SM_X + wg * 8192, ((ga0 + u) % 10) * 8, (ga0 + u) / 10, wg & 1, rb1);
        bulk_s2g_if(wt == 0 && u, g_gate + rb1 * 128 + c1 * 16 + wg * 4, sb + SM_BAR + 448 + wg * 16, 16);
        BULK_COMMIT();
      }
      if (br == 1 && it == 11 - ch) {
#pragma unroll
        for (int o = 16; o; o >>= 1) gs += __shfl_xor_sync(0xffffffffu, gs, o);
        if (lane == 0) sts32(sb + SM_BAR + 448 + (tid >> 5) * 4, __float_as_uint(rcp(1.f + ex2(gs * -1.4426950408889634f))));
      }
      if (br == 1 && it == 15) signal_bulk_if(wt == 0, &g_cnt[C_TA]);
      if (br == 1 && it >= 17 && it <= 18 && wg == (it & 3)) {
        wait_count(&g_cnt[C_TA], epoch * 512);
        mbar_wait(bar + 8 * (B_EMPTY + (it - 17)), 0);
        mbar_expect_if(wt == 0, bar + 8 * (B_KVFULL + it - 17), P1_STB);
        tma5d_if(wt == 0, sb + (it - 17) * P1_STB, &maps.qld, c0, 1, (it - 17) * 4, bar + 8 * (B_KVFULL + it - 17));
      }
      if (br == 1 && it == 19) {
        mbar_wait(bar + 8 * (B_KVFULL + 0), 0);
        const uint8_t* qp = g_qkv + rb * QRB + c0 * 2048 + orow;
        load_frag(q[0], qp);
        load_frag(q[1], qp + 1024);
        bad = ldcg32(&g_kbad);
        sts16(sb + wg * 12288 + onepos, 0x3c00);
        PROXY_FENCE();
        mbar_arrive(bar + 8 * (B_READY + 0));
      }
    };
    const int ga_a = tile_atom(c1) + 2 * ch + (((c1 & 3) == 2 && wg == 0) ? 1 : 0);
    const bool narrow_a = ((c1 & 3) == 1 && wg == 3) || ((c1 & 3) == 2 && wg == 0);
    uint32_t xh[3] = {0u, 0u, 0u};
    auto gate_fma = [&](uint32_t a, int ks) {
      const uint32_t b = lds32(sb + SM_GW + ks * 128 + lane * 4);
      gs = fmaf(__uint_as_float(a << 16), __uint_as_float(b << 16), gs);
      gs = fmaf(__uint_as_float(a & 0xffff0000u), __uint_as_float(b & 0xffff0000u), gs);
    };
    auto gate_step = [&](uint32_t dst, int ks) {
      const uint32_t a = lds32(dst + grow * 128 + (((lane >> 2) ^ (grow & 7)) << 4) + t * 4);
      if (ks < 3) { xh[0] = xh[1]; xh[1] = xh[2]; xh[2] = a; }
      else {
        if (ks == 3) { mbar_wait(bar + 8 * B_AUX, 0); gate_fma(xh[0], 0); gate_fma(xh[1], 1); gate_fma(xh[2], 2); }
        gate_fma(a, ks);
      }
      __syncwarp();
      mbar_arrive_if(ks == 9 && lane == 0, bar + 8 * B_ZERO);
    };
    auto tile = [&](auto BR) {
      constexpr int br = decltype(BR)::value;
      const int tl = c1 ^ br, k4 = tl & 3;
      const bool narrow = (k4 == 1 && wg == 3) || (k4 == 2 && wg == 0);
      const int a0 = 2 * ch + ((k4 == 2 && wg == 0) ? 1 : 0);
      if (!narrow) {
#pragma unroll 1
        for (int ks = 0; ks < 10; ks++) {
          const int it = br * 10 + ks, st = it & 3;
          mbar_wait(bar + 8 * (B_FULL + st), (it >> 2) & 1);
          TS_MARK(20 + it);
          const uint32_t dst = sb + st * P1_STB;
          const uint64_t da = mkdesc(dst + r * 8192, 16, 1024, 1), db = mkdesc(dst + 16384 + a0 * 8192, 8192, 1024, 1);
          WG_FENCE();
#pragma unroll
          for (int k = 0; k < 4; k++) wg128_ss(acc, da + k * 2, db + k * 128, (ks | k) != 0);
          WG_COMMIT();
          if (br == 0) gate_step(dst, ks);
          WG_WAIT(1);
          if (ks > 0) release(it - 1);
          duties(BR, it, ga_a, narrow_a);
        }
        WG_WAIT(0);
      } else {
#pragma unroll 1
        for (int ks = 0; ks < 10; ks++) {
          const int it = br * 10 + ks, st = it & 3;
          mbar_wait(bar + 8 * (B_FULL + st), (it >> 2) & 1);
          TS_MARK(20 + it);
          const uint32_t dst = sb + st * P1_STB;
          const uint64_t da = mkdesc(dst + r * 8192, 16, 1024, 1), db = mkdesc(dst + 16384 + a0 * 8192, 8192, 1024, 1);
          WG_FENCE();
#pragma unroll
          for (int k = 0; k < 4; k++) wg64_ss_of64(acc, da + k * 2, db + k * 128, (ks | k) != 0);
          WG_COMMIT();
          if (br == 0) gate_step(dst, ks);
          WG_WAIT(1);
          if (ks > 0) release(it - 1);
          duties(BR, it, ga_a, narrow_a);
        }
        WG_WAIT(0);
      }
      pin(acc);
      TS_MARK(2 + 2 * br);
      release(br * 10 + 9);
      const int ga0 = tile_atom(tl) + a0;
      uint32_t m0 = 0, m1 = 0;
      if (br == 0) {
        const float sk0 = __uint_as_float(mufu0 ? (127u + 70u) << 23 : (127u - 69u) << 23);
        const float sk1 = __uint_as_float(mufu1 ? (127u + 70u) << 23 : (127u - 69u) << 23);
        pack_atom_a<0>(acc, pk, ga0, sk0, sk1, m0, m1);
        if (!narrow) pack_atom_a<1>(acc, pk, ga0 + 1, sk0, sk1, m0, m1);
        const uint32_t lim0 = (mufu0 ? 127u + 110u : 127u - 29u) << 7, lim1 = (mufu1 ? 127u + 110u : 127u - 29u) << 7;
        if ((m0 & 0x7fffu) >= lim0 || ((m0 >> 16) & 0x7fffu) >= lim0 || (m1 & 0x7fffu) >= lim1 || ((m1 >> 16) & 0x7fffu) >= lim1) { g_kbad = epoch; __threadfence(); }
      } else {
        pack_atom<0, 0>(acc, pk, 0.f, 0.f, m0, m1);
        pack_atom<0, 1>(acc, pk, 0.f, 0.f, m0, m1);
        if (ch) mbar_wait(bar + 8 * (B_EMPTY + 2), 0);
        const uint32_t stg = sb + (ch ? 2 * P1_STB : SM_X) + r * 16384;
        stage(stg, 0);
        stage(stg + 8192, 16);
        mbar_wait(bar + 8 * (B_KVFULL + 1), 0);
        sts16(sb + P1_STB + wg * 12288 + onepos, 0x3c00);
        PROXY_FENCE();
        mbar_arrive(bar + 8 * (B_READY + 1));
        bar_sync(1 + wg, 128);
        tma5d_store_if(wt == 0, &maps.qst, stg, (ga0 % 10) * 8, ga0 / 10, r, 16 + rb1);
        tma5d_store_if(wt == 32 * 0 && !narrow, &maps.qst, stg + 8192, ((ga0 + 1) % 10) * 8, (ga0 + 1) / 10, r, 16 + rb1);
        BULK_COMMIT();
      }
      TS_MARK(3 + 2 * br);
    };
    tile(Int<0>{});
    tile(Int<1>{});
  }

  if (odd ? t < 2 : t >= 2) {
    if (odd) { q[0][0] = 0; q[0][1] = 0; q[1][0] = 0; q[1][1] = 0; }
    else { q[0][4] = 0; q[0][5] = 0; q[1][4] = 0; q[1][5] = 0; }
  }
  {
    uint32_t m = 0;
#pragma unroll
    for (int i = 0; i < 6; i++) m = maxabs_bf16x2(m, maxabs_bf16x2(q[0][i], q[1][i]));
    bad = bad == (int)epoch || (m & 0x7fffu) >= ((127u - 50u) << 7) || ((m >> 16) & 0x7fffu) >= ((127u - 50u) << 7);
  }
#pragma unroll
  for (int i = 0; i < 4; i++) { qc[i] = t == 0 ? 0x1c801c80u : 0u; asm volatile("" : "+r"(qc[i])); }
  events = 0x01010140u | (0x2008000u >> (2 * wg)) | (wg == 0 ? 0x8000480u : wg == 1 ? 0x40000u : wg == 2 ? 0x20000000u : 0x420000u);
  mbar_wait(bar + 8 * (B_READY + 0), 0);
  }
  float o[2][12];
#pragma unroll
  for (int i = 0; i < 12; i++) { o[0][i] = 0.f; o[1][i] = 0.f; }
  {
    uint32_t dk0 = (uint32_t)mkdesc(sb, 1024, 0, 0), dk1 = (uint32_t)mkdesc(sb + 2048, SM_CONST - 2048, 0, 0), dv = (uint32_t)mkdesc(sb + 3072, 128, 0, 0);
    TS_MARK(6);
#pragma unroll 1
    for (int i = 0; i < 32; i++) {
      if ((events >> i) & 1) {
        if ((i & 7) == 0 || i == 6 || i == 27) {
          COORDS();
          const bool p = wt == 0;
          signal_bulk_if(p && i != 8 && (i != 24 || wg != 0), &g_cnt[i == 6 ? C_TB : i == 16 ? C_KV + h : C_OB + rb * 2 + (h >> 4)]);
          if (i == 6) mbar_arrive_if(p, bar + 8 * B_STG);
          if ((i & 7) == 0) {
            WG_WAIT(0);
            mbar_arrive_if(p, bar + 8 * (B_FREE - 1) + i);
            mbar_wait(bar + 8 * B_READY + i, 0);
          }
        } else if (i == 7 || i == 10 || i == 17 || i == 22 || i == 29) {
          COORDS();
          const bool p = lane == 0;
          if (i == 7) {
            mbar_wait(bar + 8 * B_STG, 0);
            if (w == 1) wait_count(&g_cnt[C_TB], epoch * 512);
            const uint32_t fb = bar + 8 * (w ? B_KB : B_KVFULL + 2);
            mbar_expect_if(p && w < 2, fb, P1_STB);
            tma5d_if(p && w < 2, sb + (2 + w) * P1_STB, &maps.qld, c0, 1, w ? 16 + qt * 4 : 8, fb);
          } else if (i == 29) {
            mbar_wait(bar + 8 * (B_FREE + 2), 0);
            mbar_wait(bar + 8 * B_B2, 0);
            p3_load_w(p && w < 3, w);
            wait_count(&g_cnt[C_OB + rb1 * 2 + kh], epoch * 16);
            p3_load_a(p && w < 3, w);
          } else {
            if (i != 22) {
              const int u = i == 17;
              const uint32_t fb = bar + 8 * (u ? B_KVFULL + 3 : B_QB);
              mbar_wait(bar + 8 * (B_FREE + u), 0);
              mbar_expect_if(wt == 0, fb, P1_STB);
              tma5d_if(wt == 0, sb + u * 3 * P1_STB, &maps.qld, c0, u, u ? 12 : 16 + qt * 4, fb);
            }
            if (i != 17) {
              const int u = i == 10 ? 2 : 3;
              mbar_wait(bar + 8 * (B_KVFULL + u), 0);
#pragma unroll
              for (int e = 0; e < 4; e++) sts16(sb + u * P1_STB + e * 12288 + onepos, 0x3c00);
              PROXY_FENCE();
              mbar_arrive(bar + 8 * (B_READY + u));
            }
          }
        } else if (i < 16) {
          WG_WAIT(0);
          COORDS();
          const uint64_t dw = mkdesc(sb + SM_WPHI, 384, 128, 0);
          TS_MARK(7);
          const uint32_t kb = sb + 3 * P1_STB + wg * 12288, ph = sb + SM_X + (wg & 1) * 10240;
          mbar_wait(bar + 8 * B_KB, 0);
          sts16(kb + onepos, 0x3f80);
          float p0[12], p1[12];
          phi_proj(p0, p1, kb, dw);
          if (wg < 2) mbar_wait(bar + 8 * (B_LINK + wg), 0);
          uint32_t phi[10];
          feature_map(phi, p0);
#pragma unroll
          for (int u = 0; u < 10; u++) sts32(ph + (u % 5) * 2048 + orow + (u / 5) * 128, phi[u]);
          feature_map(phi, p1);
#pragma unroll
          for (int u = 0; u < 10; u++) sts32(ph + (u % 5) * 2048 + orow + (u / 5) * 128 + 1024, phi[u]);
          PROXY_FENCE();
          bar_sync(1 + wg, 128);
          const uint64_t da = mkdesc(ph, 128, 2048, 0), db = mkdesc(kb + 3072, 128, 1024, 0);
          WG_FENCE();
#pragma unroll
          for (int kk = 0; kk < 8; kk++) {
            if (kk == 0) wg24_ss_bf16_tt_i(p0, da, db);
            else wg24_ss_bf16_tt(p0, da + kk * 16, db + (kk & 3) * 16 + (kk >> 2) * 384, 1);
          }
          WG_COMMIT();
          WG_WAIT(0);
          pin(p0);
          mbar_arrive_if(lane == 0 && wg >= 2, bar + 8 * (B_LINK + (wg & 1)));
          bar_sync(1 + wg, 128);
          const uint32_t ks = kb + ((w * 16 + g) * 24 + 2 * t) * 4;
#pragma unroll
          for (int j = 0; j < 3; j++) {
            if (w < 3) asm volatile("st.shared.v2.f32 [%0], {%1, %2};" ::"r"(ks + 32 * j), "f"(p0[4 * j]), "f"(p0[4 * j + 1]) : "memory");
            if (w < 2) asm volatile("st.shared.v2.f32 [%0], {%1, %2};" ::"r"(ks + 768 + 32 * j), "f"(p0[4 * j + 2]), "f"(p0[4 * j + 3]) : "memory");
          }
          PROXY_FENCE();
          bar_sync(1 + wg, 128);
          bulk_addf_if(wt == 0, g_kv + h * 960, kb, 3840);
          BULK_COMMIT();
          TS_MARK(8);
        } else if (i == 18) {
          COORDS();
          wait_count(&g_cnt[C_KV + h], epoch * 16);
          float v[8];
#pragma unroll
          for (int u = 0; u < 8; u++) v[u] = (u < 7 || wt < 64) ? __ldcg(&g_kv[h * 960 + u * 128 + wt]) : 0.f;
#pragma unroll
          for (int u = 0; u < 9; u++) {
            const int e = u * 128 + wt, f = e / 24, d = e % 24;
            sts16(sb + SM_KVB + (f >> 3) * 384 + d * 16 + (f & 7) * 2, u < 8 ? __bfloat16_as_ushort(__float2bfloat16(v[u < 8 ? u : 0])) : (uint16_t)0);
          }
          PROXY_FENCE();
          mbar_arrive(bar + 8 * B_KVB);
        } else {
          WG_WAIT(0);
          COORDS();
          const uint64_t dw = mkdesc(sb + SM_WPHI, 384, 128, 0);
          TS_MARK(9);
          float gt[4];
#pragma unroll
          for (int u = 0; u < 4; u++) gt[u] = 1.f - __ldcg(&g_gate[rb * 128 + (u >> 1) * 64 + w * 16 + g + (u & 1) * 8]);
          mbar_wait(bar + 8 * B_QB, 0);
          float p0[12], p1[12];
          phi_proj(p0, p1, sb + wg * 12288, dw);
          const uint64_t dkv = mkdesc(sb + SM_KVB, 384, 128, 0);
          auto readout = [&](float (&p)[12], float g0, float g1, uint32_t a) {
            uint32_t phi[10];
            feature_map(phi, p);
            WG_FENCE();
            wg24_rs_bf16_i(p, phi[0], phi[5], phi[1], phi[6], dkv);
            wg24_rs_bf16(p, phi[2], phi[7], phi[3], phi[8], dkv + 48, 1);
            wg24_rs_bf16(p, phi[4], phi[9], 0u, 0u, dkv + 96, 1);
            WG_COMMIT();
            WG_WAIT(0);
            pin(p);
            const float l0 = __shfl_sync(0xffffffffu, odd ? p[0] : p[8], lsrc), l1 = __shfl_sync(0xffffffffu, odd ? p[2] : p[10], lsrc);
            stage_o(p, __fdividef(g0, l0 + 1e-6f), __fdividef(g1, l1 + 1e-6f), a, v0, v2);
          };
          mbar_wait(bar + 8 * B_KVB, 0);
          readout(p0, gt[0], gt[1], ostg + orow);
          readout(p1, gt[2], gt[3], ostg + orow + 1024);
          PROXY_FENCE();
          bar_sync(1 + wg, 128);
          mbar_arrive_if(wt == 0, bar + 8 * B_B2);
          flush_o(wt == 0, g_o + rb * ORB + (80 + c0) * 2048, ostg, odd);
          TS_MARK(10);
        }
      }
      if (!(i & 3)) TS_MARK(40 + (i >> 2));
#pragma unroll
      for (int m = 0; m < 2; m++) {
        float s[32];
        uint32_t p[16];
        WG_FENCE();
        wg64_rs_bf16_i(s, q[m][0], q[m][1], q[m][2], q[m][3], desc_lohi(dk0, 8));
        wg64_rs_bf16(s, q[m][4], q[m][5], qc[2 * m], qc[2 * m + 1], desc_lohi(dk1, 8), 1);
        WG_COMMIT();
        WG_WAIT(0);
        constexpr int A = 2 * NMB, B = 16 - A;
#pragma unroll
        for (int j = 0; j < B; j++) {
          if ((j * A) % B < A) { const int a = j * A / B; p[a] = exp2_pair_mufu(s[2 * a], s[2 * a + 1]); }
          p[A + j] = exp2_pair(s[2 * (A + j)], s[2 * (A + j) + 1]);
        }
        WG_FENCE();
#pragma unroll
        for (int kk = 0; kk < 4; kk++) wg24_rs_f16_t(o[m], p[4 * kk], p[4 * kk + 1], p[4 * kk + 2], p[4 * kk + 3], desc_lohi(dv + kk * 16, 64), 1);
        WG_COMMIT();
      }
      dk0 += 384; dk1 += 384u - (384u << 16); dv += 384;
    }
  }
  {
    COORDS();
    float gt[4];
#pragma unroll
    for (int u = 0; u < 4; u++) gt[u] = __ldcg(&g_gate[rb * 128 + (u >> 1) * 64 + w * 16 + g + (u & 1) * 8]);
    WG_WAIT(0);
    pin(o[0]); pin(o[1]);
    TS_MARK(11);
    int big = 0;
#pragma unroll
    for (int m = 0; m < 2; m++) {
      const float l0 = __shfl_sync(0xffffffffu, odd ? o[m][0] : o[m][8], lsrc), l1 = __shfl_sync(0xffffffffu, odd ? o[m][2] : o[m][10], lsrc);
      const float r0 = rcp(l0), r1 = rcp(l1);
      float chk = 0.f, mx0 = 0.f, mx1 = 0.f;
#pragma unroll
      for (int i = 0; i < 12; i++) chk = fmaf(o[m][i], 0.f, chk);
#pragma unroll
      for (int i = 4; i < 6; i++) { mx0 = fmaxf(mx0, fabsf(o[m][i])); mx1 = fmaxf(mx1, fabsf(o[m][i + 2])); }
      bad |= !(chk == 0.f) || !(l0 >= 32.f) || !(l1 >= 32.f);
      big |= fmaxf(mx0 * r0, mx1 * r1) >= 1.220703125e-4f;
      stage_o(o[m], r0 * gt[2 * m], r1 * gt[2 * m + 1], ostg + orow + m * 1024, v0, v2);
    }
    PROXY_FENCE();
    const int anybad = __syncthreads_or(bad), anybig = __syncthreads_or(big);
    if (anybad || !anybig) attn_exact(x, wqkv, h, qt, sb + SM_X);
  }
  TS_MARK(12);

  COORDS();
  if (wg == 3) {
    if (w == 3) { p3_load_w(lane == 0, 3); p3_load_a(lane == 0, 3); }
    bar_sync(4, 128);
    flush_o(lane == 0, g_o + (qt * 4 + w) * ORB + c0 * 2048, sb + SM_X + w * 6144, odd);
    signal_bulk_if(lane == 0, &g_cnt[C_OA + (qt * 4 + w) * 2 + (h >> 4)]);
    if (wt == 0) atomicAdd(&g_cnt[C_EPOCH], 1);
  } else if (wg == 2) {
    const bool p = lane == 0;
    mbar_wait(bar + 8 * (B_P3EMPTY + w), 0);
    p3_load_w(p, 4 + w);
    if (w > 0) wait_count(&g_cnt[C_OA + rb1 * 2 + kh], epoch * 16);
    p3_load_a(p, 4 + w);
    if (w < 2) {
      mbar_wait(bar + 8 * (B_P3EMPTY + w), 1);
      p3_load_w(p, 8 + w);
      if (w == 0) wait_count(&g_cnt[C_OA + rb1 * 2 + kh], epoch * 16);
      p3_load_a(p, 8 + w);
    }
  } else {
    float acc[96];
    const bool wide = (cg & 1) == wg;
    const int skip = (!wide && (cg & 1)) ? 1 : 0;
    if (wide) {
#pragma unroll 1
      for (int j = 0; j < 10; j++) {
        mbar_wait(bar + 8 * (B_P3FULL + (j & 3)), (j >> 2) & 1);
        if (j == 5) TS_MARK(13);
        if (j < 5) TS_MARK(j == 0 ? 1 : 15 + j);
        const uint32_t dst = sb + (j & 3) * P3_STB;
        const uint64_t da = mkdesc(dst + wg * 1024, 2048, 128, 0), db = mkdesc(dst + 16384, 8192, 1024, 1);
        WG_FENCE();
#pragma unroll
        for (int k = 0; k < 4; k++) wg192_ss(acc, da + k * 256, db + k * 128, (j | k) != 0);
        WG_COMMIT();
        WG_WAIT(1);
        mbar_arrive_if(j > 0 && wt == 0, bar + 8 * (B_P3EMPTY + ((j - 1) & 3)));
      }
      WG_WAIT(0);
    } else {
#pragma unroll 1
      for (int j = 0; j < 10; j++) {
        mbar_wait(bar + 8 * (B_P3FULL + (j & 3)), (j >> 2) & 1);
        if (j == 5) TS_MARK(13);
        if (j < 5) TS_MARK(j == 0 ? 1 : 15 + j);
        const uint32_t dst = sb + (j & 3) * P3_STB;
        const uint64_t da = mkdesc(dst + wg * 1024, 2048, 128, 0), db = mkdesc(dst + 16384 + skip * 8192, 8192, 1024, 1);
        WG_FENCE();
#pragma unroll
        for (int k = 0; k < 4; k++) wg128_ss_of96(acc, da + k * 256, db + k * 128, (j | k) != 0);
        WG_COMMIT();
        WG_WAIT(1);
        mbar_arrive_if(j > 0 && wt == 0, bar + 8 * (B_P3EMPTY + ((j - 1) & 3)));
      }
      WG_WAIT(0);
    }
    pin(acc);
    TS_MARK(14);
    if (!wide) mbar_wait(bar + 8 * (B_P3EMPTY + 2), 1);
    const uint32_t stg = sb + (wide ? 4 : 2) * P3_STB;
    const int r = w * 16 + (lane & 15);
#pragma unroll
    for (int i = 0; i < 24; i += 2)
      if (i < 16 || wide) {
        const int ch = (i & 7) + (lane >> 4);
        stsm4(stg + (i >> 3) * 8192 + r * 128 + ((ch ^ (r & 7)) << 4), pack_bf16(acc[4 * i], acc[4 * i + 1]), pack_bf16(acc[4 * i + 2], acc[4 * i + 3]),
              pack_bf16(acc[4 * i + 4], acc[4 * i + 5]), pack_bf16(acc[4 * i + 6], acc[4 * i + 7]));
      }
    PROXY_FENCE();
    bar_sync(1 + wg, 128);
    if (wt < (wide ? 3 : 2)) {
      PROXY_FENCE_G();
      asm volatile("cp.reduce.async.bulk.tensor.2d.global.shared::cta.add.bulk_group [%0, {%2, %3}], [%1];" ::"l"(&maps.out), "r"(stg + wt * 8192),
                   "r"((atom3 + skip + wt) * 64), "r"(rb1 * 128 + wg * 64) : "memory");
      asm volatile("cp.async.bulk.commit_group;" ::: "memory");
      asm volatile("cp.async.bulk.wait_group 0;" ::: "memory");
    }
    TS_MARK(15);
  }
  TS_DUMP();
}

typedef CUresult (*EncodeFn)(CUtensorMap*, CUtensorMapDataType, cuuint32_t, void*, const cuuint64_t*, const cuuint64_t*, const cuuint32_t*, const cuuint32_t*,
                             CUtensorMapInterleave, CUtensorMapSwizzle, CUtensorMapL2promotion, CUtensorMapFloatOOBfill);
void encode(EncodeFn enc, CUtensorMap* m, void* p, int rank, const cuuint64_t* gd, const cuuint64_t* gs, const cuuint32_t* bd) {
  const cuuint32_t es[3] = {1, 1, 1};
  enc(m, CU_TENSOR_MAP_DATA_TYPE_BFLOAT16, rank, p, gd, gs, bd, es, CU_TENSOR_MAP_INTERLEAVE_NONE, CU_TENSOR_MAP_SWIZZLE_128B,
      CU_TENSOR_MAP_L2_PROMOTION_L2_128B, CU_TENSOR_MAP_FLOAT_OOB_FILL_NONE);
}

}

extern "C" void kernel_launch(void* const* d_in, const int* in_sizes, int n_in, void* d_out, int out_size) {
  static EncodeFn enc = nullptr;
  if (!enc) {
    cudaDriverEntryPointQueryResult qr;
    cudaGetDriverEntryPoint("cuTensorMapEncodeTiled", (void**)&enc, cudaEnableDefault, &qr);
    cudaFuncSetAttribute(gated_mix_kernel, cudaFuncAttributeMaxDynamicSharedMemorySize, SMEM_BYTES);
  }
  Maps m;
  {
    const cuuint64_t gd[2] = {640, 2048}, gs[1] = {1280};
    const cuuint32_t bx[2] = {64, 128}, bo[2] = {64, 64};
    encode(enc, &m.x, d_in[0], 2, gd, gs, bx);
    encode(enc, &m.out, d_out, 2, gd, gs, bo);
  }
  for (int b = 0; b < 2; b++) {
    const cuuint64_t gd[3] = {64, 640, 30}, gs[2] = {3840, 128}, gd3[3] = {64, 640, 10}, gs3[2] = {1280, 128};
    const cuuint32_t bd[3] = {64, 64, 4}, bd3[3] = {64, 64, 3};
    encode(enc, &m.w[b], d_in[b ? 4 : 1], 3, gd, gs, bd);
    encode(enc, &m.wo[b], d_in[b ? 6 : 2], 3, gd3, gs3, bd3);
  }
  {
    void* qp = nullptr;
    cudaGetSymbolAddress(&qp, g_qkv);
    const cuuint64_t gd[5] = {128, 80, 3, 2, 32}, gs[4] = {2048, QTY, 1024, QRB};
    const cuuint32_t bl[5] = {128, 3, 2, 2, 4}, bs[5] = {128, 8, 1, 1, 1}, es[5] = {1, 1, 1, 1, 1};
    enc(&m.qld, CU_TENSOR_MAP_DATA_TYPE_UINT64, 5, qp, gd, gs, bl, es, CU_TENSOR_MAP_INTERLEAVE_NONE, CU_TENSOR_MAP_SWIZZLE_NONE, CU_TENSOR_MAP_L2_PROMOTION_L2_128B, CU_TENSOR_MAP_FLOAT_OOB_FILL_NONE);
    enc(&m.qst, CU_TENSOR_MAP_DATA_TYPE_UINT64, 5, qp, gd, gs, bs, es, CU_TENSOR_MAP_INTERLEAVE_NONE, CU_TENSOR_MAP_SWIZZLE_NONE, CU_TENSOR_MAP_L2_PROMOTION_NONE, CU_TENSOR_MAP_FLOAT_OOB_FILL_NONE);
  }
  gated_mix_kernel<<<128, 512, SMEM_BYTES, cudaStreamPerThread>>>(m, (const __nv_bfloat16*)d_in[0], (const __nv_bfloat16*)d_in[1], (const __nv_bfloat16*)d_in[5],
                                                                 (const __nv_bfloat16*)d_in[7], d_in[4], d_in[2], d_in[6], (uint4*)d_out);
}
```

```cpp
#include <cuda_runtime.h>
#include <cuda.h>
#include <cuda_bf16.h>
#include <cuda_fp16.h>
#include <stdint.h>
#pragma nv_diag_suppress 550

namespace {

constexpr int QRB = 240 * 2048;
constexpr int QBR = 16 * QRB;
constexpr int QTY = 80 * 2048;
constexpr int ORB = 160 * 2048;
constexpr int NMB = 3;

__device__ __align__(1024) uint8_t g_qkv[2 * QBR];
__device__ __align__(1024) uint8_t g_o[16 * ORB];
__device__ float g_gate[2048];
__device__ __align__(16) float g_kv[32 * 960];
__device__ uint32_t g_kbad;
__device__ uint32_t g_fb[128 * 2048 * 20];
__device__ uint32_t g_cnt[192];
constexpr int C_EPOCH = 0, C_TA = 32, C_TB = 64, C_KV = 96, C_OB = 128, C_OA = 160;

#define TS_MARK(i)
#define TS_INIT()
#define TS_REG(x)
#define TS_PUT(i, x, th)
#define TS_FIRST()
#define TS_DUMP()

__device__ __forceinline__ uint64_t mkdesc(uint32_t addr, uint32_t lbo, uint32_t sbo, int mode) {
  return (uint64_t)((addr & 0x3FFFF) >> 4) | ((uint64_t)(lbo >> 4) << 16) | ((uint64_t)(sbo >> 4) << 32) | ((uint64_t)mode << 62);
}
__device__ __forceinline__ uint64_t desc_lohi(uint32_t lo, uint32_t hi) { return ((uint64_t)hi << 32) | lo; }
#define WG_FENCE() asm volatile("wgmma.fence.sync.aligned;" ::: "memory")
#define WG_COMMIT() asm volatile("wgmma.commit_group.sync.aligned;" ::: "memory")
#define WG_WAIT(n) asm volatile("wgmma.wait_group.sync.aligned %0;" ::"n"(n) : "memory")
#define PROXY_FENCE() asm volatile("fence.proxy.async.shared::cta;" ::: "memory")
#define PROXY_FENCE_G() asm volatile("fence.proxy.async.global;" ::: "memory")
__device__ __forceinline__ void bar_sync(int id, int n) { asm volatile("bar.sync %0, %1;" ::"r"(id), "r"(n) : "memory"); }
__device__ __forceinline__ void bar_arrive(int id, int n) { asm volatile("bar.arrive %0, %1;" ::"r"(id), "r"(n) : "memory"); }
__device__ __forceinline__ void mbar_init(uint32_t a, int c) { asm volatile("mbarrier.init.shared::cta.b64 [%0], %1;" ::"r"(a), "r"(c)); }
__device__ __forceinline__ uint32_t mbar_try(uint32_t a, int par) {
  uint32_t ok;
  asm volatile("{.reg .pred p; mbarrier.try_wait.parity.shared::cta.b64 p, [%1], %2; selp.b32 %0, 1, 0, p;}" : "=r"(ok) : "r"(a), "r"(par) : "memory");
  return ok;
}
__device__ __forceinline__ void mbar_wait(uint32_t a, int par) {
  for (int i = 0; !mbar_try(a, par); i++)
    if (i > (1 << 22)) break;
}
__device__ __forceinline__ void mbar_arrive(uint32_t a) { asm volatile("mbarrier.arrive.shared::cta.b64 _, [%0];" ::"r"(a) : "memory"); }
__device__ __forceinline__ void mbar_arrive_if(bool p, uint32_t a) {
  asm volatile("{.reg .pred p; setp.ne.b32 p, %0, 0; @p mbarrier.arrive.shared::cta.b64 _, [%1];}" ::"r"((int)p), "r"(a) : "memory");
}
__device__ __forceinline__ void mbar_expect_if(bool p, uint32_t a, int bytes) {
  asm volatile("{.reg .pred p; setp.ne.b32 p, %0, 0; @p mbarrier.arrive.expect_tx.shared::cta.b64 _, [%1], %2;}" ::"r"((int)p), "r"(a), "r"(bytes) : "memory");
}
__device__ __forceinline__ void tma2d_if(bool p, uint32_t dst, const CUtensorMap* m, int c0, int c1, uint32_t bar) {
  asm volatile("{.reg .pred p; setp.ne.b32 p, %0, 0; @p cp.async.bulk.tensor.2d.shared::cluster.global.mbarrier::complete_tx::bytes [%1], [%2, {%4, %5}], [%3];}"
               ::"r"((int)p), "r"(dst), "l"(m), "r"(bar), "r"(c0), "r"(c1) : "memory");
}
__device__ __forceinline__ void tma3d_if(bool p, uint32_t dst, const CUtensorMap* m, int c1, int c2, uint32_t bar) {
  asm volatile("{.reg .pred p; setp.ne.b32 p, %0, 0; @p cp.async.bulk.tensor.3d.shared::cluster.global.mbarrier::complete_tx::bytes [%1], [%2, {%6, %4, %5}], [%3];}"
               ::"r"((int)p), "r"(dst), "l"(m), "r"(bar), "r"(c1), "r"(c2), "r"(0) : "memory");
}
__device__ __forceinline__ void bulk_g2s_if(bool p, uint32_t dst, const void* src, int bytes, uint32_t bar) {
  asm volatile("{.reg .pred p; setp.ne.b32 p, %0, 0; @p cp.async.bulk.shared::cluster.global.mbarrier::complete_tx::bytes [%1], [%2], %3, [%4];}"
               ::"r"((int)p), "r"(dst), "l"(src), "r"(bytes), "r"(bar) : "memory");
}
__device__ __forceinline__ void tma5d_if(bool p, uint32_t dst, const CUtensorMap* m, int c1, int c2, int c4, uint32_t bar) {
  asm volatile("{.reg .pred p; setp.ne.b32 p, %0, 0; @p cp.async.bulk.tensor.5d.shared::cluster.global.mbarrier::complete_tx::bytes [%1], [%2, {%7, %4, %5, %7, %6}], [%3];}"
               ::"r"((int)p), "r"(dst), "l"(m), "r"(bar), "r"(c1), "r"(c2), "r"(c4), "r"(0) : "memory");
}
__device__ __forceinline__ void tma5d_store_if(bool p, const CUtensorMap* m, uint32_t src, int c1, int c2, int c3, int c4) {
  asm volatile("{.reg .pred p; setp.ne.b32 p, %0, 0; @p cp.async.bulk.tensor.5d.global.shared::cta.bulk_group [%1, {%7, %3, %4, %5, %6}], [%2];}"
               ::"r"((int)p), "l"(m), "r"(src), "r"(c1), "r"(c2), "r"(c3), "r"(c4), "r"(0) : "memory");
}
__device__ __forceinline__ void bulk_s2g_if(bool p, void* dst, uint32_t src, int bytes) {
  asm volatile("{.reg .pred p; setp.ne.b32 p, %0, 0; @p cp.async.bulk.global.shared::cta.bulk_group [%1], [%2], %3;}" ::"r"((int)p), "l"(dst), "r"(src), "r"(bytes) : "memory");
}
__device__ __forceinline__ void bulk_or_if(bool p, void* dst, uint32_t src, int bytes) {
  asm volatile("{.reg .pred p; setp.ne.b32 p, %0, 0; @p cp.reduce.async.bulk.global.shared::cta.bulk_group.or.b32 [%1], [%2], %3;}" ::"r"((int)p), "l"(dst), "r"(src), "r"(bytes) : "memory");
}
__device__ __forceinline__ void bulk_addf_if(bool p, void* dst, uint32_t src, int bytes) {
  asm volatile("{.reg .pred p; setp.ne.b32 p, %0, 0; @p cp.reduce.async.bulk.global.shared::cta.bulk_group.add.f32 [%1], [%2], %3;}" ::"r"((int)p), "l"(dst), "r"(src), "r"(bytes) : "memory");
}
#define BULK_COMMIT() asm volatile("cp.async.bulk.commit_group;" ::: "memory")
#define BULK_WAIT() asm volatile("cp.async.bulk.wait_group 0;" ::: "memory")
#define BULK_WAIT_READ() asm volatile("cp.async.bulk.wait_group.read 0;" ::: "memory")
__device__ __forceinline__ void signal_bulk_if(bool p, uint32_t* c) {
  asm volatile("{.reg .pred p; setp.ne.b32 p, %0, 0; cp.async.bulk.wait_group 0; @p red.relaxed.gpu.global.add.u32 [%1], 1;}" ::"r"((int)p), "l"(c) : "memory");
}
__device__ __forceinline__ void wait_count(const uint32_t* c, uint32_t target) {
  for (int i = 0;; i++) {
    uint32_t v;
    asm volatile("ld.relaxed.gpu.global.u32 %0, [%1];" : "=r"(v) : "l"(c) : "memory");
    if ((int)(v - target) >= 0) break;
    if (i > (1 << 20)) break;
  }
  PROXY_FENCE_G();
}
__device__ __forceinline__ uint32_t pack_bf16(float lo, float hi) { uint32_t r; asm("cvt.rn.bf16x2.f32 %0, %1, %2;" : "=r"(r) : "f"(hi), "f"(lo)); return r; }
__device__ __forceinline__ uint32_t pack_f16(float lo, float hi) { uint32_t r; asm("cvt.rn.f16x2.f32 %0, %1, %2;" : "=r"(r) : "f"(hi), "f"(lo)); return r; }
__device__ __forceinline__ float ex2(float a) { float r; asm("ex2.approx.ftz.f32 %0, %1;" : "=f"(r) : "f"(a)); return r; }
__device__ __forceinline__ float ex2n(float a) { float r; asm("{.reg .f32 t; neg.ftz.f32 t, %1; ex2.approx.ftz.f32 %0, t;}" : "=f"(r) : "f"(a)); return r; }
__device__ __forceinline__ float rcp(float a) { float r; asm("rcp.approx.ftz.f32 %0, %1;" : "=f"(r) : "f"(a)); return r; }
__device__ __forceinline__ uint32_t maxabs_bf16x2(uint32_t a, uint32_t b) { uint32_t r; asm("max.NaN.xorsign.abs.bf16x2 %0, %1, %2;" : "=r"(r) : "r"(a), "r"(b)); return r; }
__device__ __forceinline__ uint32_t ldg32(const void* p) { return __ldg(reinterpret_cast<const uint32_t*>(p)); }
__device__ __forceinline__ uint32_t ldcg32(const void* p) { uint32_t v; asm volatile("ld.global.cg.u32 %0, [%1];" : "=r"(v) : "l"(p) : "memory"); return v; }
__device__ __forceinline__ uint32_t lds32(uint32_t a) { uint32_t v; asm volatile("ld.shared.b32 %0, [%1];" : "=r"(v) : "r"(a) : "memory"); return v; }
__device__ __forceinline__ void sts32(uint32_t a, uint32_t v) { asm volatile("st.shared.b32 [%0], %1;" ::"r"(a), "r"(v) : "memory"); }
__device__ __forceinline__ void sts16(uint32_t a, uint16_t v) { asm volatile("st.shared.b16 [%0], %1;" ::"r"(a), "h"(v) : "memory"); }
__device__ __forceinline__ void stsm4(uint32_t a, uint32_t r0, uint32_t r1, uint32_t r2, uint32_t r3) {
  asm volatile("stmatrix.sync.aligned.m8n8.x4.shared.b16 [%0], {%1, %2, %3, %4};" ::"r"(a), "r"(r0), "r"(r1), "r"(r2), "r"(r3) : "memory");
}
template <int N> __device__ __forceinline__ void pin(float (&d)[N]) {
#pragma unroll
  for (int i = 0; i < N; i++) asm volatile("" : "+f"(d[i])::"memory");
}

__device__ __forceinline__ void wg128_ss(float (&d)[64], uint64_t da, uint64_t db, int scale_d) {
  asm volatile("{\n.reg .pred p;\nsetp.ne.b32 p, %66, 0;\n"
    "wgmma.mma_async.sync.aligned.m64n128k16.f32.bf16.bf16 "
    "{%0, %1, %2, %3, %4, %5, %6, %7, %8, %9, %10, %11, %12, %13, %14, %15,"
    "%16, %17, %18, %19, %20, %21, %22, %23, %24, %25, %26, %27, %28, %29, %30, %31,"
    "%32, %33, %34, %35, %36, %37, %38, %39, %40, %41, %42, %43, %44, %45, %46, %47,"
    "%48, %49, %50, %51, %52, %53, %54, %55, %56, %57, %58, %59, %60, %61, %62, %63}, "
    "%64, %65, p, 1, 1, 0, 1;\n}\n"
    : "+f"(d[0]), "+f"(d[1]), "+f"(d[2]), "+f"(d[3]), "+f"(d[4]), "+f"(d[5]), "+f"(d[6]), "+f"(d[7]),
      "+f"(d[8]), "+f"(d[9]), "+f"(d[10]), "+f"(d[11]), "+f"(d[12]), "+f"(d[13]), "+f"(d[14]), "+f"(d[15]),
      "+f"(d[16]), "+f"(d[17]), "+f"(d[18]), "+f"(d[19]), "+f"(d[20]), "+f"(d[21]), "+f"(d[22]), "+f"(d[23]),
      "+f"(d[24]), "+f"(d[25]), "+f"(d[26]), "+f"(d[27]), "+f"(d[28]), "+f"(d[29]), "+f"(d[30]), "+f"(d[31]),
      "+f"(d[32]), "+f"(d[33]), "+f"(d[34]), "+f"(d[35]), "+f"(d[36]), "+f"(d[37]), "+f"(d[38]), "+f"(d[39]),
      "+f"(d[40]), "+f"(d[41]), "+f"(d[42]), "+f"(d[43]), "+f"(d[44]), "+f"(d[45]), "+f"(d[46]), "+f"(d[47]),
      "+f"(d[48]), "+f"(d[49]), "+f"(d[50]), "+f"(d[51]), "+f"(d[52]), "+f"(d[53]), "+f"(d[54]), "+f"(d[55]),
      "+f"(d[56]), "+f"(d[57]), "+f"(d[58]), "+f"(d[59]), "+f"(d[60]), "+f"(d[61]), "+f"(d[62]), "+f"(d[63])
    : "l"(da), "l"(db), "r"(scale_d));
}

__device__ __forceinline__ void wg64_ss_of64(float (&d)[64], uint64_t da, uint64_t db, int scale_d) {
  asm volatile("{\n.reg .pred p;\nsetp.ne.b32 p, %34, 0;\n"
    "wgmma.mma_async.sync.aligned.m64n64k16.f32.bf16.bf16 "
    "{%0, %1, %2, %3, %4, %5, %6, %7, %8, %9, %10, %11, %12, %13, %14, %15,"
    "%16, %17, %18, %19, %20, %21, %22, %23, %24, %25, %26, %27, %28, %29, %30, %31}, "
    "%32, %33, p, 1, 1, 0, 1;\n}\n"
    : "+f"(d[0]), "+f"(d[1]), "+f"(d[2]), "+f"(d[3]), "+f"(d[4]), "+f"(d[5]), "+f"(d[6]), "+f"(d[7]),
      "+f"(d[8]), "+f"(d[9]), "+f"(d[10]), "+f"(d[11]), "+f"(d[12]), "+f"(d[13]), "+f"(d[14]), "+f"(d[15]),
      "+f"(d[16]), "+f"(d[17]), "+f"(d[18]), "+f"(d[19]), "+f"(d[20]), "+f"(d[21]), "+f"(d[22]), "+f"(d[23]),
      "+f"(d[24]), "+f"(d[25]), "+f"(d[26]), "+f"(d[27]), "+f"(d[28]), "+f"(d[29]), "+f"(d[30]), "+f"(d[31])
    : "l"(da), "l"(db), "r"(scale_d));
}

__device__ __forceinline__ void wg192_ss(float (&d)[96], uint64_t da, uint64_t db, int scale_d) {
  asm volatile("{\n.reg .pred p;\nsetp.ne.b32 p, %98, 0;\n"
    "wgmma.mma_async.sync.aligned.m64n192k16.f32.bf16.bf16 "
    "{%0, %1, %2, %3, %4, %5, %6, %7, %8, %9, %10, %11, %12, %13, %14, %15,"
    "%16, %17, %18, %19, %20, %21, %22, %23, %24, %25, %26, %27, %28, %29, %30, %31,"
    "%32, %33, %34, %35, %36, %37, %38, %39, %40, %41, %42, %43, %44, %45, %46, %47,"
    "%48, %49, %50, %51, %52, %53, %54, %55, %56, %57, %58, %59, %60, %61, %62, %63,"
    "%64, %65, %66, %67, %68, %69, %70, %71, %72, %73, %74, %75, %76, %77, %78, %79,"
    "%80, %81, %82, %83, %84, %85, %86, %87, %88, %89, %90, %91, %92, %93, %94, %95}, "
    "%96, %97, p, 1, 1, 0, 1;\n}\n"
    : "+f"(d[0]), "+f"(d[1]), "+f"(d[2]), "+f"(d[3]), "+f"(d[4]), "+f"(d[5]), "+f"(d[6]), "+f"(d[7]),
      "+f"(d[8]), "+f"(d[9]), "+f"(d[10]), "+f"(d[11]), "+f"(d[12]), "+f"(d[13]), "+f"(d[14]), "+f"(d[15]),
      "+f"(d[16]), "+f"(d[17]), "+f"(d[18]), "+f"(d[19]), "+f"(d[20]), "+f"(d[21]), "+f"(d[22]), "+f"(d[23]),
      "+f"(d[24]), "+f"(d[25]), "+f"(d[26]), "+f"(d[27]), "+f"(d[28]), "+f"(d[29]), "+f"(d[30]), "+f"(d[31]),
      "+f"(d[32]), "+f"(d[33]), "+f"(d[34]), "+f"(d[35]), "+f"(d[36]), "+f"(d[37]), "+f"(d[38]), "+f"(d[39]),
      "+f"(d[40]), "+f"(d[41]), "+f"(d[42]), "+f"(d[43]), "+f"(d[44]), "+f"(d[45]), "+f"(d[46]), "+f"(d[47]),
      "+f"(d[48]), "+f"(d[49]), "+f"(d[50]), "+f"(d[51]), "+f"(d[52]), "+f"(d[53]), "+f"(d[54]), "+f"(d[55]),
      "+f"(d[56]), "+f"(d[57]), "+f"(d[58]), "+f"(d[59]), "+f"(d[60]), "+f"(d[61]), "+f"(d[62]), "+f"(d[63]),
      "+f"(d[64]), "+f"(d[65]), "+f"(d[66]), "+f"(d[67]), "+f"(d[68]), "+f"(d[69]), "+f"(d[70]), "+f"(d[71]),
      "+f"(d[72]), "+f"(d[73]), "+f"(d[74]), "+f"(d[75]), "+f"(d[76]), "+f"(d[77]), "+f"(d[78]), "+f"(d[79]),
      "+f"(d[80]), "+f"(d[81]), "+f"(d[82]), "+f"(d[83]), "+f"(d[84]), "+f"(d[85]), "+f"(d[86]), "+f"(d[87]),
      "+f"(d[88]), "+f"(d[89]), "+f"(d[90]), "+f"(d[91]), "+f"(d[92]), "+f"(d[93]), "+f"(d[94]), "+f"(d[95])
    : "l"(da), "l"(db), "r"(scale_d));
}

__device__ __forceinline__ void wg128_ss_of96(float (&d)[96], uint64_t da, uint64_t db, int scale_d) {
  asm volatile("{\n.reg .pred p;\nsetp.ne.b32 p, %66, 0;\n"
    "wgmma.mma_async.sync.aligned.m64n128k16.f32.bf16.bf16 "
    "{%0, %1, %2, %3, %4, %5, %6, %7, %8, %9, %10, %11, %12, %13, %14, %15,"
    "%16, %17, %18, %19, %20, %21, %22, %23, %24, %25, %26, %27, %28, %29, %30, %31,"
    "%32, %33, %34, %35, %36, %37, %38, %39, %40, %41, %42, %43, %44, %45, %46, %47,"
    "%48, %49, %50, %51, %52, %53, %54, %55, %56, %57, %58, %59, %60, %61, %62, %63}, "
    "%64, %65, p, 1, 1, 0, 1;\n}\n"
    : "+f"(d[0]), "+f"(d[1]), "+f"(d[2]), "+f"(d[3]), "+f"(d[4]), "+f"(d[5]), "+f"(d[6]), "+f"(d[7]),
      "+f"(d[8]), "+f"(d[9]), "+f"(d[10]), "+f"(d[11]), "+f"(d[12]), "+f"(d[13]), "+f"(d[14]), "+f"(d[15]),
      "+f"(d[16]), "+f"(d[17]), "+f"(d[18]), "+f"(d[19]), "+f"(d[20]), "+f"(d[21]), "+f"(d[22]), "+f"(d[23]),
      "+f"(d[24]), "+f"(d[25]), "+f"(d[26]), "+f"(d[27]), "+f"(d[28]), "+f"(d[29]), "+f"(d[30]), "+f"(d[31]),
      "+f"(d[32]), "+f"(d[33]), "+f"(d[34]), "+f"(d[35]), "+f"(d[36]), "+f"(d[37]), "+f"(d[38]), "+f"(d[39]),
      "+f"(d[40]), "+f"(d[41]), "+f"(d[42]), "+f"(d[43]), "+f"(d[44]), "+f"(d[45]), "+f"(d[46]), "+f"(d[47]),
      "+f"(d[48]), "+f"(d[49]), "+f"(d[50]), "+f"(d[51]), "+f"(d[52]), "+f"(d[53]), "+f"(d[54]), "+f"(d[55]),
      "+f"(d[56]), "+f"(d[57]), "+f"(d[58]), "+f"(d[59]), "+f"(d[60]), "+f"(d[61]), "+f"(d[62]), "+f"(d[63])
    : "l"(da), "l"(db), "r"(scale_d));
}

__device__ __forceinline__ void wg64_rs_bf16(float (&d)[32], uint32_t a0, uint32_t a1, uint32_t a2, uint32_t a3, uint64_t db, int scale_d) {
  asm volatile("{\n.reg .pred p;\nsetp.ne.b32 p, %37, 0;\n"
    "wgmma.mma_async.sync.aligned.m64n64k16.f32.bf16.bf16 "
    "{%0, %1, %2, %3, %4, %5, %6, %7, %8, %9, %10, %11, %12, %13, %14, %15,"
    "%16, %17, %18, %19, %20, %21, %22, %23, %24, %25, %26, %27, %28, %29, %30, %31}, "
    "{%32, %33, %34, %35}, %36, p, 1, 1, 0;\n}\n"
    : "+f"(d[0]), "+f"(d[1]), "+f"(d[2]), "+f"(d[3]), "+f"(d[4]), "+f"(d[5]), "+f"(d[6]), "+f"(d[7]),
      "+f"(d[8]), "+f"(d[9]), "+f"(d[10]), "+f"(d[11]), "+f"(d[12]), "+f"(d[13]), "+f"(d[14]), "+f"(d[15]),
      "+f"(d[16]), "+f"(d[17]), "+f"(d[18]), "+f"(d[19]), "+f"(d[20]), "+f"(d[21]), "+f"(d[22]), "+f"(d[23]),
      "+f"(d[24]), "+f"(d[25]), "+f"(d[26]), "+f"(d[27]), "+f"(d[28]), "+f"(d[29]), "+f"(d[30]), "+f"(d[31])
    : "r"(a0), "r"(a1), "r"(a2), "r"(a3), "l"(db), "r"(scale_d));
}

__device__ __forceinline__ void wg24_rs_f16_t(float (&d)[12], uint32_t a0, uint32_t a1, uint32_t a2, uint32_t a3, uint64_t db, int scale_d) {
  asm volatile("{\n.reg .pred p;\nsetp.ne.b32 p, %17, 0;\n"
    "wgmma.mma_async.sync.aligned.m64n24k16.f32.f16.f16 "
    "{%0, %1, %2, %3, %4, %5, %6, %7, %8, %9, %10, %11}, "
    "{%12, %13, %14, %15}, %16, p, 1, 1, 1;\n}\n"
    : "+f"(d[0]), "+f"(d[1]), "+f"(d[2]), "+f"(d[3]), "+f"(d[4]), "+f"(d[5]), "+f"(d[6]), "+f"(d[7]),
      "+f"(d[8]), "+f"(d[9]), "+f"(d[10]), "+f"(d[11])
    : "r"(a0), "r"(a1), "r"(a2), "r"(a3), "l"(db), "r"(scale_d));
}

__device__ __forceinline__ void wg24_rs_bf16(float (&d)[12], uint32_t a0, uint32_t a1, uint32_t a2, uint32_t a3, uint64_t db, int scale_d) {
  asm volatile("{\n.reg .pred p;\nsetp.ne.b32 p, %17, 0;\n"
    "wgmma.mma_async.sync.aligned.m64n24k16.f32.bf16.bf16 "
    "{%0, %1, %2, %3, %4, %5, %6, %7, %8, %9, %10, %11}, "
    "{%12, %13, %14, %15}, %16, p, 1, 1, 0;\n}\n"
    : "+f"(d[0]), "+f"(d[1]), "+f"(d[2]), "+f"(d[3]), "+f"(d[4]), "+f"(d[5]), "+f"(d[6]), "+f"(d[7]),
      "+f"(d[8]), "+f"(d[9]), "+f"(d[10]), "+f"(d[11])
    : "r"(a0), "r"(a1), "r"(a2), "r"(a3), "l"(db), "r"(scale_d));
}

__device__ __forceinline__ void wg24_ss_bf16_tt(float (&d)[12], uint64_t da, uint64_t db, int scale_d) {
  asm volatile("{\n.reg .pred p;\nsetp.ne.b32 p, %14, 0;\n"
    "wgmma.mma_async.sync.aligned.m64n24k16.f32.bf16.bf16 "
    "{%0, %1, %2, %3, %4, %5, %6, %7, %8, %9, %10, %11}, "
    "%12, %13, p, 1, 1, 1, 1;\n}\n"
    : "+f"(d[0]), "+f"(d[1]), "+f"(d[2]), "+f"(d[3]), "+f"(d[4]), "+f"(d[5]), "+f"(d[6]), "+f"(d[7]),
      "+f"(d[8]), "+f"(d[9]), "+f"(d[10]), "+f"(d[11])
    : "l"(da), "l"(db), "r"(scale_d));
}

__device__ __forceinline__ void wg64_rs_bf16_i(float (&d)[32], uint32_t a0, uint32_t a1, uint32_t a2, uint32_t a3, uint64_t db) {
  asm volatile("{\n.reg .pred p;\nsetp.ne.b32 p, 0, 0;\n"
    "wgmma.mma_async.sync.aligned.m64n64k16.f32.bf16.bf16 "
    "{%0, %1, %2, %3, %4, %5, %6, %7, %8, %9, %10, %11, %12, %13, %14, %15,"
    "%16, %17, %18, %19, %20, %21, %22, %23, %24, %25, %26, %27, %28, %29, %30, %31}, "
    "{%32, %33, %34, %35}, %36, p, 1, 1, 0;\n}\n"
    : "=f"(d[0]), "=f"(d[1]), "=f"(d[2]), "=f"(d[3]), "=f"(d[4]), "=f"(d[5]), "=f"(d[6]), "=f"(d[7]),
      "=f"(d[8]), "=f"(d[9]), "=f"(d[10]), "=f"(d[11]), "=f"(d[12]), "=f"(d[13]), "=f"(d[14]), "=f"(d[15]),
      "=f"(d[16]), "=f"(d[17]), "=f"(d[18]), "=f"(d[19]), "=f"(d[20]), "=f"(d[21]), "=f"(d[22]), "=f"(d[23]),
      "=f"(d[24]), "=f"(d[25]), "=f"(d[26]), "=f"(d[27]), "=f"(d[28]), "=f"(d[29]), "=f"(d[30]), "=f"(d[31])
    : "r"(a0), "r"(a1), "r"(a2), "r"(a3), "l"(db));
}

__device__ __forceinline__ void wg24_rs_bf16_i(float (&d)[12], uint32_t a0, uint32_t a1, uint32_t a2, uint32_t a3, uint64_t db) {
  asm volatile("{\n.reg .pred p;\nsetp.ne.b32 p, 0, 0;\n"
    "wgmma.mma_async.sync.aligned.m64n24k16.f32.bf16.bf16 "
    "{%0, %1, %2, %3, %4, %5, %6, %7, %8, %9, %10, %11}, "
    "{%12, %13, %14, %15}, %16, p, 1, 1, 0;\n}\n"
    : "=f"(d[0]), "=f"(d[1]), "=f"(d[2]), "=f"(d[3]), "=f"(d[4]), "=f"(d[5]), "=f"(d[6]), "=f"(d[7]),
      "=f"(d[8]), "=f"(d[9]), "=f"(d[10]), "=f"(d[11])
    : "r"(a0), "r"(a1), "r"(a2), "r"(a3), "l"(db));
}

__device__ __forceinline__ void wg24_ss_bf16_tt_i(float (&d)[12], uint64_t da, uint64_t db) {
  asm volatile("{\n.reg .pred p;\nsetp.ne.b32 p, 0, 0;\n"
    "wgmma.mma_async.sync.aligned.m64n24k16.f32.bf16.bf16 "
    "{%0, %1, %2, %3, %4, %5, %6, %7, %8, %9, %10, %11}, "
    "%12, %13, p, 1, 1, 1, 1;\n}\n"
    : "=f"(d[0]), "=f"(d[1]), "=f"(d[2]), "=f"(d[3]), "=f"(d[4]), "=f"(d[5]), "=f"(d[6]), "=f"(d[7]),
      "=f"(d[8]), "=f"(d[9]), "=f"(d[10]), "=f"(d[11])
    : "l"(da), "l"(db));
}

__device__ __forceinline__ void wg24_ss_bf16(float (&d)[12], uint64_t da, uint64_t db, int scale_d) {
  asm volatile("{\n.reg .pred p;\nsetp.ne.b32 p, %14, 0;\n"
    "wgmma.mma_async.sync.aligned.m64n24k16.f32.bf16.bf16 "
    "{%0, %1, %2, %3, %4, %5, %6, %7, %8, %9, %10, %11}, "
    "%12, %13, p, 1, 1, 0, 0;\n}\n"
    : "+f"(d[0]), "+f"(d[1]), "+f"(d[2]), "+f"(d[3]), "+f"(d[4]), "+f"(d[5]), "+f"(d[6]), "+f"(d[7]),
      "+f"(d[8]), "+f"(d[9]), "+f"(d[10]), "+f"(d[11])
    : "l"(da), "l"(db), "r"(scale_d));
}

__device__ __forceinline__ void wg24_ss_bf16_i(float (&d)[12], uint64_t da, uint64_t db) {
  asm volatile("{\n.reg .pred p;\nsetp.ne.b32 p, 0, 0;\n"
    "wgmma.mma_async.sync.aligned.m64n24k16.f32.bf16.bf16 "
    "{%0, %1, %2, %3, %4, %5, %6, %7, %8, %9, %10, %11}, "
    "%12, %13, p, 1, 1, 0, 0;\n}\n"
    : "=f"(d[0]), "=f"(d[1]), "=f"(d[2]), "=f"(d[3]), "=f"(d[4]), "=f"(d[5]), "=f"(d[6]), "=f"(d[7]),
      "=f"(d[8]), "=f"(d[9]), "=f"(d[10]), "=f"(d[11])
    : "l"(da), "l"(db));
}

constexpr int P1_STB = 49152, P3_STB = 40960;
constexpr int SM_X = 196608;
constexpr int SM_KVB = SM_X + 24576;
constexpr int SM_GW = SM_X + 8192, SM_WRAW = SM_GW + 1280, SM_EP = SM_WRAW + 800;
constexpr int SM_CONST = SM_X + 32768, SM_WPHI = SM_CONST + 1024, SM_BAR = SM_WPHI + 1536;
constexpr int SMEM_BYTES = SM_BAR + 512;
constexpr int B_FULL = 0, B_AUX = 4, B_KB = 5, B_QB = 6, B_KVFULL = 7, B_P3FULL = 11, B_P3EMPTY = 15, B_EMPTY = 19, B_LINK = 23, B_FREE = 25,
              B_STG = 28, B_B2 = 29, B_ZERO = 30, B_READY = 31, B_KVB = 35;

template <int V> struct Int { static constexpr int value = V; };
struct Maps { CUtensorMap x, w[2], wo[2], out, qld, qst; };

__device__ __forceinline__ int tile_atom(int t) { return (t >> 2) * 15 + ((0xB740 >> ((t & 3) * 4)) & 15); }

template <int MODE, int A>
__device__ __forceinline__ void pack_atom(const float (&acc)[64], uint32_t (&r)[32], float s0, float s1, uint32_t& m0, uint32_t& m1) {
#pragma unroll
  for (int e = A * 16; e < A * 16 + 16; e++) {
    const float s = (e & 1) ? s1 : s0;
    if (MODE == 0) r[e] = pack_bf16(acc[2 * e], acc[2 * e + 1]);
    else if (MODE == 3) r[e] = pack_f16(acc[2 * e], acc[2 * e + 1]);
    else r[e] = pack_bf16(acc[2 * e] * s, acc[2 * e + 1] * s);
    if (MODE == 2) { if (e & 1) m1 = maxabs_bf16x2(m1, r[e]); else m0 = maxabs_bf16x2(m0, r[e]); }
  }
}
template <int A>
__device__ __forceinline__ void pack_atom_a(const float (&acc)[64], uint32_t (&r)[32], int ga, float sk0, float sk1, uint32_t& m0, uint32_t& m1) {
  if (ga < 10) { const float cq = __uint_as_float(463809372u); pack_atom<1, A>(acc, r, cq, cq, m0, m1); }
  else if (ga < 20) pack_atom<2, A>(acc, r, sk0, sk1, m0, m1);
  else pack_atom<3, A>(acc, r, 0.f, 0.f, m0, m1);
}

__device__ __forceinline__ uint32_t exp2_pair(float a, float b) {
  uint32_t z, w, h;
  asm volatile("cvt.pack.sat.s16.s32 %0, %2, %1;" : "=r"(z) : "r"(__float_as_uint(a)), "r"(__float_as_uint(b)));
  asm volatile("lop3.b32 %0, %1, 0x03ff03ff, 0x34003400, 0xEA;" : "=r"(w) : "r"(z));
  asm volatile("fma.rn.f16x2 %0, %1, %1, %2;" : "=r"(h) : "r"(w), "r"(0x36203620));
  asm volatile("fma.rn.f16x2 %0, %0, %1, %2;" : "+r"(h) : "r"(w), "r"(0x2e012e01));
  return h + z - w;
}
__device__ __forceinline__ uint32_t exp2_pair_mufu(float a, float b) {
  float x, y; uint32_t r;
  asm volatile("ex2.approx.ftz.f32 %0, %1;" : "=f"(x) : "f"(a));
  asm volatile("ex2.approx.ftz.f32 %0, %1;" : "=f"(y) : "f"(b));
  asm volatile("cvt.rn.f16x2.f32 %0, %1, %2;" : "=r"(r) : "f"(y), "f"(x));
  return r;
}
__device__ __forceinline__ void load_frag(uint32_t (&a)[6], const uint8_t* p) {
  a[0] = ldcg32(p); a[1] = ldcg32(p + 128); a[2] = ldcg32(p + 2048); a[3] = ldcg32(p + 2048 + 128); a[4] = ldcg32(p + 4096); a[5] = ldcg32(p + 4096 + 128);
}
template <bool EXACT>
__device__ __forceinline__ bool feature_rows(uint32_t (&phi)[10], const float (&p)[12]) {
  const float L = 1.4426950408889634f;
  bool ok = true;
#pragma unroll
  for (int r = 0; r < 2; r++) {
    const float v[5] = {p[2 * r], p[2 * r + 1], p[4 + 2 * r], p[5 + 2 * r], p[8 + 2 * r]};
    float ep[5], en[5];
    if (EXACT) {
      float mx = fmaxf(fmaxf(fmaxf(v[0], v[1]), fmaxf(v[2], v[3])), v[4]);
      float mn = fminf(fminf(fminf(v[0], v[1]), fminf(v[2], v[3])), v[4]);
      mx = fmaxf(mx, __shfl_xor_sync(0xffffffffu, mx, 1)); mn = fminf(mn, __shfl_xor_sync(0xffffffffu, mn, 1));
      mx = fmaxf(mx, __shfl_xor_sync(0xffffffffu, mx, 2)); mn = fminf(mn, __shfl_xor_sync(0xffffffffu, mn, 2));
#pragma unroll
      for (int i = 0; i < 5; i++) { ep[i] = ex2((v[i] - mx) * L); en[i] = ex2((mn - v[i]) * L); }
    } else {
#pragma unroll
      for (int i = 0; i < 5; i++) { const float u = v[i] * L; ep[i] = ex2(u); en[i] = ex2n(u); }
    }
    float sp = (ep[0] + ep[1]) + (ep[2] + ep[3]) + ep[4], sn = (en[0] + en[1]) + (en[2] + en[3]) + en[4];
    sp += __shfl_xor_sync(0xffffffffu, sp, 1); sn += __shfl_xor_sync(0xffffffffu, sn, 1);
    sp += __shfl_xor_sync(0xffffffffu, sp, 2); sn += __shfl_xor_sync(0xffffffffu, sn, 2);
    ok = ok && sp + sn < 1.2676506e30f;
    const float rp = rcp(sp), rn = rcp(sn);
#pragma unroll
    for (int i = 0; i < 5; i++) phi[5 * r + i] = pack_bf16(ep[i] * rp, en[i] * rn);
  }
  return ok;
}
__device__ __forceinline__ void feature_map(uint32_t (&phi)[10], const float (&p)[12]) {
  if (!__all_sync(0xffffffffu, feature_rows<false>(phi, p))) feature_rows<true>(phi, p);
}
__device__ __forceinline__ void phi_proj(float (&p0)[12], float (&p1)[12], uint32_t a, uint64_t dw) {
  const uint64_t da = mkdesc(a, 1024, 128, 0), db = mkdesc(a + 2048, 0, 128, 0);
  WG_FENCE();
  wg24_ss_bf16_i(p0, da, dw);
  wg24_ss_bf16(p0, db, dw + 48, 1);
  wg24_ss_bf16_i(p1, da + 384, dw);
  wg24_ss_bf16(p1, db + 384, dw + 48, 1);
  WG_COMMIT();
  WG_WAIT(0);
  pin(p0); pin(p1);
}
__device__ __forceinline__ void stage_o(const float (&o)[12], float s0, float s1, uint32_t a, bool v0, bool v2) {
#pragma unroll
  for (int j = 0; j < 3; j++) {
    const bool v = j == 1 || (j == 0 ? v0 : v2);
    sts32(a + j * 2048, v ? pack_bf16(o[4 * j] * s0, o[4 * j + 1] * s0) : 0u);
    sts32(a + j * 2048 + 128, v ? pack_bf16(o[4 * j + 2] * s1, o[4 * j + 3] * s1) : 0u);
  }
}
__device__ __forceinline__ void flush_o(bool p, uint8_t* dst, uint32_t src, bool odd) {
  bulk_s2g_if(p, dst + (odd ? 2048 : 0), src + (odd ? 2048 : 0), 4096);
  bulk_or_if(p, dst + (odd ? 0 : 4096), src + (odd ? 0 : 4096), 2048);
  BULK_COMMIT();
}

__device__ __forceinline__ void proj20(float (&acc)[20], const __nv_bfloat16* __restrict__ xr, const __nv_bfloat16* __restrict__ wc) {
#pragma unroll
  for (int d = 0; d < 20; d++) acc[d] = 0.f;
#pragma unroll 2
  for (int k = 0; k < 640; k++) {
    const float xv = __bfloat162float(xr[k]);
#pragma unroll
    for (int d = 0; d < 10; d++) {
      const uint32_t u = ldg32(wc + k * 1920 + 2 * d);
      acc[2 * d] = fmaf(xv, __uint_as_float(u << 16), acc[2 * d]);
      acc[2 * d + 1] = fmaf(xv, __uint_as_float(u & 0xffff0000u), acc[2 * d + 1]);
    }
  }
}
__device__ __noinline__ void attn_exact(const __nv_bfloat16* __restrict__ x, const __nv_bfloat16* __restrict__ wqkv, int h, int qt, uint32_t stg) {
  const int tid = threadIdx.x;
  uint32_t* kvs = g_fb + blockIdx.x * (2048 * 20);
  float a[20];
  for (int i = 0; i < 8; i++) {
    const int key = (i >> 1) * 512 + tid, ty = 1 + (i & 1);
    proj20(a, x + key * 640, wqkv + ty * 640 + h * 20);
#pragma unroll
    for (int d = 0; d < 10; d++) kvs[key * 20 + (i & 1) * 10 + d] = pack_bf16(a[2 * d], a[2 * d + 1]);
  }
  const int row = qt * 512 + tid;
  proj20(a, x + row * 640, wqkv + h * 20);
#pragma unroll
  for (int d = 0; d < 20; d++) a[d] = __bfloat162float(__float2bfloat16(a[d]));
  __syncthreads();
  float o[20], m = -INFINITY, l = 0.f;
#pragma unroll
  for (int d = 0; d < 20; d++) o[d] = 0.f;
  for (int key = 0; key < 2048; key++) {
    uint32_t u[20];
#pragma unroll
    for (int d = 0; d < 5; d++) {
      const uint4 t4 = *reinterpret_cast<const uint4*>(kvs + key * 20 + 4 * d);
      u[4 * d] = t4.x; u[4 * d + 1] = t4.y; u[4 * d + 2] = t4.z; u[4 * d + 3] = t4.w;
    }
    float s = 0.f;
#pragma unroll
    for (int d = 0; d < 10; d++) {
      s = fmaf(a[2 * d], __uint_as_float(u[d] << 16), s);
      s = fmaf(a[2 * d + 1], __uint_as_float(u[d] & 0xffff0000u), s);
    }
    s *= 0.22360679774997896f;
    const float mn = fmaxf(m, s), cr = __expf(m - mn), p = __expf(s - mn);
    m = mn;
    l = l * cr + p;
#pragma unroll
    for (int d = 0; d < 10; d++) {
      o[2 * d] = fmaf(p, __uint_as_float(u[10 + d] << 16), o[2 * d] * cr);
      o[2 * d + 1] = fmaf(p, __uint_as_float(u[10 + d] & 0xffff0000u), o[2 * d + 1] * cr);
    }
  }
  const float sc = __ldcg(&g_gate[row]) / l;
#pragma unroll
  for (int d = 0; d < 10; d++) {
    const int col = (h & 1) * 4 + 2 * d;
    sts32(stg + (tid >> 7) * 6144 + (col >> 3) * 2048 + (tid & 127) * 16 + (col & 7) * 2, pack_bf16(o[2 * d] * sc, o[2 * d + 1] * sc));
  }
  PROXY_FENCE();
  __syncthreads();
}

#define COORDS()                                                                                                        \
  int tid, bid;                                                                                                         \
  asm volatile("mov.u32 %0, %%tid.x;" : "=r"(tid));                                                                     \
  asm volatile("mov.u32 %0, %%ctaid.x;" : "=r"(bid));                                                                   \
  const int wg = __shfl_sync(0xffffffffu, tid >> 7, 0);                                                                 \
  const int lane = tid & 31, w = (tid >> 5) & 3, g = lane >> 2, t = lane & 3, wt = tid & 127;                           \
  const int rb1 = bid >> 3, c1 = bid & 7;                                       \
  const int h = bid >> 2, qt = bid & 3, rb = qt * 4 + wg;                    \
  const bool odd = h & 1;                                                                                               \
  const int c0 = (h * 5) >> 1;                                               \
  const int lsrc = (lane & ~3) | (odd ? 0 : 2);                                                                         \
  const bool v0 = !odd || t >= 2, v2 = odd || t < 2;                                                                    \
  const uint32_t ostg = sb + SM_X + wg * 6144, orow = (w * 16 + g) * 16 + t * 4;                                        \
  const uint32_t onepos = (wt >> 6) * 6144 + 3072 + (odd ? 0 : 2048 + 8) + (wt & 63) * 16;                              \
  const int kh = bid & 1, cg = (bid >> 1) & 3, atom3 = (cg >> 1) * 5 + (cg & 1) * 2;                                    \
  auto p3_load_w = [&](bool p, int j) {                                                                                 \
    const uint32_t fb = bar + 8 * (B_P3FULL + (j & 3));                                                                 \
    mbar_expect_if(p, fb, P3_STB);                                                                                      \
    tma3d_if(p, sb + (j & 3) * P3_STB + 16384, &maps.wo[j < 5], (kh * 5 + (j < 5 ? j : j - 5)) * 64, atom3, fb);       \
  };                                                                                                                    \
  auto p3_load_a = [&](bool p, int j) {                                                                                 \
    bulk_g2s_if(p, sb + (j & 3) * P3_STB, g_o + rb1 * ORB + ((j < 5 ? 10 + j : j - 5) + kh * 5) * 16384, 16384,         \
                bar + 8 * (B_P3FULL + (j & 3)));                                                                        \
  };                                                                                                                    \
  (void)g; (void)t; (void)wt; (void)rb1; (void)c1; (void)rb; (void)c0; (void)lsrc; (void)v0; (void)v2; (void)ostg;      \
  (void)orow; (void)onepos; (void)atom3; (void)p3_load_w; (void)p3_load_a

__global__ void __launch_bounds__(512, 1)
gated_mix_kernel(const __grid_constant__ Maps maps, const __nv_bfloat16* __restrict__ x, const __nv_bfloat16* __restrict__ wqkv, const __nv_bfloat16* __restrict__ w_phi,
                 const __nv_bfloat16* __restrict__ gate_w, const void* wqkv_b, const void* wo_a, const void* wo_b, uint4* __restrict__ out) {
  extern __shared__ __align__(1024) uint8_t smem_raw[];
  const uint32_t sb = (uint32_t)__cvta_generic_to_shared(smem_raw);
  const uint32_t bar = sb + SM_BAR;
  uint32_t q[2][6], qc[4], epoch, events;
  int bad;
  {
  COORDS();
  TS_INIT();

  auto p1_load = [&](bool p, int it) {
    const int st = it & 3, br = it >= 10, ks = it - br * 10;
    const uint32_t dst = sb + st * P1_STB, fb = bar + 8 * (B_FULL + st);
    mbar_expect_if(p, fb, P1_STB);
    tma2d_if(p, dst, &maps.x, ks * 64, rb1 * 128, fb);
    tma3d_if(p, dst + 16384, &maps.w[br], ks * 64, tile_atom(c1 ^ br), fb);
  };
  if (wt == 0) {
    mbar_init(bar + 8 * (B_FULL + wg), 1);
    asm volatile("fence.mbarrier_init.release.cluster;" ::: "memory");
    if (wg == 0) p1_load(true, 0);
  }
  TS_REG(tsa_);
  if (wt == 32) {
#pragma unroll
    for (int u = 0; u < 4; u++)
      if (wg == u) {
#pragma unroll
        for (int i = B_AUX + u * 8; i < B_AUX + u * 8 + 8; i++)
          mbar_init(bar + 8 * i, i == B_AUX ? 3 : i < B_P3EMPTY ? 1 : i < B_EMPTY ? 2 : i < B_ZERO ? 4 : i == B_ZERO ? 16 : i < B_READY + 2 ? 512 : 128);
      }
    asm volatile("fence.mbarrier_init.release.cluster;" ::: "memory");
  }
  TS_REG(tsb_);
  TS_REG(tsc_);
  asm volatile("st.shared.v4.b32 [%0], {%1, %1, %1, %1};" ::"r"(sb + SM_X + tid * 16), "r"(0) : "memory");
  if (tid < 256) sts32(sb + SM_CONST + tid * 4, (tid & 3) ? 0u : ((tid >> 5) < NMB ? 0xdd02e192u : 0x00001ef0u));
  PROXY_FENCE();
  TS_REG(tsd_);
  __syncthreads();
  if (wg > 0) p1_load(wt == 0, wg);
  if (wt == 64) {
    if (wg == 1) { mbar_expect_if(true, bar + 8 * B_AUX, 1280); bulk_g2s_if(true, sb + SM_GW, gate_w, 1280, bar + 8 * B_AUX); }
    if (wg == 2) { mbar_expect_if(true, bar + 8 * B_AUX, 800); bulk_g2s_if(true, sb + SM_WRAW, w_phi + h * 400, 800, bar + 8 * B_AUX); }
    if (wg == 3) { mbar_expect_if(true, bar + 8 * B_AUX, 16); bulk_g2s_if(true, sb + SM_EP, &g_cnt[C_EPOCH], 16, bar + 8 * B_AUX); }
  }
  TS_FIRST();

  {
    float acc[64];
    const int r = wg & 1, ch = wg >> 1;
    const bool mufu0 = 2 * w < NMB, mufu1 = 2 * w + 1 < NMB;
    uint32_t pk[32];
    float gs = 0.f;
    const int grow = c1 * 16 + (tid >> 5);
    auto stage = [&](uint32_t stg, int e0) {
#pragma unroll
      for (int e = 0; e < 16; e += 4) stsm4(stg + (w * 16 + (lane & 15)) * 16 + (lane >> 4) * 1024 + e * 512, pk[e0 + e], pk[e0 + e + 1], pk[e0 + e + 2], pk[e0 + e + 3]);
    };
    auto release = [&](int it) {
      mbar_arrive_if(wt == 0, bar + 8 * (B_EMPTY + (it & 3)));
      if (wg == 3 && it < 16) {
        mbar_wait(bar + 8 * (B_EMPTY + (it & 3)), (it >> 2) & 1);
        p1_load(wt == 0, it + 4);
      }
    };
    auto duties = [&](auto BR, int it, int ga0, bool narrow_a) {
      constexpr int br = decltype(BR)::value;
      if (br == 0 && wg == 0 && it >= 1 && it <= 4) {
        const bool p = wt == 0;
        if (it < 4) bulk_s2g_if(p, reinterpret_cast<uint8_t*>(out) + bid * 20480 + (it - 1) * 8192, sb + SM_X, it == 3 ? 4096 : 8192);
        else bulk_s2g_if(p, g_kv + bid * 240, sb + SM_X, 960);
        bulk_s2g_if(p, g_o + rb1 * ORB + ((c1 * 4 + it - 1) * 5 + 2) * 2048, sb + SM_X, 2048);
        BULK_COMMIT();
      }
      if (br == 0 && it == 2 && wg == 1 && wt < 3) {
        const int bytes = wt == 0 ? 19200 : 6400;
        const uint8_t* p = reinterpret_cast<const uint8_t*>(wt == 0 ? wqkv_b : wt == 1 ? wo_a : wo_b) + bid * bytes;
        asm volatile("cp.async.bulk.prefetch.L2.global [%0], %1;" ::"l"(p), "r"(bytes) : "memory");
      }
      if (br == 0 && it == 4) {
        epoch = (lds32(sb + SM_EP) >> 7) + 1;
#pragma unroll
        for (int u = 0; u < 2; u++) {
          const int i = tid + u * 512, k = i / 24, n = i % 24, ii = 2 * (n >> 3) + (n & 1), f = 4 * ii + ((n & 7) >> 1), d = k - (odd ? 4 : 0);
          uint16_t v = 0;
          if (d >= 0 && d < 20 && ii < 5) asm volatile("ld.shared.u16 %0, [%1];" : "=h"(v) : "r"(sb + SM_WRAW + (d * 20 + f) * 2) : "memory");
          if (i < 768) sts16(sb + SM_WPHI + (k >> 3) * 384 + n * 16 + (k & 7) * 2, v);
        }
      }
      if (br == 0 && it == 6 && wg == 0) BULK_WAIT_READ();
      if (br == 1 && (it == 10 + ch || it == 12 + ch)) {
        const int u = it >= 12;
        if (!u) {
          mbar_wait(bar + 8 * B_ZERO, 0);
          stage(sb + SM_X + wg * 8192, 0);
        } else {
          BULK_WAIT_READ();
          bar_sync(1 + wg, 128);
          stage(sb + SM_X + wg * 8192, 16);
        }
        PROXY_FENCE();
        bar_sync(1 + wg, 128);
        tma5d_store_if(wt == 0 && !(u && narrow_a), &maps.qst, sb + SM_X + wg * 8192, ((ga0 + u) % 10) * 8, (ga0 + u) / 10, wg & 1, rb1);
        bulk_s2g_if(wt == 0 && u, g_gate + rb1 * 128 + c1 * 16 + wg * 4, sb + SM_BAR + 448 + wg * 16, 16);
        BULK_COMMIT();
      }
      if (br == 1 && it == 11 - ch) {
#pragma unroll
        for (int o = 16; o; o >>= 1) gs += __shfl_xor_sync(0xffffffffu, gs, o);
        if (lane == 0) sts32(sb + SM_BAR + 448 + (tid >> 5) * 4, __float_as_uint(rcp(1.f + ex2(gs * -1.4426950408889634f))));
      }
      if (br == 1 && it == 15) signal_bulk_if(wt == 0, &g_cnt[C_TA]);
      if (br == 1 && it >= 17 && it <= 18 && wg == it - 17) {
        wait_count(&g_cnt[C_TA], epoch * 512);
        mbar_wait(bar + 8 * (B_EMPTY + (it - 17)), 0);
        mbar_expect_if(wt == 0, bar + 8 * (B_KVFULL + it - 17), P1_STB);
        tma5d_if(wt == 0, sb + (it - 17) * P1_STB, &maps.qld, c0, 1, (it - 17) * 4, bar + 8 * (B_KVFULL + it - 17));
      }
      if (br == 1 && it == 19) {
        mbar_wait(bar + 8 * (B_KVFULL + 0), 0);
        const uint8_t* qp = g_qkv + rb * QRB + c0 * 2048 + orow;
        load_frag(q[0], qp);
        load_frag(q[1], qp + 1024);
        bad = ldcg32(&g_kbad);
        sts16(sb + wg * 12288 + onepos, 0x3c00);
        PROXY_FENCE();
        mbar_arrive(bar + 8 * (B_READY + 0));
      }
    };
    const int ga_a = tile_atom(c1) + 2 * ch + (((c1 & 3) == 2 && wg == 0) ? 1 : 0);
    const bool narrow_a = ((c1 & 3) == 1 && wg == 3) || ((c1 & 3) == 2 && wg == 0);
    uint32_t xh[3] = {0u, 0u, 0u};
    auto gate_fma = [&](uint32_t a, int ks) {
      const uint32_t b = lds32(sb + SM_GW + ks * 128 + lane * 4);
      gs = fmaf(__uint_as_float(a << 16), __uint_as_float(b << 16), gs);
      gs = fmaf(__uint_as_float(a & 0xffff0000u), __uint_as_float(b & 0xffff0000u), gs);
    };
    auto gate_step = [&](uint32_t dst, int ks) {
      const uint32_t a = lds32(dst + grow * 128 + (((lane >> 2) ^ (grow & 7)) << 4) + t * 4);
      if (ks < 3) { xh[0] = xh[1]; xh[1] = xh[2]; xh[2] = a; }
      else {
        if (ks == 3) { mbar_wait(bar + 8 * B_AUX, 0); gate_fma(xh[0], 0); gate_fma(xh[1], 1); gate_fma(xh[2], 2); }
        gate_fma(a, ks);
      }
      __syncwarp();
      mbar_arrive_if(ks == 9 && lane == 0, bar + 8 * B_ZERO);
    };
    auto tile = [&](auto BR) {
      constexpr int br = decltype(BR)::value;
      const int tl = c1 ^ br, k4 = tl & 3;
      const bool narrow = (k4 == 1 && wg == 3) || (k4 == 2 && wg == 0);
      const int a0 = 2 * ch + ((k4 == 2 && wg == 0) ? 1 : 0);
      if (!narrow) {
#pragma unroll 1
        for (int ks = 0; ks < 10; ks++) {
          const int it = br * 10 + ks, st = it & 3;
          mbar_wait(bar + 8 * (B_FULL + st), (it >> 2) & 1);
          TS_MARK(20 + it);
          const uint32_t dst = sb + st * P1_STB;
          const uint64_t da = mkdesc(dst + r * 8192, 16, 1024, 1), db = mkdesc(dst + 16384 + a0 * 8192, 8192, 1024, 1);
          bar_sync(5 + wg, 256);
          WG_FENCE();
#pragma unroll
          for (int k = 0; k < 4; k++) wg128_ss(acc, da + k * 2, db + k * 128, (ks | k) != 0);
          WG_COMMIT();
          if (it < 19 || wg < 3) bar_arrive(5 + ((wg + 1) & 3), 256);
          if (br == 0) gate_step(dst, ks);
          WG_WAIT(1);
          if (ks > 0) release(it - 1);
          duties(BR, it, ga_a, narrow_a);
        }
        WG_WAIT(0);
      } else {
#pragma unroll 1
        for (int ks = 0; ks < 10; ks++) {
          const int it = br * 10 + ks, st = it & 3;
          mbar_wait(bar + 8 * (B_FULL + st), (it >> 2) & 1);
          TS_MARK(20 + it);
          const uint32_t dst = sb + st * P1_STB;
          const uint64_t da = mkdesc(dst + r * 8192, 16, 1024, 1), db = mkdesc(dst + 16384 + a0 * 8192, 8192, 1024, 1);
          bar_sync(5 + wg, 256);
          WG_FENCE();
#pragma unroll
          for (int k = 0; k < 4; k++) wg64_ss_of64(acc, da + k * 2, db + k * 128, (ks | k) != 0);
          WG_COMMIT();
          if (it < 19 || wg < 3) bar_arrive(5 + ((wg + 1) & 3), 256);
          if (br == 0) gate_step(dst, ks);
          WG_WAIT(1);
          if (ks > 0) release(it - 1);
          duties(BR, it, ga_a, narrow_a);
        }
        WG_WAIT(0);
      }
      pin(acc);
      TS_MARK(2 + 2 * br);
      release(br * 10 + 9);
      const int ga0 = tile_atom(tl) + a0;
      uint32_t m0 = 0, m1 = 0;
      if (br == 0) {
        const float sk0 = __uint_as_float(mufu0 ? (127u + 70u) << 23 : (127u - 69u) << 23);
        const float sk1 = __uint_as_float(mufu1 ? (127u + 70u) << 23 : (127u - 69u) << 23);
        pack_atom_a<0>(acc, pk, ga0, sk0, sk1, m0, m1);
        if (!narrow) pack_atom_a<1>(acc, pk, ga0 + 1, sk0, sk1, m0, m1);
        const uint32_t lim0 = (mufu0 ? 127u + 110u : 127u - 29u) << 7, lim1 = (mufu1 ? 127u + 110u : 127u - 29u) << 7;
        if ((m0 & 0x7fffu) >= lim0 || ((m0 >> 16) & 0x7fffu) >= lim0 || (m1 & 0x7fffu) >= lim1 || ((m1 >> 16) & 0x7fffu) >= lim1) { g_kbad = epoch; __threadfence(); }
      } else {
        pack_atom<0, 0>(acc, pk, 0.f, 0.f, m0, m1);
        pack_atom<0, 1>(acc, pk, 0.f, 0.f, m0, m1);
        if (ch) mbar_wait(bar + 8 * (B_EMPTY + 2), 0);
        const uint32_t stg = sb + (ch ? 2 * P1_STB : SM_X) + r * 16384;
        stage(stg, 0);
        stage(stg + 8192, 16);
        mbar_wait(bar + 8 * (B_KVFULL + 1), 0);
        sts16(sb + P1_STB + wg * 12288 + onepos, 0x3c00);
        PROXY_FENCE();
        mbar_arrive(bar + 8 * (B_READY + 1));
        bar_sync(1 + wg, 128);
        tma5d_store_if(wt == 0, &maps.qst, stg, (ga0 % 10) * 8, ga0 / 10, r, 16 + rb1);
        tma5d_store_if(wt == 32 * 0 && !narrow, &maps.qst, stg + 8192, ((ga0 + 1) % 10) * 8, (ga0 + 1) / 10, r, 16 + rb1);
        BULK_COMMIT();
      }
      TS_MARK(3 + 2 * br);
    };
    if (wg == 3) bar_arrive(5, 256);
    tile(Int<0>{});
    tile(Int<1>{});
  }

  if (odd ? t < 2 : t >= 2) {
    if (odd) { q[0][0] = 0; q[0][1] = 0; q[1][0] = 0; q[1][1] = 0; }
    else { q[0][4] = 0; q[0][5] = 0; q[1][4] = 0; q[1][5] = 0; }
  }
  {
    uint32_t m = 0;
#pragma unroll
    for (int i = 0; i < 6; i++) m = maxabs_bf16x2(m, maxabs_bf16x2(q[0][i], q[1][i]));
    bad = bad == (int)epoch || (m & 0x7fffu) >= ((127u - 50u) << 7) || ((m >> 16) & 0x7fffu) >= ((127u - 50u) << 7);
  }
#pragma unroll
  for (int i = 0; i < 4; i++) { qc[i] = t == 0 ? 0x1c801c80u : 0u; asm volatile("" : "+r"(qc[i])); }
  events = 0x01010140u | (0x2008000u >> (2 * wg)) | (wg == 0 ? 0x8000480u : wg == 1 ? 0x40000u : wg == 2 ? 0x20000000u : 0x420000u);
  mbar_wait(bar + 8 * (B_READY + 0), 0);
  }
  float o[2][12];
#pragma unroll
  for (int i = 0; i < 12; i++) { o[0][i] = 0.f; o[1][i] = 0.f; }
  {
    uint32_t dk0 = (uint32_t)mkdesc(sb, 1024, 0, 0), dk1 = (uint32_t)mkdesc(sb + 2048, SM_CONST - 2048, 0, 0), dv = (uint32_t)mkdesc(sb + 3072, 128, 0, 0);
    TS_MARK(6);
#pragma unroll 1
    for (int i = 0; i < 32; i++) {
      if ((events >> i) & 1) {
        if ((i & 7) == 0 || i == 6 || i == 27) {
          COORDS();
          const bool p = wt == 0;
          signal_bulk_if(p && i != 8 && (i != 24 || wg != 0), &g_cnt[i == 6 ? C_TB : i == 16 ? C_KV + h : C_OB + rb * 2 + (h >> 4)]);
          if (i == 6) mbar_arrive_if(p, bar + 8 * B_STG);
          if ((i & 7) == 0) {
            WG_WAIT(0);
            mbar_arrive_if(p, bar + 8 * (B_FREE - 1) + i);
            mbar_wait(bar + 8 * B_READY + i, 0);
          }
        } else if (i == 7 || i == 10 || i == 17 || i == 22 || i == 29) {
          COORDS();
          const bool p = lane == 0;
          if (i == 7) {
            mbar_wait(bar + 8 * B_STG, 0);
            if (w == 1) wait_count(&g_cnt[C_TB], epoch * 512);
            const uint32_t fb = bar + 8 * (w ? B_KB : B_KVFULL + 2);
            mbar_expect_if(p && w < 2, fb, P1_STB);
            tma5d_if(p && w < 2, sb + (2 + w) * P1_STB, &maps.qld, c0, 1, w ? 16 + qt * 4 : 8, fb);
          } else if (i == 29) {
            mbar_wait(bar + 8 * (B_FREE + 2), 0);
            mbar_wait(bar + 8 * B_B2, 0);
            p3_load_w(p && w < 3, w);
            wait_count(&g_cnt[C_OB + rb1 * 2 + kh], epoch * 16);
            p3_load_a(p && w < 3, w);
          } else {
            if (i != 22) {
              const int u = i == 17;
              const uint32_t fb = bar + 8 * (u ? B_KVFULL + 3 : B_QB);
              mbar_wait(bar + 8 * (B_FREE + u), 0);
              mbar_expect_if(wt == 0, fb, P1_STB);
              tma5d_if(wt == 0, sb + u * 3 * P1_STB, &maps.qld, c0, u, u ? 12 : 16 + qt * 4, fb);
            }
            if (i != 17) {
              const int u = i == 10 ? 2 : 3;
              mbar_wait(bar + 8 * (B_KVFULL + u), 0);
#pragma unroll
              for (int e = 0; e < 4; e++) sts16(sb + u * P1_STB + e * 12288 + onepos, 0x3c00);
              PROXY_FENCE();
              mbar_arrive(bar + 8 * (B_READY + u));
            }
          }
        } else if (i < 16) {
          WG_WAIT(0);
          COORDS();
          const uint64_t dw = mkdesc(sb + SM_WPHI, 384, 128, 0);
          TS_MARK(7);
          const uint32_t kb = sb + 3 * P1_STB + wg * 12288, ph = sb + SM_X + (wg & 1) * 10240;
          mbar_wait(bar + 8 * B_KB, 0);
          sts16(kb + onepos, 0x3f80);
          float p0[12], p1[12];
          phi_proj(p0, p1, kb, dw);
          if (wg < 2) mbar_wait(bar + 8 * (B_LINK + wg), 0);
          uint32_t phi[10];
          feature_map(phi, p0);
#pragma unroll
          for (int u = 0; u < 10; u++) sts32(ph + (u % 5) * 2048 + orow + (u / 5) * 128, phi[u]);
          feature_map(phi, p1);
#pragma unroll
          for (int u = 0; u < 10; u++) sts32(ph + (u % 5) * 2048 + orow + (u / 5) * 128 + 1024, phi[u]);
          PROXY_FENCE();
          bar_sync(1 + wg, 128);
          const uint64_t da = mkdesc(ph, 128, 2048, 0), db = mkdesc(kb + 3072, 128, 1024, 0);
          WG_FENCE();
#pragma unroll
          for (int kk = 0; kk < 8; kk++) {
            if (kk == 0) wg24_ss_bf16_tt_i(p0, da, db);
            else wg24_ss_bf16_tt(p0, da + kk * 16, db + (kk & 3) * 16 + (kk >> 2) * 384, 1);
          }
          WG_COMMIT();
          WG_WAIT(0);
          pin(p0);
          mbar_arrive_if(lane == 0 && wg >= 2, bar + 8 * (B_LINK + (wg & 1)));
          bar_sync(1 + wg, 128);
          const uint32_t ks = kb + ((w * 16 + g) * 24 + 2 * t) * 4;
#pragma unroll
          for (int j = 0; j < 3; j++) {
            if (w < 3) asm volatile("st.shared.v2.f32 [%0], {%1, %2};" ::"r"(ks + 32 * j), "f"(p0[4 * j]), "f"(p0[4 * j + 1]) : "memory");
            if (w < 2) asm volatile("st.shared.v2.f32 [%0], {%1, %2};" ::"r"(ks + 768 + 32 * j), "f"(p0[4 * j + 2]), "f"(p0[4 * j + 3]) : "memory");
          }
          PROXY_FENCE();
          bar_sync(1 + wg, 128);
          bulk_addf_if(wt == 0, g_kv + h * 960, kb, 3840);
          BULK_COMMIT();
          TS_MARK(8);
        } else if (i == 18) {
          COORDS();
          wait_count(&g_cnt[C_KV + h], epoch * 16);
          float v[8];
#pragma unroll
          for (int u = 0; u < 8; u++) v[u] = (u < 7 || wt < 64) ? __ldcg(&g_kv[h * 960 + u * 128 + wt]) : 0.f;
#pragma unroll
          for (int u = 0; u < 9; u++) {
            const int e = u * 128 + wt, f = e / 24, d = e % 24;
            sts16(sb + SM_KVB + (f >> 3) * 384 + d * 16 + (f & 7) * 2, u < 8 ? __bfloat16_as_ushort(__float2bfloat16(v[u < 8 ? u : 0])) : (uint16_t)0);
          }
          PROXY_FENCE();
          mbar_arrive(bar + 8 * B_KVB);
        } else {
          WG_WAIT(0);
          COORDS();
          const uint64_t dw = mkdesc(sb + SM_WPHI, 384, 128, 0);
          TS_MARK(9);
          float gt[4];
#pragma unroll
          for (int u = 0; u < 4; u++) gt[u] = 1.f - __ldcg(&g_gate[rb * 128 + (u >> 1) * 64 + w * 16 + g + (u & 1) * 8]);
          mbar_wait(bar + 8 * B_QB, 0);
          float p0[12], p1[12];
          phi_proj(p0, p1, sb + wg * 12288, dw);
          const uint64_t dkv = mkdesc(sb + SM_KVB, 384, 128, 0);
          auto readout = [&](float (&p)[12], float g0, float g1, uint32_t a) {
            uint32_t phi[10];
            feature_map(phi, p);
            WG_FENCE();
            wg24_rs_bf16_i(p, phi[0], phi[5], phi[1], phi[6], dkv);
            wg24_rs_bf16(p, phi[2], phi[7], phi[3], phi[8], dkv + 48, 1);
            wg24_rs_bf16(p, phi[4], phi[9], 0u, 0u, dkv + 96, 1);
            WG_COMMIT();
            WG_WAIT(0);
            pin(p);
            const float l0 = __shfl_sync(0xffffffffu, odd ? p[0] : p[8], lsrc), l1 = __shfl_sync(0xffffffffu, odd ? p[2] : p[10], lsrc);
            stage_o(p, __fdividef(g0, l0 + 1e-6f), __fdividef(g1, l1 + 1e-6f), a, v0, v2);
          };
          mbar_wait(bar + 8 * B_KVB, 0);
          readout(p0, gt[0], gt[1], ostg + orow);
          readout(p1, gt[2], gt[3], ostg + orow + 1024);
          PROXY_FENCE();
          bar_sync(1 + wg, 128);
          mbar_arrive_if(wt == 0, bar + 8 * B_B2);
          flush_o(wt == 0, g_o + rb * ORB + (80 + c0) * 2048, ostg, odd);
          TS_MARK(10);
        }
      }
      if (!(i & 3)) TS_MARK(40 + (i >> 2));
#pragma unroll
      for (int m = 0; m < 2; m++) {
        float s[32];
        uint32_t p[16];
        WG_FENCE();
        wg64_rs_bf16_i(s, q[m][0], q[m][1], q[m][2], q[m][3], desc_lohi(dk0, 8));
        wg64_rs_bf16(s, q[m][4], q[m][5], qc[2 * m], qc[2 * m + 1], desc_lohi(dk1, 8), 1);
        WG_COMMIT();
        WG_WAIT(0);
        constexpr int A = 2 * NMB, B = 16 - A;
#pragma unroll
        for (int j = 0; j < B; j++) {
          if ((j * A) % B < A) { const int a = j * A / B; p[a] = exp2_pair_mufu(s[2 * a], s[2 * a + 1]); }
          p[A + j] = exp2_pair(s[2 * (A + j)], s[2 * (A + j) + 1]);
        }
        WG_FENCE();
#pragma unroll
        for (int kk = 0; kk < 4; kk++) wg24_rs_f16_t(o[m], p[4 * kk], p[4 * kk + 1], p[4 * kk + 2], p[4 * kk + 3], desc_lohi(dv + kk * 16, 64), 1);
        WG_COMMIT();
      }
      dk0 += 384; dk1 += 384u - (384u << 16); dv += 384;
    }
  }
  {
    COORDS();
    float gt[4];
#pragma unroll
    for (int u = 0; u < 4; u++) gt[u] = __ldcg(&g_gate[rb * 128 + (u >> 1) * 64 + w * 16 + g + (u & 1) * 8]);
    WG_WAIT(0);
    pin(o[0]); pin(o[1]);
    TS_MARK(11);
    int big = 0;
#pragma unroll
    for (int m = 0; m < 2; m++) {
      const float l0 = __shfl_sync(0xffffffffu, odd ? o[m][0] : o[m][8], lsrc), l1 = __shfl_sync(0xffffffffu, odd ? o[m][2] : o[m][10], lsrc);
      const float r0 = rcp(l0), r1 = rcp(l1);
      float chk = 0.f, mx0 = 0.f, mx1 = 0.f;
#pragma unroll
      for (int i = 0; i < 12; i++) chk = fmaf(o[m][i], 0.f, chk);
#pragma unroll
      for (int i = 4; i < 6; i++) { mx0 = fmaxf(mx0, fabsf(o[m][i])); mx1 = fmaxf(mx1, fabsf(o[m][i + 2])); }
      bad |= !(chk == 0.f) || !(l0 >= 32.f) || !(l1 >= 32.f);
      big |= fmaxf(mx0 * r0, mx1 * r1) >= 1.220703125e-4f;
      stage_o(o[m], r0 * gt[2 * m], r1 * gt[2 * m + 1], ostg + orow + m * 1024, v0, v2);
    }
    PROXY_FENCE();
    const int anybad = __syncthreads_or(bad), anybig = __syncthreads_or(big);
    if (anybad || !anybig) attn_exact(x, wqkv, h, qt, sb + SM_X);
  }
  TS_MARK(12);

  COORDS();
  if (wg == 3) {
    if (w == 3) { p3_load_w(lane == 0, 3); p3_load_a(lane == 0, 3); }
    bar_sync(4, 128);
    flush_o(lane == 0, g_o + (qt * 4 + w) * ORB + c0 * 2048, sb + SM_X + w * 6144, odd);
    signal_bulk_if(lane == 0, &g_cnt[C_OA + (qt * 4 + w) * 2 + (h >> 4)]);
    if (wt == 0) atomicAdd(&g_cnt[C_EPOCH], 1);
  } else if (wg == 2) {
    const bool p = lane == 0;
    mbar_wait(bar + 8 * (B_P3EMPTY + w), 0);
    p3_load_w(p, 4 + w);
    if (w > 0) wait_count(&g_cnt[C_OA + rb1 * 2 + kh], epoch * 16);
    p3_load_a(p, 4 + w);
    if (w < 2) {
      mbar_wait(bar + 8 * (B_P3EMPTY + w), 1);
      p3_load_w(p, 8 + w);
      if (w == 0) wait_count(&g_cnt[C_OA + rb1 * 2 + kh], epoch * 16);
      p3_load_a(p, 8 + w);
    }
  } else {
    float acc[96];
    const bool wide = (cg & 1) == wg;
    const int skip = (!wide && (cg & 1)) ? 1 : 0;
    if (wide) {
#pragma unroll 1
      for (int j = 0; j < 10; j++) {
        mbar_wait(bar + 8 * (B_P3FULL + (j & 3)), (j >> 2) & 1);
        if (j == 5) TS_MARK(13);
        if (j < 5) TS_MARK(j == 0 ? 1 : 15 + j);
        const uint32_t dst = sb + (j & 3) * P3_STB;
        const uint64_t da = mkdesc(dst + wg * 1024, 2048, 128, 0), db = mkdesc(dst + 16384, 8192, 1024, 1);
        WG_FENCE();
#pragma unroll
        for (int k = 0; k < 4; k++) wg192_ss(acc, da + k * 256, db + k * 128, (j | k) != 0);
        WG_COMMIT();
        WG_WAIT(1);
        mbar_arrive_if(j > 0 && wt == 0, bar + 8 * (B_P3EMPTY + ((j - 1) & 3)));
      }
      WG_WAIT(0);
    } else {
#pragma unroll 1
      for (int j = 0; j < 10; j++) {
        mbar_wait(bar + 8 * (B_P3FULL + (j & 3)), (j >> 2) & 1);
        if (j == 5) TS_MARK(13);
        if (j < 5) TS_MARK(j == 0 ? 1 : 15 + j);
        const uint32_t dst = sb + (j & 3) * P3_STB;
        const uint64_t da = mkdesc(dst + wg * 1024, 2048, 128, 0), db = mkdesc(dst + 16384 + skip * 8192, 8192, 1024, 1);
        WG_FENCE();
#pragma unroll
        for (int k = 0; k < 4; k++) wg128_ss_of96(acc, da + k * 256, db + k * 128, (j | k) != 0);
        WG_COMMIT();
        WG_WAIT(1);
        mbar_arrive_if(j > 0 && wt == 0, bar + 8 * (B_P3EMPTY + ((j - 1) & 3)));
      }
      WG_WAIT(0);
    }
    pin(acc);
    TS_MARK(14);
    if (!wide) mbar_wait(bar + 8 * (B_P3EMPTY + 2), 1);
    const uint32_t stg = sb + (wide ? 4 : 2) * P3_STB;
    const int r = w * 16 + (lane & 15);
#pragma unroll
    for (int i = 0; i < 24; i += 2)
      if (i < 16 || wide) {
        const int ch = (i & 7) + (lane >> 4);
        stsm4(stg + (i >> 3) * 8192 + r * 128 + ((ch ^ (r & 7)) << 4), pack_bf16(acc[4 * i], acc[4 * i + 1]), pack_bf16(acc[4 * i + 2], acc[4 * i + 3]),
              pack_bf16(acc[4 * i + 4], acc[4 * i + 5]), pack_bf16(acc[4 * i + 6], acc[4 * i + 7]));
      }
    PROXY_FENCE();
    bar_sync(1 + wg, 128);
    if (wt < (wide ? 3 : 2)) {
      PROXY_FENCE_G();
      asm volatile("cp.reduce.async.bulk.tensor.2d.global.shared::cta.add.bulk_group [%0, {%2, %3}], [%1];" ::"l"(&maps.out), "r"(stg + wt * 8192),
                   "r"((atom3 + skip + wt) * 64), "r"(rb1 * 128 + wg * 64) : "memory");
      asm volatile("cp.async.bulk.commit_group;" ::: "memory");
      asm volatile("cp.async.bulk.wait_group 0;" ::: "memory");
    }
    TS_MARK(15);
  }
  TS_DUMP();
}

typedef CUresult (*EncodeFn)(CUtensorMap*, CUtensorMapDataType, cuuint32_t, void*, const cuuint64_t*, const cuuint64_t*, const cuuint32_t*, const cuuint32_t*,
                             CUtensorMapInterleave, CUtensorMapSwizzle, CUtensorMapL2promotion, CUtensorMapFloatOOBfill);
void encode(EncodeFn enc, CUtensorMap* m, void* p, int rank, const cuuint64_t* gd, const cuuint64_t* gs, const cuuint32_t* bd) {
  const cuuint32_t es[3] = {1, 1, 1};
  enc(m, CU_TENSOR_MAP_DATA_TYPE_BFLOAT16, rank, p, gd, gs, bd, es, CU_TENSOR_MAP_INTERLEAVE_NONE, CU_TENSOR_MAP_SWIZZLE_128B,
      CU_TENSOR_MAP_L2_PROMOTION_L2_128B, CU_TENSOR_MAP_FLOAT_OOB_FILL_NONE);
}

}

extern "C" void kernel_launch(void* const* d_in, const int* in_sizes, int n_in, void* d_out, int out_size) {
  static EncodeFn enc = nullptr;
  if (!enc) {
    cudaDriverEntryPointQueryResult qr;
    cudaGetDriverEntryPoint("cuTensorMapEncodeTiled", (void**)&enc, cudaEnableDefault, &qr);
    cudaFuncSetAttribute(gated_mix_kernel, cudaFuncAttributeMaxDynamicSharedMemorySize, SMEM_BYTES);
  }
  Maps m;
  {
    const cuuint64_t gd[2] = {640, 2048}, gs[1] = {1280};
    const cuuint32_t bx[2] = {64, 128}, bo[2] = {64, 64};
    encode(enc, &m.x, d_in[0], 2, gd, gs, bx);
    encode(enc, &m.out, d_out, 2, gd, gs, bo);
  }
  for (int b = 0; b < 2; b++) {
    const cuuint64_t gd[3] = {64, 640, 30}, gs[2] = {3840, 128}, gd3[3] = {64, 640, 10}, gs3[2] = {1280, 128};
    const cuuint32_t bd[3] = {64, 64, 4}, bd3[3] = {64, 64, 3};
    encode(enc, &m.w[b], d_in[b ? 4 : 1], 3, gd, gs, bd);
    encode(enc, &m.wo[b], d_in[b ? 6 : 2], 3, gd3, gs3, bd3);
  }
  {
    void* qp = nullptr;
    cudaGetSymbolAddress(&qp, g_qkv);
    const cuuint64_t gd[5] = {128, 80, 3, 2, 32}, gs[4] = {2048, QTY, 1024, QRB};
    const cuuint32_t bl[5] = {128, 3, 2, 2, 4}, bs[5] = {128, 8, 1, 1, 1}, es[5] = {1, 1, 1, 1, 1};
    enc(&m.qld, CU_TENSOR_MAP_DATA_TYPE_UINT64, 5, qp, gd, gs, bl, es, CU_TENSOR_MAP_INTERLEAVE_NONE, CU_TENSOR_MAP_SWIZZLE_NONE, CU_TENSOR_MAP_L2_PROMOTION_L2_128B, CU_TENSOR_MAP_FLOAT_OOB_FILL_NONE);
    enc(&m.qst, CU_TENSOR_MAP_DATA_TYPE_UINT64, 5, qp, gd, gs, bs, es, CU_TENSOR_MAP_INTERLEAVE_NONE, CU_TENSOR_MAP_SWIZZLE_NONE, CU_TENSOR_MAP_L2_PROMOTION_NONE, CU_TENSOR_MAP_FLOAT_OOB_FILL_NONE);
  }
  gated_mix_kernel<<<128, 512, SMEM_BYTES, cudaStreamPerThread>>>(m, (const __nv_bfloat16*)d_in[0], (const __nv_bfloat16*)d_in[1], (const __nv_bfloat16*)d_in[5],
                                                                 (const __nv_bfloat16*)d_in[7], d_in[4], d_in[2], d_in[6], (uint4*)d_out);
}
```

```cpp
#include <cuda_runtime.h>
#include <cuda.h>
#include <cuda_bf16.h>
#include <cuda_fp16.h>
#include <stdint.h>
#pragma nv_diag_suppress 550

namespace {

constexpr int QRB = 240 * 2048;
constexpr int QBR = 16 * QRB;
constexpr int QTY = 80 * 2048;
constexpr int ORB = 160 * 2048;
constexpr int NMB = 3;

__device__ __align__(1024) uint8_t g_qkv[2 * QBR];
__device__ __align__(1024) uint8_t g_o[16 * ORB];
__device__ float g_gate[2048];
__device__ __align__(16) float g_kv[32 * 960];
__device__ uint32_t g_kbad;
__device__ uint32_t g_fb[128 * 2048 * 20];
__device__ uint32_t g_cnt[192];
constexpr int C_EPOCH = 0, C_TA = 32, C_TB = 64, C_KV = 96, C_OB = 128, C_OA = 160;

#define TS_MARK(i)
#define TS_INIT()
#define TS_REG(x)
#define TS_PUT(i, x, th)
#define TS_FIRST()
#define TS_DUMP()

__device__ __forceinline__ uint64_t mkdesc(uint32_t addr, uint32_t lbo, uint32_t sbo, int mode) {
  return (uint64_t)((addr & 0x3FFFF) >> 4) | ((uint64_t)(lbo >> 4) << 16) | ((uint64_t)(sbo >> 4) << 32) | ((uint64_t)mode << 62);
}
__device__ __forceinline__ uint64_t desc_lohi(uint32_t lo, uint32_t hi) { return ((uint64_t)hi << 32) | lo; }
#define WG_FENCE() asm volatile("wgmma.fence.sync.aligned;" ::: "memory")
#define WG_COMMIT() asm volatile("wgmma.commit_group.sync.aligned;" ::: "memory")
#define WG_WAIT(n) asm volatile("wgmma.wait_group.sync.aligned %0;" ::"n"(n) : "memory")
#define PROXY_FENCE() asm volatile("fence.proxy.async.shared::cta;" ::: "memory")
#define PROXY_FENCE_G() asm volatile("fence.proxy.async.global;" ::: "memory")
__device__ __forceinline__ void bar_sync(int id, int n) { asm volatile("bar.sync %0, %1;" ::"r"(id), "r"(n) : "memory"); }
__device__ __forceinline__ void bar_arrive(int id, int n) { asm volatile("bar.arrive %0, %1;" ::"r"(id), "r"(n) : "memory"); }
__device__ __forceinline__ void mbar_init(uint32_t a, int c) { asm volatile("mbarrier.init.shared::cta.b64 [%0], %1;" ::"r"(a), "r"(c)); }
__device__ __forceinline__ uint32_t mbar_try(uint32_t a, int par) {
  uint32_t ok;
  asm volatile("{.reg .pred p; mbarrier.try_wait.parity.shared::cta.b64 p, [%1], %2; selp.b32 %0, 1, 0, p;}" : "=r"(ok) : "r"(a), "r"(par) : "memory");
  return ok;
}
__device__ __forceinline__ void mbar_wait(uint32_t a, int par) {
  for (int i = 0; !mbar_try(a, par); i++)
    if (i > (1 << 22)) break;
}
__device__ __forceinline__ void mbar_arrive(uint32_t a) { asm volatile("mbarrier.arrive.shared::cta.b64 _, [%0];" ::"r"(a) : "memory"); }
__device__ __forceinline__ bool elect() {
  uint32_t p;
  asm volatile("{.reg .pred P; elect.sync _|P, 0xffffffff; selp.b32 %0, 1, 0, P;}" : "=r"(p));
  return p;
}
__device__ __forceinline__ void mbar_arrive_if(bool p, uint32_t a) {
  asm volatile("{.reg .pred p; setp.ne.b32 p, %0, 0; @p mbarrier.arrive.shared::cta.b64 _, [%1];}" ::"r"((int)p), "r"(a) : "memory");
}
__device__ __forceinline__ void mbar_expect_if(bool p, uint32_t a, int bytes) {
  asm volatile("{.reg .pred p; setp.ne.b32 p, %0, 0; @p mbarrier.arrive.expect_tx.shared::cta.b64 _, [%1], %2;}" ::"r"((int)p), "r"(a), "r"(bytes) : "memory");
}
__device__ __forceinline__ void tma2d_if(bool p, uint32_t dst, const CUtensorMap* m, int c0, int c1, uint32_t bar) {
  asm volatile("{.reg .pred p; setp.ne.b32 p, %0, 0; @p cp.async.bulk.tensor.2d.shared::cluster.global.mbarrier::complete_tx::bytes [%1], [%2, {%4, %5}], [%3];}"
               ::"r"((int)p), "r"(dst), "l"(m), "r"(bar), "r"(c0), "r"(c1) : "memory");
}
__device__ __forceinline__ void tma3d_if(bool p, uint32_t dst, const CUtensorMap* m, int c1, int c2, uint32_t bar) {
  asm volatile("{.reg .pred p; setp.ne.b32 p, %0, 0; @p cp.async.bulk.tensor.3d.shared::cluster.global.mbarrier::complete_tx::bytes [%1], [%2, {%6, %4, %5}], [%3];}"
               ::"r"((int)p), "r"(dst), "l"(m), "r"(bar), "r"(c1), "r"(c2), "r"(0) : "memory");
}
__device__ __forceinline__ void bulk_g2s_if(bool p, uint32_t dst, const void* src, int bytes, uint32_t bar) {
  asm volatile("{.reg .pred p; setp.ne.b32 p, %0, 0; @p cp.async.bulk.shared::cluster.global.mbarrier::complete_tx::bytes [%1], [%2], %3, [%4];}"
               ::"r"((int)p), "r"(dst), "l"(src), "r"(bytes), "r"(bar) : "memory");
}
__device__ __forceinline__ void tma5d_if(bool p, uint32_t dst, const CUtensorMap* m, int c1, int c2, int c4, uint32_t bar) {
  asm volatile("{.reg .pred p; setp.ne.b32 p, %0, 0; @p cp.async.bulk.tensor.5d.shared::cluster.global.mbarrier::complete_tx::bytes [%1], [%2, {%7, %4, %5, %7, %6}], [%3];}"
               ::"r"((int)p), "r"(dst), "l"(m), "r"(bar), "r"(c1), "r"(c2), "r"(c4), "r"(0) : "memory");
}
__device__ __forceinline__ void tma5d_store_if(bool p, const CUtensorMap* m, uint32_t src, int c1, int c2, int c3, int c4) {
  asm volatile("{.reg .pred p; setp.ne.b32 p, %0, 0; @p cp.async.bulk.tensor.5d.global.shared::cta.bulk_group [%1, {%7, %3, %4, %5, %6}], [%2];}"
               ::"r"((int)p), "l"(m), "r"(src), "r"(c1), "r"(c2), "r"(c3), "r"(c4), "r"(0) : "memory");
}
__device__ __forceinline__ void bulk_s2g_if(bool p, void* dst, uint32_t src, int bytes) {
  asm volatile("{.reg .pred p; setp.ne.b32 p, %0, 0; @p cp.async.bulk.global.shared::cta.bulk_group [%1], [%2], %3;}" ::"r"((int)p), "l"(dst), "r"(src), "r"(bytes) : "memory");
}
__device__ __forceinline__ void bulk_or_if(bool p, void* dst, uint32_t src, int bytes) {
  asm volatile("{.reg .pred p; setp.ne.b32 p, %0, 0; @p cp.reduce.async.bulk.global.shared::cta.bulk_group.or.b32 [%1], [%2], %3;}" ::"r"((int)p), "l"(dst), "r"(src), "r"(bytes) : "memory");
}
__device__ __forceinline__ void bulk_addf_if(bool p, void* dst, uint32_t src, int bytes) {
  asm volatile("{.reg .pred p; setp.ne.b32 p, %0, 0; @p cp.reduce.async.bulk.global.shared::cta.bulk_group.add.f32 [%1], [%2], %3;}" ::"r"((int)p), "l"(dst), "r"(src), "r"(bytes) : "memory");
}
#define BULK_COMMIT() asm volatile("cp.async.bulk.commit_group;" ::: "memory")
#define BULK_WAIT() asm volatile("cp.async.bulk.wait_group 0;" ::: "memory")
#define BULK_WAIT_READ() asm volatile("cp.async.bulk.wait_group.read 0;" ::: "memory")
__device__ __forceinline__ void signal_bulk_if(bool p, uint32_t* c) {
  asm volatile("{.reg .pred p; setp.ne.b32 p, %0, 0; cp.async.bulk.wait_group 0; @p red.relaxed.gpu.global.add.u32 [%1], 1;}" ::"r"((int)p), "l"(c) : "memory");
}
__device__ __forceinline__ void wait_count(const uint32_t* c, uint32_t target) {
  for (int i = 0;; i++) {
    uint32_t v;
    asm volatile("ld.relaxed.gpu.global.u32 %0, [%1];" : "=r"(v) : "l"(c) : "memory");
    if ((int)(v - target) >= 0) break;
    if (i > (1 << 20)) break;
  }
  PROXY_FENCE_G();
}
__device__ __forceinline__ uint32_t pack_bf16(float lo, float hi) { uint32_t r; asm("cvt.rn.bf16x2.f32 %0, %1, %2;" : "=r"(r) : "f"(hi), "f"(lo)); return r; }
__device__ __forceinline__ uint32_t pack_f16(float lo, float hi) { uint32_t r; asm("cvt.rn.f16x2.f32 %0, %1, %2;" : "=r"(r) : "f"(hi), "f"(lo)); return r; }
__device__ __forceinline__ float ex2(float a) { float r; asm("ex2.approx.ftz.f32 %0, %1;" : "=f"(r) : "f"(a)); return r; }
__device__ __forceinline__ float ex2n(float a) { float r; asm("{.reg .f32 t; neg.ftz.f32 t, %1; ex2.approx.ftz.f32 %0, t;}" : "=f"(r) : "f"(a)); return r; }
__device__ __forceinline__ float rcp(float a) { float r; asm("rcp.approx.ftz.f32 %0, %1;" : "=f"(r) : "f"(a)); return r; }
__device__ __forceinline__ uint32_t maxabs_bf16x2(uint32_t a, uint32_t b) { uint32_t r; asm("max.NaN.xorsign.abs.bf16x2 %0, %1, %2;" : "=r"(r) : "r"(a), "r"(b)); return r; }
__device__ __forceinline__ uint32_t ldg32(const void* p) { return __ldg(reinterpret_cast<const uint32_t*>(p)); }
__device__ __forceinline__ uint32_t ldcg32(const void* p) { uint32_t v; asm volatile("ld.global.cg.u32 %0, [%1];" : "=r"(v) : "l"(p) : "memory"); return v; }
__device__ __forceinline__ uint32_t lds32(uint32_t a) { uint32_t v; asm volatile("ld.shared.b32 %0, [%1];" : "=r"(v) : "r"(a) : "memory"); return v; }
__device__ __forceinline__ void sts32(uint32_t a, uint32_t v) { asm volatile("st.shared.b32 [%0], %1;" ::"r"(a), "r"(v) : "memory"); }
__device__ __forceinline__ void sts16(uint32_t a, uint16_t v) { asm volatile("st.shared.b16 [%0], %1;" ::"r"(a), "h"(v) : "memory"); }
__device__ __forceinline__ void stsm4(uint32_t a, uint32_t r0, uint32_t r1, uint32_t r2, uint32_t r3) {
  asm volatile("stmatrix.sync.aligned.m8n8.x4.shared.b16 [%0], {%1, %2, %3, %4};" ::"r"(a), "r"(r0), "r"(r1), "r"(r2), "r"(r3) : "memory");
}
template <int N> __device__ __forceinline__ void pin(float (&d)[N]) {
#pragma unroll
  for (int i = 0; i < N; i++) asm volatile("" : "+f"(d[i])::"memory");
}

__device__ __forceinline__ void wg128_ss(float (&d)[64], uint64_t da, uint64_t db, int scale_d) {
  asm volatile("{\n.reg .pred p;\nsetp.ne.b32 p, %66, 0;\n"
    "wgmma.mma_async.sync.aligned.m64n128k16.f32.bf16.bf16 "
    "{%0, %1, %2, %3, %4, %5, %6, %7, %8, %9, %10, %11, %12, %13, %14, %15,"
    "%16, %17, %18, %19, %20, %21, %22, %23, %24, %25, %26, %27, %28, %29, %30, %31,"
    "%32, %33, %34, %35, %36, %37, %38, %39, %40, %41, %42, %43, %44, %45, %46, %47,"
    "%48, %49, %50, %51, %52, %53, %54, %55, %56, %57, %58, %59, %60, %61, %62, %63}, "
    "%64, %65, p, 1, 1, 0, 1;\n}\n"
    : "+f"(d[0]), "+f"(d[1]), "+f"(d[2]), "+f"(d[3]), "+f"(d[4]), "+f"(d[5]), "+f"(d[6]), "+f"(d[7]),
      "+f"(d[8]), "+f"(d[9]), "+f"(d[10]), "+f"(d[11]), "+f"(d[12]), "+f"(d[13]), "+f"(d[14]), "+f"(d[15]),
      "+f"(d[16]), "+f"(d[17]), "+f"(d[18]), "+f"(d[19]), "+f"(d[20]), "+f"(d[21]), "+f"(d[22]), "+f"(d[23]),
      "+f"(d[24]), "+f"(d[25]), "+f"(d[26]), "+f"(d[27]), "+f"(d[28]), "+f"(d[29]), "+f"(d[30]), "+f"(d[31]),
      "+f"(d[32]), "+f"(d[33]), "+f"(d[34]), "+f"(d[35]), "+f"(d[36]), "+f"(d[37]), "+f"(d[38]), "+f"(d[39]),
      "+f"(d[40]), "+f"(d[41]), "+f"(d[42]), "+f"(d[43]), "+f"(d[44]), "+f"(d[45]), "+f"(d[46]), "+f"(d[47]),
      "+f"(d[48]), "+f"(d[49]), "+f"(d[50]), "+f"(d[51]), "+f"(d[52]), "+f"(d[53]), "+f"(d[54]), "+f"(d[55]),
      "+f"(d[56]), "+f"(d[57]), "+f"(d[58]), "+f"(d[59]), "+f"(d[60]), "+f"(d[61]), "+f"(d[62]), "+f"(d[63])
    : "l"(da), "l"(db), "r"(scale_d));
}

__device__ __forceinline__ void wg64_ss_of64(float (&d)[64], uint64_t da, uint64_t db, int scale_d) {
  asm volatile("{\n.reg .pred p;\nsetp.ne.b32 p, %34, 0;\n"
    "wgmma.mma_async.sync.aligned.m64n64k16.f32.bf16.bf16 "
    "{%0, %1, %2, %3, %4, %5, %6, %7, %8, %9, %10, %11, %12, %13, %14, %15,"
    "%16, %17, %18, %19, %20, %21, %22, %23, %24, %25, %26, %27, %28, %29, %30, %31}, "
    "%32, %33, p, 1, 1, 0, 1;\n}\n"
    : "+f"(d[0]), "+f"(d[1]), "+f"(d[2]), "+f"(d[3]), "+f"(d[4]), "+f"(d[5]), "+f"(d[6]), "+f"(d[7]),
      "+f"(d[8]), "+f"(d[9]), "+f"(d[10]), "+f"(d[11]), "+f"(d[12]), "+f"(d[13]), "+f"(d[14]), "+f"(d[15]),
      "+f"(d[16]), "+f"(d[17]), "+f"(d[18]), "+f"(d[19]), "+f"(d[20]), "+f"(d[21]), "+f"(d[22]), "+f"(d[23]),
      "+f"(d[24]), "+f"(d[25]), "+f"(d[26]), "+f"(d[27]), "+f"(d[28]), "+f"(d[29]), "+f"(d[30]), "+f"(d[31])
    : "l"(da), "l"(db), "r"(scale_d));
}

__device__ __forceinline__ void wg192_ss(float (&d)[96], uint64_t da, uint64_t db, int scale_d) {
  asm volatile("{\n.reg .pred p;\nsetp.ne.b32 p, %98, 0;\n"
    "wgmma.mma_async.sync.aligned.m64n192k16.f32.bf16.bf16 "
    "{%0, %1, %2, %3, %4, %5, %6, %7, %8, %9, %10, %11, %12, %13, %14, %15,"
    "%16, %17, %18, %19, %20, %21, %22, %23, %24, %25, %26, %27, %28, %29, %30, %31,"
    "%32, %33, %34, %35, %36, %37, %38, %39, %40, %41, %42, %43, %44, %45, %46, %47,"
    "%48, %49, %50, %51, %52, %53, %54, %55, %56, %57, %58, %59, %60, %61, %62, %63,"
    "%64, %65, %66, %67, %68, %69, %70, %71, %72, %73, %74, %75, %76, %77, %78, %79,"
    "%80, %81, %82, %83, %84, %85, %86, %87, %88, %89, %90, %91, %92, %93, %94, %95}, "
    "%96, %97, p, 1, 1, 0, 1;\n}\n"
    : "+f"(d[0]), "+f"(d[1]), "+f"(d[2]), "+f"(d[3]), "+f"(d[4]), "+f"(d[5]), "+f"(d[6]), "+f"(d[7]),
      "+f"(d[8]), "+f"(d[9]), "+f"(d[10]), "+f"(d[11]), "+f"(d[12]), "+f"(d[13]), "+f"(d[14]), "+f"(d[15]),
      "+f"(d[16]), "+f"(d[17]), "+f"(d[18]), "+f"(d[19]), "+f"(d[20]), "+f"(d[21]), "+f"(d[22]), "+f"(d[23]),
      "+f"(d[24]), "+f"(d[25]), "+f"(d[26]), "+f"(d[27]), "+f"(d[28]), "+f"(d[29]), "+f"(d[30]), "+f"(d[31]),
      "+f"(d[32]), "+f"(d[33]), "+f"(d[34]), "+f"(d[35]), "+f"(d[36]), "+f"(d[37]), "+f"(d[38]), "+f"(d[39]),
      "+f"(d[40]), "+f"(d[41]), "+f"(d[42]), "+f"(d[43]), "+f"(d[44]), "+f"(d[45]), "+f"(d[46]), "+f"(d[47]),
      "+f"(d[48]), "+f"(d[49]), "+f"(d[50]), "+f"(d[51]), "+f"(d[52]), "+f"(d[53]), "+f"(d[54]), "+f"(d[55]),
      "+f"(d[56]), "+f"(d[57]), "+f"(d[58]), "+f"(d[59]), "+f"(d[60]), "+f"(d[61]), "+f"(d[62]), "+f"(d[63]),
      "+f"(d[64]), "+f"(d[65]), "+f"(d[66]), "+f"(d[67]), "+f"(d[68]), "+f"(d[69]), "+f"(d[70]), "+f"(d[71]),
      "+f"(d[72]), "+f"(d[73]), "+f"(d[74]), "+f"(d[75]), "+f"(d[76]), "+f"(d[77]), "+f"(d[78]), "+f"(d[79]),
      "+f"(d[80]), "+f"(d[81]), "+f"(d[82]), "+f"(d[83]), "+f"(d[84]), "+f"(d[85]), "+f"(d[86]), "+f"(d[87]),
      "+f"(d[88]), "+f"(d[89]), "+f"(d[90]), "+f"(d[91]), "+f"(d[92]), "+f"(d[93]), "+f"(d[94]), "+f"(d[95])
    : "l"(da), "l"(db), "r"(scale_d));
}

__device__ __forceinline__ void wg128_ss_of96(float (&d)[96], uint64_t da, uint64_t db, int scale_d) {
  asm volatile("{\n.reg .pred p;\nsetp.ne.b32 p, %66, 0;\n"
    "wgmma.mma_async.sync.aligned.m64n128k16.f32.bf16.bf16 "
    "{%0, %1, %2, %3, %4, %5, %6, %7, %8, %9, %10, %11, %12, %13, %14, %15,"
    "%16, %17, %18, %19, %20, %21, %22, %23, %24, %25, %26, %27, %28, %29, %30, %31,"
    "%32, %33, %34, %35, %36, %37, %38, %39, %40, %41, %42, %43, %44, %45, %46, %47,"
    "%48, %49, %50, %51, %52, %53, %54, %55, %56, %57, %58, %59, %60, %61, %62, %63}, "
    "%64, %65, p, 1, 1, 0, 1;\n}\n"
    : "+f"(d[0]), "+f"(d[1]), "+f"(d[2]), "+f"(d[3]), "+f"(d[4]), "+f"(d[5]), "+f"(d[6]), "+f"(d[7]),
      "+f"(d[8]), "+f"(d[9]), "+f"(d[10]), "+f"(d[11]), "+f"(d[12]), "+f"(d[13]), "+f"(d[14]), "+f"(d[15]),
      "+f"(d[16]), "+f"(d[17]), "+f"(d[18]), "+f"(d[19]), "+f"(d[20]), "+f"(d[21]), "+f"(d[22]), "+f"(d[23]),
      "+f"(d[24]), "+f"(d[25]), "+f"(d[26]), "+f"(d[27]), "+f"(d[28]), "+f"(d[29]), "+f"(d[30]), "+f"(d[31]),
      "+f"(d[32]), "+f"(d[33]), "+f"(d[34]), "+f"(d[35]), "+f"(d[36]), "+f"(d[37]), "+f"(d[38]), "+f"(d[39]),
      "+f"(d[40]), "+f"(d[41]), "+f"(d[42]), "+f"(d[43]), "+f"(d[44]), "+f"(d[45]), "+f"(d[46]), "+f"(d[47]),
      "+f"(d[48]), "+f"(d[49]), "+f"(d[50]), "+f"(d[51]), "+f"(d[52]), "+f"(d[53]), "+f"(d[54]), "+f"(d[55]),
      "+f"(d[56]), "+f"(d[57]), "+f"(d[58]), "+f"(d[59]), "+f"(d[60]), "+f"(d[61]), "+f"(d[62]), "+f"(d[63])
    : "l"(da), "l"(db), "r"(scale_d));
}

__device__ __forceinline__ void wg64_rs_bf16(float (&d)[32], uint32_t a0, uint32_t a1, uint32_t a2, uint32_t a3, uint64_t db, int scale_d) {
  asm volatile("{\n.reg .pred p;\nsetp.ne.b32 p, %37, 0;\n"
    "wgmma.mma_async.sync.aligned.m64n64k16.f32.bf16.bf16 "
    "{%0, %1, %2, %3, %4, %5, %6, %7, %8, %9, %10, %11, %12, %13, %14, %15,"
    "%16, %17, %18, %19, %20, %21, %22, %23, %24, %25, %26, %27, %28, %29, %30, %31}, "
    "{%32, %33, %34, %35}, %36, p, 1, 1, 0;\n}\n"
    : "+f"(d[0]), "+f"(d[1]), "+f"(d[2]), "+f"(d[3]), "+f"(d[4]), "+f"(d[5]), "+f"(d[6]), "+f"(d[7]),
      "+f"(d[8]), "+f"(d[9]), "+f"(d[10]), "+f"(d[11]), "+f"(d[12]), "+f"(d[13]), "+f"(d[14]), "+f"(d[15]),
      "+f"(d[16]), "+f"(d[17]), "+f"(d[18]), "+f"(d[19]), "+f"(d[20]), "+f"(d[21]), "+f"(d[22]), "+f"(d[23]),
      "+f"(d[24]), "+f"(d[25]), "+f"(d[26]), "+f"(d[27]), "+f"(d[28]), "+f"(d[29]), "+f"(d[30]), "+f"(d[31])
    : "r"(a0), "r"(a1), "r"(a2), "r"(a3), "l"(db), "r"(scale_d));
}

__device__ __forceinline__ void wg24_rs_f16_t(float (&d)[12], uint32_t a0, uint32_t a1, uint32_t a2, uint32_t a3, uint64_t db, int scale_d) {
  asm volatile("{\n.reg .pred p;\nsetp.ne.b32 p, %17, 0;\n"
    "wgmma.mma_async.sync.aligned.m64n24k16.f32.f16.f16 "
    "{%0, %1, %2, %3, %4, %5, %6, %7, %8, %9, %10, %11}, "
    "{%12, %13, %14, %15}, %16, p, 1, 1, 1;\n}\n"
    : "+f"(d[0]), "+f"(d[1]), "+f"(d[2]), "+f"(d[3]), "+f"(d[4]), "+f"(d[5]), "+f"(d[6]), "+f"(d[7]),
      "+f"(d[8]), "+f"(d[9]), "+f"(d[10]), "+f"(d[11])
    : "r"(a0), "r"(a1), "r"(a2), "r"(a3), "l"(db), "r"(scale_d));
}

__device__ __forceinline__ void wg24_rs_bf16(float (&d)[12], uint32_t a0, uint32_t a1, uint32_t a2, uint32_t a3, uint64_t db, int scale_d) {
  asm volatile("{\n.reg .pred p;\nsetp.ne.b32 p, %17, 0;\n"
    "wgmma.mma_async.sync.aligned.m64n24k16.f32.bf16.bf16 "
    "{%0, %1, %2, %3, %4, %5, %6, %7, %8, %9, %10, %11}, "
    "{%12, %13, %14, %15}, %16, p, 1, 1, 0;\n}\n"
    : "+f"(d[0]), "+f"(d[1]), "+f"(d[2]), "+f"(d[3]), "+f"(d[4]), "+f"(d[5]), "+f"(d[6]), "+f"(d[7]),
      "+f"(d[8]), "+f"(d[9]), "+f"(d[10]), "+f"(d[11])
    : "r"(a0), "r"(a1), "r"(a2), "r"(a3), "l"(db), "r"(scale_d));
}

__device__ __forceinline__ void wg24_ss_bf16_tt(float (&d)[12], uint64_t da, uint64_t db, int scale_d) {
  asm volatile("{\n.reg .pred p;\nsetp.ne.b32 p, %14, 0;\n"
    "wgmma.mma_async.sync.aligned.m64n24k16.f32.bf16.bf16 "
    "{%0, %1, %2, %3, %4, %5, %6, %7, %8, %9, %10, %11}, "
    "%12, %13, p, 1, 1, 1, 1;\n}\n"
    : "+f"(d[0]), "+f"(d[1]), "+f"(d[2]), "+f"(d[3]), "+f"(d[4]), "+f"(d[5]), "+f"(d[6]), "+f"(d[7]),
      "+f"(d[8]), "+f"(d[9]), "+f"(d[10]), "+f"(d[11])
    : "l"(da), "l"(db), "r"(scale_d));
}

__device__ __forceinline__ void wg64_rs_bf16_i(float (&d)[32], uint32_t a0, uint32_t a1, uint32_t a2, uint32_t a3, uint64_t db) {
  asm volatile("{\n.reg .pred p;\nsetp.ne.b32 p, 0, 0;\n"
    "wgmma.mma_async.sync.aligned.m64n64k16.f32.bf16.bf16 "
    "{%0, %1, %2, %3, %4, %5, %6, %7, %8, %9, %10, %11, %12, %13, %14, %15,"
    "%16, %17, %18, %19, %20, %21, %22, %23, %24, %25, %26, %27, %28, %29, %30, %31}, "
    "{%32, %33, %34, %35}, %36, p, 1, 1, 0;\n}\n"
    : "=f"(d[0]), "=f"(d[1]), "=f"(d[2]), "=f"(d[3]), "=f"(d[4]), "=f"(d[5]), "=f"(d[6]), "=f"(d[7]),
      "=f"(d[8]), "=f"(d[9]), "=f"(d[10]), "=f"(d[11]), "=f"(d[12]), "=f"(d[13]), "=f"(d[14]), "=f"(d[15]),
      "=f"(d[16]), "=f"(d[17]), "=f"(d[18]), "=f"(d[19]), "=f"(d[20]), "=f"(d[21]), "=f"(d[22]), "=f"(d[23]),
      "=f"(d[24]), "=f"(d[25]), "=f"(d[26]), "=f"(d[27]), "=f"(d[28]), "=f"(d[29]), "=f"(d[30]), "=f"(d[31])
    : "r"(a0), "r"(a1), "r"(a2), "r"(a3), "l"(db));
}

__device__ __forceinline__ void wg24_rs_bf16_i(float (&d)[12], uint32_t a0, uint32_t a1, uint32_t a2, uint32_t a3, uint64_t db) {
  asm volatile("{\n.reg .pred p;\nsetp.ne.b32 p, 0, 0;\n"
    "wgmma.mma_async.sync.aligned.m64n24k16.f32.bf16.bf16 "
    "{%0, %1, %2, %3, %4, %5, %6, %7, %8, %9, %10, %11}, "
    "{%12, %13, %14, %15}, %16, p, 1, 1, 0;\n}\n"
    : "=f"(d[0]), "=f"(d[1]), "=f"(d[2]), "=f"(d[3]), "=f"(d[4]), "=f"(d[5]), "=f"(d[6]), "=f"(d[7]),
      "=f"(d[8]), "=f"(d[9]), "=f"(d[10]), "=f"(d[11])
    : "r"(a0), "r"(a1), "r"(a2), "r"(a3), "l"(db));
}

__device__ __forceinline__ void wg24_ss_bf16_tt_i(float (&d)[12], uint64_t da, uint64_t db) {
  asm volatile("{\n.reg .pred p;\nsetp.ne.b32 p, 0, 0;\n"
    "wgmma.mma_async.sync.aligned.m64n24k16.f32.bf16.bf16 "
    "{%0, %1, %2, %3, %4, %5, %6, %7, %8, %9, %10, %11}, "
    "%12, %13, p, 1, 1, 1, 1;\n}\n"
    : "=f"(d[0]), "=f"(d[1]), "=f"(d[2]), "=f"(d[3]), "=f"(d[4]), "=f"(d[5]), "=f"(d[6]), "=f"(d[7]),
      "=f"(d[8]), "=f"(d[9]), "=f"(d[10]), "=f"(d[11])
    : "l"(da), "l"(db));
}

__device__ __forceinline__ void wg24_ss_bf16(float (&d)[12], uint64_t da, uint64_t db, int scale_d) {
  asm volatile("{\n.reg .pred p;\nsetp.ne.b32 p, %14, 0;\n"
    "wgmma.mma_async.sync.aligned.m64n24k16.f32.bf16.bf16 "
    "{%0, %1, %2, %3, %4, %5, %6, %7, %8, %9, %10, %11}, "
    "%12, %13, p, 1, 1, 0, 0;\n}\n"
    : "+f"(d[0]), "+f"(d[1]), "+f"(d[2]), "+f"(d[3]), "+f"(d[4]), "+f"(d[5]), "+f"(d[6]), "+f"(d[7]),
      "+f"(d[8]), "+f"(d[9]), "+f"(d[10]), "+f"(d[11])
    : "l"(da), "l"(db), "r"(scale_d));
}

__device__ __forceinline__ void wg24_ss_bf16_i(float (&d)[12], uint64_t da, uint64_t db) {
  asm volatile("{\n.reg .pred p;\nsetp.ne.b32 p, 0, 0;\n"
    "wgmma.mma_async.sync.aligned.m64n24k16.f32.bf16.bf16 "
    "{%0, %1, %2, %3, %4, %5, %6, %7, %8, %9, %10, %11}, "
    "%12, %13, p, 1, 1, 0, 0;\n}\n"
    : "=f"(d[0]), "=f"(d[1]), "=f"(d[2]), "=f"(d[3]), "=f"(d[4]), "=f"(d[5]), "=f"(d[6]), "=f"(d[7]),
      "=f"(d[8]), "=f"(d[9]), "=f"(d[10]), "=f"(d[11])
    : "l"(da), "l"(db));
}

constexpr int P1_STB = 49152, P3_STB = 40960;
constexpr int SM_X = 196608;
constexpr int SM_KVB = SM_X + 24576;
constexpr int SM_GW = SM_X + 8192, SM_WRAW = SM_GW + 1280, SM_EP = SM_WRAW + 800;
constexpr int SM_CONST = SM_X + 32768, SM_WPHI = SM_CONST + 1024, SM_BAR = SM_WPHI + 1536;
constexpr int SMEM_BYTES = SM_BAR + 512;
constexpr int B_FULL = 0, B_AUX = 4, B_KB = 5, B_QB = 6, B_KVFULL = 7, B_P3FULL = 11, B_P3EMPTY = 15, B_EMPTY = 19, B_LINK = 23, B_FREE = 25,
              B_STG = 28, B_B2 = 29, B_ZERO = 30, B_READY = 31, B_KVB = 35;

template <int V> struct Int { static constexpr int value = V; };
struct Maps { CUtensorMap x, w[2], wo[2], out, qld, qst; };

__device__ __forceinline__ int tile_atom(int t) { return (t >> 2) * 15 + ((0xB740 >> ((t & 3) * 4)) & 15); }

template <int MODE, int A>
__device__ __forceinline__ void pack_atom(const float (&acc)[64], uint32_t (&r)[32], float s0, float s1, uint32_t& m0, uint32_t& m1) {
#pragma unroll
  for (int e = A * 16; e < A * 16 + 16; e++) {
    const float s = (e & 1) ? s1 : s0;
    if (MODE == 0) r[e] = pack_bf16(acc[2 * e], acc[2 * e + 1]);
    else if (MODE == 3) r[e] = pack_f16(acc[2 * e], acc[2 * e + 1]);
    else r[e] = pack_bf16(acc[2 * e] * s, acc[2 * e + 1] * s);
    if (MODE == 2) { if (e & 1) m1 = maxabs_bf16x2(m1, r[e]); else m0 = maxabs_bf16x2(m0, r[e]); }
  }
}
template <int A>
__device__ __forceinline__ void pack_atom_a(const float (&acc)[64], uint32_t (&r)[32], int ga, float sk0, float sk1, uint32_t& m0, uint32_t& m1) {
  if (ga < 10) { const float cq = __uint_as_float(463809372u); pack_atom<1, A>(acc, r, cq, cq, m0, m1); }
  else if (ga < 20) pack_atom<2, A>(acc, r, sk0, sk1, m0, m1);
  else pack_atom<3, A>(acc, r, 0.f, 0.f, m0, m1);
}

__device__ __forceinline__ uint32_t exp2_pair(float a, float b) {
  uint32_t z, w, h;
  asm volatile("cvt.pack.sat.s16.s32 %0, %2, %1;" : "=r"(z) : "r"(__float_as_uint(a)), "r"(__float_as_uint(b)));
  asm volatile("lop3.b32 %0, %1, 0x03ff03ff, 0x34003400, 0xEA;" : "=r"(w) : "r"(z));
  asm volatile("fma.rn.f16x2 %0, %1, %1, %2;" : "=r"(h) : "r"(w), "r"(0x36203620));
  asm volatile("fma.rn.f16x2 %0, %0, %1, %2;" : "+r"(h) : "r"(w), "r"(0x2e012e01));
  return h + z - w;
}
__device__ __forceinline__ uint32_t exp2_pair_mufu(float a, float b) {
  float x, y; uint32_t r;
  asm volatile("ex2.approx.ftz.f32 %0, %1;" : "=f"(x) : "f"(a));
  asm volatile("ex2.approx.ftz.f32 %0, %1;" : "=f"(y) : "f"(b));
  asm volatile("cvt.rn.f16x2.f32 %0, %1, %2;" : "=r"(r) : "f"(y), "f"(x));
  return r;
}
__device__ __forceinline__ void load_frag(uint32_t (&a)[6], const uint8_t* p) {
  a[0] = ldcg32(p); a[1] = ldcg32(p + 128); a[2] = ldcg32(p + 2048); a[3] = ldcg32(p + 2048 + 128); a[4] = ldcg32(p + 4096); a[5] = ldcg32(p + 4096 + 128);
}
template <bool EXACT>
__device__ __forceinline__ bool feature_rows(uint32_t (&phi)[10], const float (&p)[12]) {
  const float L = 1.4426950408889634f;
  bool ok = true;
#pragma unroll
  for (int r = 0; r < 2; r++) {
    const float v[5] = {p[2 * r], p[2 * r + 1], p[4 + 2 * r], p[5 + 2 * r], p[8 + 2 * r]};
    float ep[5], en[5];
    if (EXACT) {
      float mx = fmaxf(fmaxf(fmaxf(v[0], v[1]), fmaxf(v[2], v[3])), v[4]);
      float mn = fminf(fminf(fminf(v[0], v[1]), fminf(v[2], v[3])), v[4]);
      mx = fmaxf(mx, __shfl_xor_sync(0xffffffffu, mx, 1)); mn = fminf(mn, __shfl_xor_sync(0xffffffffu, mn, 1));
      mx = fmaxf(mx, __shfl_xor_sync(0xffffffffu, mx, 2)); mn = fminf(mn, __shfl_xor_sync(0xffffffffu, mn, 2));
#pragma unroll
      for (int i = 0; i < 5; i++) { ep[i] = ex2((v[i] - mx) * L); en[i] = ex2((mn - v[i]) * L); }
    } else {
#pragma unroll
      for (int i = 0; i < 5; i++) { const float u = v[i] * L; ep[i] = ex2(u); en[i] = ex2n(u); }
    }
    float sp = (ep[0] + ep[1]) + (ep[2] + ep[3]) + ep[4], sn = (en[0] + en[1]) + (en[2] + en[3]) + en[4];
    sp += __shfl_xor_sync(0xffffffffu, sp, 1); sn += __shfl_xor_sync(0xffffffffu, sn, 1);
    sp += __shfl_xor_sync(0xffffffffu, sp, 2); sn += __shfl_xor_sync(0xffffffffu, sn, 2);
    ok = ok && sp + sn < 1.2676506e30f;
    const float rp = rcp(sp), rn = rcp(sn);
#pragma unroll
    for (int i = 0; i < 5; i++) phi[5 * r + i] = pack_bf16(ep[i] * rp, en[i] * rn);
  }
  return ok;
}
__device__ __forceinline__ void feature_map(uint32_t (&phi)[10], const float (&p)[12]) {
  if (!__all_sync(0xffffffffu, feature_rows<false>(phi, p))) feature_rows<true>(phi, p);
}
__device__ __forceinline__ void phi_proj(float (&p0)[12], float (&p1)[12], uint32_t a, uint64_t dw) {
  const uint64_t da = mkdesc(a, 1024, 128, 0), db = mkdesc(a + 2048, 0, 128, 0);
  WG_FENCE();
  wg24_ss_bf16_i(p0, da, dw);
  wg24_ss_bf16(p0, db, dw + 48, 1);
  wg24_ss_bf16_i(p1, da + 384, dw);
  wg24_ss_bf16(p1, db + 384, dw + 48, 1);
  WG_COMMIT();
  WG_WAIT(0);
  pin(p0); pin(p1);
}
__device__ __forceinline__ void stage_o(const float (&o)[12], float s0, float s1, uint32_t a, bool v0, bool v2) {
#pragma unroll
  for (int j = 0; j < 3; j++) {
    const bool v = j == 1 || (j == 0 ? v0 : v2);
    sts32(a + j * 2048, v ? pack_bf16(o[4 * j] * s0, o[4 * j + 1] * s0) : 0u);
    sts32(a + j * 2048 + 128, v ? pack_bf16(o[4 * j + 2] * s1, o[4 * j + 3] * s1) : 0u);
  }
}
__device__ __forceinline__ void flush_o(bool p, uint8_t* dst, uint32_t src, bool odd) {
  bulk_s2g_if(p, dst + (odd ? 2048 : 0), src + (odd ? 2048 : 0), 4096);
  bulk_or_if(p, dst + (odd ? 0 : 4096), src + (odd ? 0 : 4096), 2048);
  BULK_COMMIT();
}

__device__ __forceinline__ void proj20(float (&acc)[20], const __nv_bfloat16* __restrict__ xr, const __nv_bfloat16* __restrict__ wc) {
#pragma unroll
  for (int d = 0; d < 20; d++) acc[d] = 0.f;
#pragma unroll 2
  for (int k = 0; k < 640; k++) {
    const float xv = __bfloat162float(xr[k]);
#pragma unroll
    for (int d = 0; d < 10; d++) {
      const uint32_t u = ldg32(wc + k * 1920 + 2 * d);
      acc[2 * d] = fmaf(xv, __uint_as_float(u << 16), acc[2 * d]);
      acc[2 * d + 1] = fmaf(xv, __uint_as_float(u & 0xffff0000u), acc[2 * d + 1]);
    }
  }
}
__device__ __noinline__ void attn_exact(const __nv_bfloat16* __restrict__ x, const __nv_bfloat16* __restrict__ wqkv, int h, int qt, uint32_t stg) {
  const int tid = threadIdx.x;
  uint32_t* kvs = g_fb + blockIdx.x * (2048 * 20);
  float a[20];
  for (int i = 0; i < 8; i++) {
    const int key = (i >> 1) * 512 + tid, ty = 1 + (i & 1);
    proj20(a, x + key * 640, wqkv + ty * 640 + h * 20);
#pragma unroll
    for (int d = 0; d < 10; d++) kvs[key * 20 + (i & 1) * 10 + d] = pack_bf16(a[2 * d], a[2 * d + 1]);
  }
  const int row = qt * 512 + tid;
  proj20(a, x + row * 640, wqkv + h * 20);
#pragma unroll
  for (int d = 0; d < 20; d++) a[d] = __bfloat162float(__float2bfloat16(a[d]));
  __syncthreads();
  float o[20], m = -INFINITY, l = 0.f;
#pragma unroll
  for (int d = 0; d < 20; d++) o[d] = 0.f;
  for (int key = 0; key < 2048; key++) {
    uint32_t u[20];
#pragma unroll
    for (int d = 0; d < 5; d++) {
      const uint4 t4 = *reinterpret_cast<const uint4*>(kvs + key * 20 + 4 * d);
      u[4 * d] = t4.x; u[4 * d + 1] = t4.y; u[4 * d + 2] = t4.z; u[4 * d + 3] = t4.w;
    }
    float s = 0.f;
#pragma unroll
    for (int d = 0; d < 10; d++) {
      s = fmaf(a[2 * d], __uint_as_float(u[d] << 16), s);
      s = fmaf(a[2 * d + 1], __uint_as_float(u[d] & 0xffff0000u), s);
    }
    s *= 0.22360679774997896f;
    const float mn = fmaxf(m, s), cr = __expf(m - mn), p = __expf(s - mn);
    m = mn;
    l = l * cr + p;
#pragma unroll
    for (int d = 0; d < 10; d++) {
      o[2 * d] = fmaf(p, __uint_as_float(u[10 + d] << 16), o[2 * d] * cr);
      o[2 * d + 1] = fmaf(p, __uint_as_float(u[10 + d] & 0xffff0000u), o[2 * d + 1] * cr);
    }
  }
  const float sc = __ldcg(&g_gate[row]) / l;
#pragma unroll
  for (int d = 0; d < 10; d++) {
    const int col = (h & 1) * 4 + 2 * d;
    sts32(stg + (tid >> 7) * 6144 + (col >> 3) * 2048 + (tid & 127) * 16 + (col & 7) * 2, pack_bf16(o[2 * d] * sc, o[2 * d + 1] * sc));
  }
  PROXY_FENCE();
  __syncthreads();
}

#define COORDS()                                                                                                        \
  int tid, bid;                                                                                                         \
  asm volatile("mov.u32 %0, %%tid.x;" : "=r"(tid));                                                                     \
  asm volatile("mov.u32 %0, %%ctaid.x;" : "=r"(bid));                                                                   \
  const int wg = __shfl_sync(0xffffffffu, tid >> 7, 0);                                                                 \
  const int lane = tid & 31, w = (tid >> 5) & 3, g = lane >> 2, t = lane & 3, wt = tid & 127;                           \
  const int rb1 = bid >> 3, c1 = bid & 7;                                       \
  const int h = bid >> 2, qt = bid & 3, rb = qt * 4 + wg;                    \
  const bool odd = h & 1;                                                                                               \
  const int c0 = (h * 5) >> 1;                                               \
  const int lsrc = (lane & ~3) | (odd ? 0 : 2);                                                                         \
  const bool v0 = !odd || t >= 2, v2 = odd || t < 2;                                                                    \
  const uint32_t ostg = sb + SM_X + wg * 6144, orow = (w * 16 + g) * 16 + t * 4;                                        \
  const uint32_t onepos = (wt >> 6) * 6144 + 3072 + (odd ? 0 : 2048 + 8) + (wt & 63) * 16;                              \
  const int kh = bid & 1, cg = (bid >> 1) & 3, atom3 = (cg >> 1) * 5 + (cg & 1) * 2;                                    \
  auto p3_load_w = [&](bool p, int j) {                                                                                 \
    const uint32_t fb = bar + 8 * (B_P3FULL + (j & 3));                                                                 \
    mbar_expect_if(p, fb, P3_STB);                                                                                      \
    tma3d_if(p, sb + (j & 3) * P3_STB + 16384, &maps.wo[j < 5], (kh * 5 + (j < 5 ? j : j - 5)) * 64, atom3, fb);       \
  };                                                                                                                    \
  auto p3_load_a = [&](bool p, int j) {                                                                                 \
    bulk_g2s_if(p, sb + (j & 3) * P3_STB, g_o + rb1 * ORB + ((j < 5 ? 10 + j : j - 5) + kh * 5) * 16384, 16384,         \
                bar + 8 * (B_P3FULL + (j & 3)));                                                                        \
  };                                                                                                                    \
  (void)g; (void)t; (void)wt; (void)rb1; (void)c1; (void)rb; (void)c0; (void)lsrc; (void)v0; (void)v2; (void)ostg;      \
  (void)orow; (void)onepos; (void)atom3; (void)p3_load_w; (void)p3_load_a

#define P1_LOAD()                                                                                                       \
  auto p1_load = [&](bool p, int it) {                                                                                  \
    const int st = it & 3, b2 = it >= 10, ks = it - b2 * 10;                                                            \
    const uint32_t dst = sb + st * P1_STB, fb = bar + 8 * (B_FULL + st);                                                \
    mbar_expect_if(p, fb, P1_STB);                                                                                      \
    tma2d_if(p, dst, &maps.x, ks * 64, rb1 * 128, fb);                                                                  \
    tma3d_if(p, dst + 16384, &maps.w[b2], ks * 64, tile_atom(c1 ^ b2), fb);                                             \
  }

__global__ void __launch_bounds__(512, 1)
gated_mix_kernel(const __grid_constant__ Maps maps, const __nv_bfloat16* __restrict__ x, const __nv_bfloat16* __restrict__ wqkv, const __nv_bfloat16* __restrict__ w_phi,
                 const __nv_bfloat16* __restrict__ gate_w, const void* wqkv_b, const void* wo_a, const void* wo_b, uint4* __restrict__ out) {
  extern __shared__ __align__(1024) uint8_t smem_raw[];
  const uint32_t sb = (uint32_t)__cvta_generic_to_shared(smem_raw);
  const uint32_t bar = sb + SM_BAR;
  uint32_t q[2][6], qc[4], epoch, events;
  int bad;
  {
  COORDS();
  TS_INIT();

  P1_LOAD();
  if (wt == 0) {
    mbar_init(bar + 8 * (B_FULL + wg), 1);
    asm volatile("fence.mbarrier_init.release.cluster;" ::: "memory");
    if (wg == 0) p1_load(true, 0);
  }
  TS_REG(tsa_);
  if (wt == 32) {
#pragma unroll
    for (int u = 0; u < 4; u++)
      if (wg == u) {
#pragma unroll
        for (int i = B_AUX + u * 8; i < B_AUX + u * 8 + 8; i++)
          mbar_init(bar + 8 * i, i == B_AUX ? 3 : i < B_P3EMPTY ? 1 : i < B_EMPTY ? 2 : i < B_ZERO ? 4 : i == B_ZERO ? 16 : i < B_READY + 2 ? 512 : 128);
      }
    asm volatile("fence.mbarrier_init.release.cluster;" ::: "memory");
  }
  TS_REG(tsb_);
  TS_REG(tsc_);
  asm volatile("st.shared.v4.b32 [%0], {%1, %1, %1, %1};" ::"r"(sb + SM_X + tid * 16), "r"(0) : "memory");
  if (tid < 256) sts32(sb + SM_CONST + tid * 4, (tid & 3) ? 0u : ((tid >> 5) < NMB ? 0xdd02e192u : 0x00001ef0u));
  PROXY_FENCE();
  TS_REG(tsd_);
  __syncthreads();
  if (wg > 0) p1_load(wt == 0, wg);
  if (wt == 64) {
    if (wg == 1) { mbar_expect_if(true, bar + 8 * B_AUX, 1280); bulk_g2s_if(true, sb + SM_GW, gate_w, 1280, bar + 8 * B_AUX); }
    if (wg == 2) { mbar_expect_if(true, bar + 8 * B_AUX, 800); bulk_g2s_if(true, sb + SM_WRAW, w_phi + h * 400, 800, bar + 8 * B_AUX); }
    if (wg == 3) { mbar_expect_if(true, bar + 8 * B_AUX, 16); bulk_g2s_if(true, sb + SM_EP, &g_cnt[C_EPOCH], 16, bar + 8 * B_AUX); }
  }
  TS_FIRST();

  }
  {
    float acc[64];
    uint32_t pk[32];
    float gs = 0.f;
    auto tile = [&](auto BR) {
    constexpr int br = decltype(BR)::value;
    COORDS();
    P1_LOAD();
    const int r = wg & 1, ch = wg >> 1;
    uint32_t xh[3];
    const int grow = c1 * 16 + (tid >> 5);
    const uint32_t gx = sb + grow * 128 + ((g ^ (grow & 7)) << 4) + t * 4, gw = sb + SM_GW + lane * 4;
    const uint32_t srow = (w * 16 + (lane & 15)) * 16 + (lane >> 4) * 1024;
    const bool lead = w == 0;
    auto stage = [&](uint32_t stg, int e0) {
#pragma unroll
      for (int e = 0; e < 16; e += 4) stsm4(stg + srow + e * 512, pk[e0 + e], pk[e0 + e + 1], pk[e0 + e + 2], pk[e0 + e + 3]);
    };
    auto gate_fma = [&](uint32_t a, int ks) {
      const uint32_t b = lds32(gw + ks * 128);
      gs = fmaf(__uint_as_float(a << 16), __uint_as_float(b << 16), gs);
      gs = fmaf(__uint_as_float(a & 0xffff0000u), __uint_as_float(b & 0xffff0000u), gs);
    };
    auto release = [&](int it) {
      if (lead) {
        if (elect()) mbar_arrive(bar + 8 * (B_EMPTY + (it & 3)));
        if (wg == 3 && it < 16) {
          mbar_wait(bar + 8 * (B_EMPTY + (it & 3)), (it >> 2) & 1);
          if (elect()) p1_load(true, it + 4);
        }
      }
    };
    const int ga_a = tile_atom(c1) + 2 * ch + (((c1 & 3) == 2 && wg == 0) ? 1 : 0);
    const bool narrow_a = ((c1 & 3) == 1 && wg == 3) || ((c1 & 3) == 2 && wg == 0);
    auto duties = [&](int it) {
      if (it < 10) {
        const uint32_t a = lds32(gx + (it & 3) * P1_STB);
        if (it < 3) xh[it < 3 ? it : 0] = a;
        else {
          if (it == 3) { mbar_wait(bar + 8 * B_AUX, 0); gate_fma(xh[0], 0); gate_fma(xh[1], 1); gate_fma(xh[2], 2); }
          gate_fma(a, it);
        }
        if (it == 9) { __syncwarp(); if (elect()) mbar_arrive(bar + 8 * B_ZERO); }
      }
      if (it >= 1 && it <= 4 && wg == 0 && lead) {
        if (elect()) {
          if (it < 4) bulk_s2g_if(true, reinterpret_cast<uint8_t*>(out) + bid * 20480 + (it - 1) * 8192, sb + SM_X, it == 3 ? 4096 : 8192);
          else bulk_s2g_if(true, g_kv + bid * 240, sb + SM_X, 960);
          bulk_s2g_if(true, g_o + rb1 * ORB + ((c1 * 4 + it - 1) * 5 + 2) * 2048, sb + SM_X, 2048);
          BULK_COMMIT();
        }
      }
      if (it >= 1 && it <= 3 && wg == 1 && lead) {
        const int bytes = it == 1 ? 19200 : 6400;
        const uint8_t* p = reinterpret_cast<const uint8_t*>(it == 1 ? wqkv_b : it == 2 ? wo_a : wo_b) + bid * bytes;
        if (elect()) asm volatile("cp.async.bulk.prefetch.L2.global [%0], %1;" ::"l"(p), "r"(bytes) : "memory");
      }
      if (it == 4) epoch = (lds32(sb + SM_EP) >> 7) + 1;
      if (it == 5 || (it == 6 && wg < 2)) {
        const int i = tid + (it - 5) * 512, k = i / 24, n = i % 24, ii = 2 * (n >> 3) + (n & 1), f = 4 * ii + ((n & 7) >> 1), d = k - (odd ? 4 : 0);
        uint16_t v = 0;
        if (d >= 0 && d < 20 && ii < 5) asm volatile("ld.shared.u16 %0, [%1];" : "=h"(v) : "r"(sb + SM_WRAW + (d * 20 + f) * 2) : "memory");
        sts16(sb + SM_WPHI + (k >> 3) * 384 + n * 16 + (k & 7) * 2, v);
      }
      if (it == 7 && wg == 0) BULK_WAIT_READ();
      if (it >= 10 && it <= 13) {
        if ((it & 1) == ch) {
          const int u = it >= 12;
          if (!u) mbar_wait(bar + 8 * B_ZERO, 0);
          else { BULK_WAIT_READ(); bar_sync(1 + wg, 128); }
          stage(sb + SM_X + wg * 8192, u * 16);
          PROXY_FENCE();
          bar_sync(1 + wg, 128);
          if (lead && elect()) {
            if (!(u && narrow_a)) tma5d_store_if(true, &maps.qst, sb + SM_X + wg * 8192, ((ga_a + u) % 10) * 8, (ga_a + u) / 10, r, rb1);
            if (u) bulk_s2g_if(true, g_gate + rb1 * 128 + c1 * 16 + wg * 4, sb + SM_BAR + 448 + wg * 16, 16);
            BULK_COMMIT();
          }
        } else if (it < 12) {
#pragma unroll
          for (int o = 16; o; o >>= 1) gs += __shfl_xor_sync(0xffffffffu, gs, o);
          if (lane == 0) sts32(sb + SM_BAR + 448 + (tid >> 5) * 4, __float_as_uint(rcp(1.f + ex2(gs * -1.4426950408889634f))));
        }
      }
      if (it == 15 && lead) signal_bulk_if(lane == 0, &g_cnt[C_TA]);
      if ((it == 17 || it == 18) && wg == it - 17 && lead) {
        wait_count(&g_cnt[C_TA], epoch * 512);
        mbar_wait(bar + 8 * (B_EMPTY + (it - 17)), 0);
        if (elect()) {
          mbar_expect_if(true, bar + 8 * (B_KVFULL + it - 17), P1_STB);
          tma5d_if(true, sb + (it - 17) * P1_STB, &maps.qld, c0, 1, (it - 17) * 4, bar + 8 * (B_KVFULL + it - 17));
        }
      }
      if (it == 19) {
        mbar_wait(bar + 8 * (B_KVFULL + 0), 0);
        const uint8_t* qp = g_qkv + rb * QRB + c0 * 2048 + orow;
        load_frag(q[0], qp);
        load_frag(q[1], qp + 1024);
        bad = ldcg32(&g_kbad);
        sts16(sb + wg * 12288 + onepos, 0x3c00);
        PROXY_FENCE();
        mbar_arrive(bar + 8 * (B_READY + 0));
      }
    };
      const int tl = c1 ^ br, k4 = tl & 3;
      const bool narrow = (k4 == 1 && wg == 3) || (k4 == 2 && wg == 0);
      const int a0 = 2 * ch + ((k4 == 2 && wg == 0) ? 1 : 0);
      const uint32_t da = (uint32_t)mkdesc(sb + r * 8192, 16, 0, 0), db = (uint32_t)mkdesc(sb + 16384 + a0 * 8192, 8192, 0, 0);
      auto run = [&](auto NARROW) {
#pragma unroll
        for (int ks = 0; ks < 10; ks++) {
          const int it = br * 10 + ks, so = (it & 3) * (P1_STB / 16);
          mbar_wait(bar + 8 * (B_FULL + (it & 3)), (it >> 2) & 1);
          TS_MARK(20 + it);
          bar_sync(5 + wg, 256);
          WG_FENCE();
#pragma unroll
          for (int k = 0; k < 4; k++) {
            if (decltype(NARROW)::value) wg64_ss_of64(acc, desc_lohi(da + so + k * 2, 0x40000040u), desc_lohi(db + so + k * 128, 0x40000040u), (ks | k) != 0);
            else wg128_ss(acc, desc_lohi(da + so + k * 2, 0x40000040u), desc_lohi(db + so + k * 128, 0x40000040u), (ks | k) != 0);
          }
          WG_COMMIT();
          if (it < 19 || wg < 3) bar_arrive(5 + ((wg + 1) & 3), 256);
          WG_WAIT(1);
          if (ks > 0) release(it - 1);
          duties(it);
        }
        WG_WAIT(0);
      };
      if (br == 0 && wg == 3) bar_arrive(5, 256);
      if (narrow) run(Int<1>{}); else run(Int<0>{});
      pin(acc);
      TS_MARK(2 + 2 * br);
      release(br * 10 + 9);
      const int ga0 = tile_atom(tl) + a0;
      uint32_t m0 = 0, m1 = 0;
      if (br == 0) {
        const bool mufu0 = 2 * w < NMB, mufu1 = 2 * w + 1 < NMB;
        const float sk0 = __uint_as_float(mufu0 ? (127u + 70u) << 23 : (127u - 69u) << 23);
        const float sk1 = __uint_as_float(mufu1 ? (127u + 70u) << 23 : (127u - 69u) << 23);
        pack_atom_a<0>(acc, pk, ga0, sk0, sk1, m0, m1);
        if (!narrow) pack_atom_a<1>(acc, pk, ga0 + 1, sk0, sk1, m0, m1);
        const uint32_t lim0 = (mufu0 ? 127u + 110u : 127u - 29u) << 7, lim1 = (mufu1 ? 127u + 110u : 127u - 29u) << 7;
        if ((m0 & 0x7fffu) >= lim0 || ((m0 >> 16) & 0x7fffu) >= lim0 || (m1 & 0x7fffu) >= lim1 || ((m1 >> 16) & 0x7fffu) >= lim1) { g_kbad = epoch; __threadfence(); }
      } else {
        pack_atom<0, 0>(acc, pk, 0.f, 0.f, m0, m1);
        pack_atom<0, 1>(acc, pk, 0.f, 0.f, m0, m1);
        if (ch) mbar_wait(bar + 8 * (B_EMPTY + 2), 0);
        const uint32_t stg = sb + (ch ? 2 * P1_STB : SM_X) + r * 16384;
        stage(stg, 0);
        stage(stg + 8192, 16);
        mbar_wait(bar + 8 * (B_KVFULL + 1), 0);
        sts16(sb + P1_STB + wg * 12288 + onepos, 0x3c00);
        PROXY_FENCE();
        mbar_arrive(bar + 8 * (B_READY + 1));
        bar_sync(1 + wg, 128);
        if (lead && elect()) {
          tma5d_store_if(true, &maps.qst, stg, (ga0 % 10) * 8, ga0 / 10, r, 16 + rb1);
          if (!narrow) tma5d_store_if(true, &maps.qst, stg + 8192, ((ga0 + 1) % 10) * 8, (ga0 + 1) / 10, r, 16 + rb1);
          BULK_COMMIT();
        }
      }
      TS_MARK(3 + 2 * br);
    };
    tile(Int<0>{});
    tile(Int<1>{});
  }

  {
  COORDS();
  if (odd ? t < 2 : t >= 2) {
    if (odd) { q[0][0] = 0; q[0][1] = 0; q[1][0] = 0; q[1][1] = 0; }
    else { q[0][4] = 0; q[0][5] = 0; q[1][4] = 0; q[1][5] = 0; }
  }
  {
    uint32_t m = 0;
#pragma unroll
    for (int i = 0; i < 6; i++) m = maxabs_bf16x2(m, maxabs_bf16x2(q[0][i], q[1][i]));
    bad = bad == (int)epoch || (m & 0x7fffu) >= ((127u - 50u) << 7) || ((m >> 16) & 0x7fffu) >= ((127u - 50u) << 7);
  }
#pragma unroll
  for (int i = 0; i < 4; i++) { qc[i] = t == 0 ? 0x1c801c80u : 0u; asm volatile("" : "+r"(qc[i])); }
  events = 0x01010140u | (0x2008000u >> (2 * wg)) | (wg == 0 ? 0x8000480u : wg == 1 ? 0x40000u : wg == 2 ? 0x20000000u : 0x420000u);
  mbar_wait(bar + 8 * (B_READY + 0), 0);
  }
  float o[2][12];
#pragma unroll
  for (int i = 0; i < 12; i++) { o[0][i] = 0.f; o[1][i] = 0.f; }
  {
    uint32_t dk0 = (uint32_t)mkdesc(sb, 1024, 0, 0), dk1 = (uint32_t)mkdesc(sb + 2048, SM_CONST - 2048, 0, 0), dv = (uint32_t)mkdesc(sb + 3072, 128, 0, 0);
    TS_MARK(6);
#pragma unroll 1
    for (int i = 0; i < 32; i++) {
      if ((events >> i) & 1) {
        if ((i & 7) == 0 || i == 6 || i == 27) {
          COORDS();
          const bool p = wt == 0;
          signal_bulk_if(p && i != 8 && (i != 24 || wg != 0), &g_cnt[i == 6 ? C_TB : i == 16 ? C_KV + h : C_OB + rb * 2 + (h >> 4)]);
          if (i == 6) mbar_arrive_if(p, bar + 8 * B_STG);
          if ((i & 7) == 0) {
            WG_WAIT(0);
            mbar_arrive_if(p, bar + 8 * (B_FREE - 1) + i);
            mbar_wait(bar + 8 * B_READY + i, 0);
          }
        } else if (i == 7 || i == 10 || i == 17 || i == 22 || i == 29) {
          COORDS();
          const bool p = lane == 0;
          if (i == 7) {
            mbar_wait(bar + 8 * B_STG, 0);
            if (w == 1) wait_count(&g_cnt[C_TB], epoch * 512);
            const uint32_t fb = bar + 8 * (w ? B_KB : B_KVFULL + 2);
            mbar_expect_if(p && w < 2, fb, P1_STB);
            tma5d_if(p && w < 2, sb + (2 + w) * P1_STB, &maps.qld, c0, 1, w ? 16 + qt * 4 : 8, fb);
          } else if (i == 29) {
            mbar_wait(bar + 8 * (B_FREE + 2), 0);
            mbar_wait(bar + 8 * B_B2, 0);
            p3_load_w(p && w < 3, w);
            wait_count(&g_cnt[C_OB + rb1 * 2 + kh], epoch * 16);
            p3_load_a(p && w < 3, w);
          } else {
            if (i != 22) {
              const int u = i == 17;
              const uint32_t fb = bar + 8 * (u ? B_KVFULL + 3 : B_QB);
              mbar_wait(bar + 8 * (B_FREE + u), 0);
              mbar_expect_if(wt == 0, fb, P1_STB);
              tma5d_if(wt == 0, sb + u * 3 * P1_STB, &maps.qld, c0, u, u ? 12 : 16 + qt * 4, fb);
            }
            if (i != 17) {
              const int u = i == 10 ? 2 : 3;
              mbar_wait(bar + 8 * (B_KVFULL + u), 0);
#pragma unroll
              for (int e = 0; e < 4; e++) sts16(sb + u * P1_STB + e * 12288 + onepos, 0x3c00);
              PROXY_FENCE();
              mbar_arrive(bar + 8 * (B_READY + u));
            }
          }
        } else if (i < 16) {
          WG_WAIT(0);
          COORDS();
          const uint64_t dw = mkdesc(sb + SM_WPHI, 384, 128, 0);
          TS_MARK(7);
          const uint32_t kb = sb + 3 * P1_STB + wg * 12288, ph = sb + SM_X + (wg & 1) * 10240;
          mbar_wait(bar + 8 * B_KB, 0);
          sts16(kb + onepos, 0x3f80);
          float p0[12], p1[12];
          phi_proj(p0, p1, kb, dw);
          if (wg < 2) mbar_wait(bar + 8 * (B_LINK + wg), 0);
          uint32_t phi[10];
          feature_map(phi, p0);
#pragma unroll
          for (int u = 0; u < 10; u++) sts32(ph + (u % 5) * 2048 + orow + (u / 5) * 128, phi[u]);
          feature_map(phi, p1);
#pragma unroll
          for (int u = 0; u < 10; u++) sts32(ph + (u % 5) * 2048 + orow + (u / 5) * 128 + 1024, phi[u]);
          PROXY_FENCE();
          bar_sync(1 + wg, 128);
          const uint64_t da = mkdesc(ph, 128, 2048, 0), db = mkdesc(kb + 3072, 128, 1024, 0);
          WG_FENCE();
#pragma unroll
          for (int kk = 0; kk < 8; kk++) {
            if (kk == 0) wg24_ss_bf16_tt_i(p0, da, db);
            else wg24_ss_bf16_tt(p0, da + kk * 16, db + (kk & 3) * 16 + (kk >> 2) * 384, 1);
          }
          WG_COMMIT();
          WG_WAIT(0);
          pin(p0);
          mbar_arrive_if(lane == 0 && wg >= 2, bar + 8 * (B_LINK + (wg & 1)));
          bar_sync(1 + wg, 128);
          const uint32_t ks = kb + ((w * 16 + g) * 24 + 2 * t) * 4;
#pragma unroll
          for (int j = 0; j < 3; j++) {
            if (w < 3) asm volatile("st.shared.v2.f32 [%0], {%1, %2};" ::"r"(ks + 32 * j), "f"(p0[4 * j]), "f"(p0[4 * j + 1]) : "memory");
            if (w < 2) asm volatile("st.shared.v2.f32 [%0], {%1, %2};" ::"r"(ks + 768 + 32 * j), "f"(p0[4 * j + 2]), "f"(p0[4 * j + 3]) : "memory");
          }
          PROXY_FENCE();
          bar_sync(1 + wg, 128);
          bulk_addf_if(wt == 0, g_kv + h * 960, kb, 3840);
          BULK_COMMIT();
          TS_MARK(8);
        } else if (i == 18) {
          COORDS();
          wait_count(&g_cnt[C_KV + h], epoch * 16);
          float v[8];
#pragma unroll
          for (int u = 0; u < 8; u++) v[u] = (u < 7 || wt < 64) ? __ldcg(&g_kv[h * 960 + u * 128 + wt]) : 0.f;
#pragma unroll
          for (int u = 0; u < 9; u++) {
            const int e = u * 128 + wt, f = e / 24, d = e % 24;
            sts16(sb + SM_KVB + (f >> 3) * 384 + d * 16 + (f & 7) * 2, u < 8 ? __bfloat16_as_ushort(__float2bfloat16(v[u < 8 ? u : 0])) : (uint16_t)0);
          }
          PROXY_FENCE();
          mbar_arrive(bar + 8 * B_KVB);
        } else {
          WG_WAIT(0);
          COORDS();
          const uint64_t dw = mkdesc(sb + SM_WPHI, 384, 128, 0);
          TS_MARK(9);
          float gt[4];
#pragma unroll
          for (int u = 0; u < 4; u++) gt[u] = 1.f - __ldcg(&g_gate[rb * 128 + (u >> 1) * 64 + w * 16 + g + (u & 1) * 8]);
          mbar_wait(bar + 8 * B_QB, 0);
          float p0[12], p1[12];
          phi_proj(p0, p1, sb + wg * 12288, dw);
          const uint64_t dkv = mkdesc(sb + SM_KVB, 384, 128, 0);
          auto readout = [&](float (&p)[12], float g0, float g1, uint32_t a) {
            uint32_t phi[10];
            feature_map(phi, p);
            WG_FENCE();
            wg24_rs_bf16_i(p, phi[0], phi[5], phi[1], phi[6], dkv);
            wg24_rs_bf16(p, phi[2], phi[7], phi[3], phi[8], dkv + 48, 1);
            wg24_rs_bf16(p, phi[4], phi[9], 0u, 0u, dkv + 96, 1);
            WG_COMMIT();
            WG_WAIT(0);
            pin(p);
            const float l0 = __shfl_sync(0xffffffffu, odd ? p[0] : p[8], lsrc), l1 = __shfl_sync(0xffffffffu, odd ? p[2] : p[10], lsrc);
            stage_o(p, __fdividef(g0, l0 + 1e-6f), __fdividef(g1, l1 + 1e-6f), a, v0, v2);
          };
          mbar_wait(bar + 8 * B_KVB, 0);
          readout(p0, gt[0], gt[1], ostg + orow);
          readout(p1, gt[2], gt[3], ostg + orow + 1024);
          PROXY_FENCE();
          bar_sync(1 + wg, 128);
          mbar_arrive_if(wt == 0, bar + 8 * B_B2);
          flush_o(wt == 0, g_o + rb * ORB + (80 + c0) * 2048, ostg, odd);
          TS_MARK(10);
        }
      }
      if (!(i & 3)) TS_MARK(40 + (i >> 2));
#pragma unroll
      for (int m = 0; m < 2; m++) {
        float s[32];
        uint32_t p[16];
        WG_FENCE();
        wg64_rs_bf16_i(s, q[m][0], q[m][1], q[m][2], q[m][3], desc_lohi(dk0, 8));
        wg64_rs_bf16(s, q[m][4], q[m][5], qc[2 * m], qc[2 * m + 1], desc_lohi(dk1, 8), 1);
        WG_COMMIT();
        WG_WAIT(0);
        constexpr int A = 2 * NMB, B = 16 - A;
#pragma unroll
        for (int j = 0; j < B; j++) {
          if ((j * A) % B < A) { const int a = j * A / B; p[a] = exp2_pair_mufu(s[2 * a], s[2 * a + 1]); }
          p[A + j] = exp2_pair(s[2 * (A + j)], s[2 * (A + j) + 1]);
        }
        WG_FENCE();
#pragma unroll
        for (int kk = 0; kk < 4; kk++) wg24_rs_f16_t(o[m], p[4 * kk], p[4 * kk + 1], p[4 * kk + 2], p[4 * kk + 3], desc_lohi(dv + kk * 16, 64), 1);
        WG_COMMIT();
      }
      dk0 += 384; dk1 += 384u - (384u << 16); dv += 384;
    }
  }
  {
    COORDS();
    float gt[4];
#pragma unroll
    for (int u = 0; u < 4; u++) gt[u] = __ldcg(&g_gate[rb * 128 + (u >> 1) * 64 + w * 16 + g + (u & 1) * 8]);
    WG_WAIT(0);
    pin(o[0]); pin(o[1]);
    TS_MARK(11);
    int big = 0;
#pragma unroll
    for (int m = 0; m < 2; m++) {
      const float l0 = __shfl_sync(0xffffffffu, odd ? o[m][0] : o[m][8], lsrc), l1 = __shfl_sync(0xffffffffu, odd ? o[m][2] : o[m][10], lsrc);
      const float r0 = rcp(l0), r1 = rcp(l1);
      float chk = 0.f, mx0 = 0.f, mx1 = 0.f;
#pragma unroll
      for (int i = 0; i < 12; i++) chk = fmaf(o[m][i], 0.f, chk);
#pragma unroll
      for (int i = 4; i < 6; i++) { mx0 = fmaxf(mx0, fabsf(o[m][i])); mx1 = fmaxf(mx1, fabsf(o[m][i + 2])); }
      bad |= !(chk == 0.f) || !(l0 >= 32.f) || !(l1 >= 32.f);
      big |= fmaxf(mx0 * r0, mx1 * r1) >= 1.220703125e-4f;
      stage_o(o[m], r0 * gt[2 * m], r1 * gt[2 * m + 1], ostg + orow + m * 1024, v0, v2);
    }
    PROXY_FENCE();
    const int anybad = __syncthreads_or(bad), anybig = __syncthreads_or(big);
    if (anybad || !anybig) attn_exact(x, wqkv, h, qt, sb + SM_X);
  }
  TS_MARK(12);

  COORDS();
  if (wg == 3) {
    if (w == 3) { p3_load_w(lane == 0, 3); p3_load_a(lane == 0, 3); }
    bar_sync(4, 128);
    flush_o(lane == 0, g_o + (qt * 4 + w) * ORB + c0 * 2048, sb + SM_X + w * 6144, odd);
    signal_bulk_if(lane == 0, &g_cnt[C_OA + (qt * 4 + w) * 2 + (h >> 4)]);
    if (wt == 0) atomicAdd(&g_cnt[C_EPOCH], 1);
  } else if (wg == 2) {
    const bool p = lane == 0;
    mbar_wait(bar + 8 * (B_P3EMPTY + w), 0);
    p3_load_w(p, 4 + w);
    if (w > 0) wait_count(&g_cnt[C_OA + rb1 * 2 + kh], epoch * 16);
    p3_load_a(p, 4 + w);
    if (w < 2) {
      mbar_wait(bar + 8 * (B_P3EMPTY + w), 1);
      p3_load_w(p, 8 + w);
      if (w == 0) wait_count(&g_cnt[C_OA + rb1 * 2 + kh], epoch * 16);
      p3_load_a(p, 8 + w);
    }
  } else {
    float acc[96];
    const bool wide = (cg & 1) == wg;
    const int skip = (!wide && (cg & 1)) ? 1 : 0;
    if (wide) {
#pragma unroll 1
      for (int j = 0; j < 10; j++) {
        mbar_wait(bar + 8 * (B_P3FULL + (j & 3)), (j >> 2) & 1);
        if (j == 5) TS_MARK(13);
        if (j < 5) TS_MARK(j == 0 ? 1 : 15 + j);
        const uint32_t dst = sb + (j & 3) * P3_STB;
        const uint64_t da = mkdesc(dst + wg * 1024, 2048, 128, 0), db = mkdesc(dst + 16384, 8192, 1024, 1);
        WG_FENCE();
#pragma unroll
        for (int k = 0; k < 4; k++) wg192_ss(acc, da + k * 256, db + k * 128, (j | k) != 0);
        WG_COMMIT();
        WG_WAIT(1);
        mbar_arrive_if(j > 0 && wt == 0, bar + 8 * (B_P3EMPTY + ((j - 1) & 3)));
      }
      WG_WAIT(0);
    } else {
#pragma unroll 1
      for (int j = 0; j < 10; j++) {
        mbar_wait(bar + 8 * (B_P3FULL + (j & 3)), (j >> 2) & 1);
        if (j == 5) TS_MARK(13);
        if (j < 5) TS_MARK(j == 0 ? 1 : 15 + j);
        const uint32_t dst = sb + (j & 3) * P3_STB;
        const uint64_t da = mkdesc(dst + wg * 1024, 2048, 128, 0), db = mkdesc(dst + 16384 + skip * 8192, 8192, 1024, 1);
        WG_FENCE();
#pragma unroll
        for (int k = 0; k < 4; k++) wg128_ss_of96(acc, da + k * 256, db + k * 128, (j | k) != 0);
        WG_COMMIT();
        WG_WAIT(1);
        mbar_arrive_if(j > 0 && wt == 0, bar + 8 * (B_P3EMPTY + ((j - 1) & 3)));
      }
      WG_WAIT(0);
    }
    pin(acc);
    TS_MARK(14);
    if (!wide) mbar_wait(bar + 8 * (B_P3EMPTY + 2), 1);
    const uint32_t stg = sb + (wide ? 4 : 2) * P3_STB;
    const int r = w * 16 + (lane & 15);
#pragma unroll
    for (int i = 0; i < 24; i += 2)
      if (i < 16 || wide) {
        const int ch = (i & 7) + (lane >> 4);
        stsm4(stg + (i >> 3) * 8192 + r * 128 + ((ch ^ (r & 7)) << 4), pack_bf16(acc[4 * i], acc[4 * i + 1]), pack_bf16(acc[4 * i + 2], acc[4 * i + 3]),
              pack_bf16(acc[4 * i + 4], acc[4 * i + 5]), pack_bf16(acc[4 * i + 6], acc[4 * i + 7]));
      }
    PROXY_FENCE();
    bar_sync(1 + wg, 128);
    if (wt < (wide ? 3 : 2)) {
      PROXY_FENCE_G();
      asm volatile("cp.reduce.async.bulk.tensor.2d.global.shared::cta.add.bulk_group [%0, {%2, %3}], [%1];" ::"l"(&maps.out), "r"(stg + wt * 8192),
                   "r"((atom3 + skip + wt) * 64), "r"(rb1 * 128 + wg * 64) : "memory");
      asm volatile("cp.async.bulk.commit_group;" ::: "memory");
      asm volatile("cp.async.bulk.wait_group 0;" ::: "memory");
    }
    TS_MARK(15);
  }
  TS_DUMP();
}

typedef CUresult (*EncodeFn)(CUtensorMap*, CUtensorMapDataType, cuuint32_t, void*, const cuuint64_t*, const cuuint64_t*, const cuuint32_t*, const cuuint32_t*,
                             CUtensorMapInterleave, CUtensorMapSwizzle, CUtensorMapL2promotion, CUtensorMapFloatOOBfill);
void encode(EncodeFn enc, CUtensorMap* m, void* p, int rank, const cuuint64_t* gd, const cuuint64_t* gs, const cuuint32_t* bd) {
  const cuuint32_t es[3] = {1, 1, 1};
  enc(m, CU_TENSOR_MAP_DATA_TYPE_BFLOAT16, rank, p, gd, gs, bd, es, CU_TENSOR_MAP_INTERLEAVE_NONE, CU_TENSOR_MAP_SWIZZLE_128B,
      CU_TENSOR_MAP_L2_PROMOTION_L2_128B, CU_TENSOR_MAP_FLOAT_OOB_FILL_NONE);
}

}

extern "C" void kernel_launch(void* const* d_in, const int* in_sizes, int n_in, void* d_out, int out_size) {
  static EncodeFn enc = nullptr;
  if (!enc) {
    cudaDriverEntryPointQueryResult qr;
    cudaGetDriverEntryPoint("cuTensorMapEncodeTiled", (void**)&enc, cudaEnableDefault, &qr);
    cudaFuncSetAttribute(gated_mix_kernel, cudaFuncAttributeMaxDynamicSharedMemorySize, SMEM_BYTES);
  }
  Maps m;
  {
    const cuuint64_t gd[2] = {640, 2048}, gs[1] = {1280};
    const cuuint32_t bx[2] = {64, 128}, bo[2] = {64, 64};
    encode(enc, &m.x, d_in[0], 2, gd, gs, bx);
    encode(enc, &m.out, d_out, 2, gd, gs, bo);
  }
  for (int b = 0; b < 2; b++) {
    const cuuint64_t gd[3] = {64, 640, 30}, gs[2] = {3840, 128}, gd3[3] = {64, 640, 10}, gs3[2] = {1280, 128};
    const cuuint32_t bd[3] = {64, 64, 4}, bd3[3] = {64, 64, 3};
    encode(enc, &m.w[b], d_in[b ? 4 : 1], 3, gd, gs, bd);
    encode(enc, &m.wo[b], d_in[b ? 6 : 2], 3, gd3, gs3, bd3);
  }
  {
    void* qp = nullptr;
    cudaGetSymbolAddress(&qp, g_qkv);
    const cuuint64_t gd[5] = {128, 80, 3, 2, 32}, gs[4] = {2048, QTY, 1024, QRB};
    const cuuint32_t bl[5] = {128, 3, 2, 2, 4}, bs[5] = {128, 8, 1, 1, 1}, es[5] = {1, 1, 1, 1, 1};
    enc(&m.qld, CU_TENSOR_MAP_DATA_TYPE_UINT64, 5, qp, gd, gs, bl, es, CU_TENSOR_MAP_INTERLEAVE_NONE, CU_TENSOR_MAP_SWIZZLE_NONE, CU_TENSOR_MAP_L2_PROMOTION_L2_128B, CU_TENSOR_MAP_FLOAT_OOB_FILL_NONE);
    enc(&m.qst, CU_TENSOR_MAP_DATA_TYPE_UINT64, 5, qp, gd, gs, bs, es, CU_TENSOR_MAP_INTERLEAVE_NONE, CU_TENSOR_MAP_SWIZZLE_NONE, CU_TENSOR_MAP_L2_PROMOTION_NONE, CU_TENSOR_MAP_FLOAT_OOB_FILL_NONE);
  }
  gated_mix_kernel<<<128, 512, SMEM_BYTES, cudaStreamPerThread>>>(m, (const __nv_bfloat16*)d_in[0], (const __nv_bfloat16*)d_in[1], (const __nv_bfloat16*)d_in[5],
                                                                 (const __nv_bfloat16*)d_in[7], d_in[4], d_in[2], d_in[6], (uint4*)d_out);
}
```

```cpp
#include <cuda_runtime.h>
#include <cuda.h>
#include <cuda_bf16.h>
#include <cuda_fp16.h>
#include <stdint.h>
#pragma nv_diag_suppress 550

namespace {

constexpr int QRB = 240 * 2048;
constexpr int QBR = 16 * QRB;
constexpr int QTY = 80 * 2048;
constexpr int ORB = 160 * 2048;
constexpr int NMB = 3;

__device__ __align__(1024) uint8_t g_qkv[2 * QBR];
__device__ __align__(1024) uint8_t g_o[16 * ORB];
__device__ float g_gate[2048];
__device__ __align__(16) float g_kv[32 * 960];
__device__ uint32_t g_kbad;
__device__ uint32_t g_fb[128 * 2048 * 20];
__device__ uint32_t g_cnt[192];
constexpr int C_EPOCH = 0, C_TA = 32, C_TB = 64, C_KV = 96, C_OB = 128, C_OA = 160;

#define TS_MARK(i)
#define TS_INIT()
#define TS_REG(x)
#define TS_PUT(i, x, th)
#define TS_FIRST()
#define TS_DUMP()

__device__ __forceinline__ uint64_t mkdesc(uint32_t addr, uint32_t lbo, uint32_t sbo, int mode) {
  return (uint64_t)((addr & 0x3FFFF) >> 4) | ((uint64_t)(lbo >> 4) << 16) | ((uint64_t)(sbo >> 4) << 32) | ((uint64_t)mode << 62);
}
__device__ __forceinline__ uint64_t desc_lohi(uint32_t lo, uint32_t hi) { return ((uint64_t)hi << 32) | lo; }
#define WG_FENCE() asm volatile("wgmma.fence.sync.aligned;" ::: "memory")
#define WG_COMMIT() asm volatile("wgmma.commit_group.sync.aligned;" ::: "memory")
#define WG_WAIT(n) asm volatile("wgmma.wait_group.sync.aligned %0;" ::"n"(n) : "memory")
#define PROXY_FENCE() asm volatile("fence.proxy.async.shared::cta;" ::: "memory")
#define PROXY_FENCE_G() asm volatile("fence.proxy.async.global;" ::: "memory")
__device__ __forceinline__ void bar_sync(int id, int n) { asm volatile("bar.sync %0, %1;" ::"r"(id), "r"(n) : "memory"); }
__device__ __forceinline__ void bar_arrive(int id, int n) { asm volatile("bar.arrive %0, %1;" ::"r"(id), "r"(n) : "memory"); }
__device__ __forceinline__ void mbar_init(uint32_t a, int c) { asm volatile("mbarrier.init.shared::cta.b64 [%0], %1;" ::"r"(a), "r"(c)); }
__device__ __forceinline__ uint32_t mbar_try(uint32_t a, int par) {
  uint32_t ok;
  asm volatile("{.reg .pred p; mbarrier.try_wait.parity.shared::cta.b64 p, [%1], %2; selp.b32 %0, 1, 0, p;}" : "=r"(ok) : "r"(a), "r"(par) : "memory");
  return ok;
}
__device__ __forceinline__ void mbar_wait(uint32_t a, int par) {
  for (int i = 0; !mbar_try(a, par); i++)
    if (i > (1 << 22)) break;
}
__device__ __forceinline__ void mbar_arrive(uint32_t a) { asm volatile("mbarrier.arrive.shared::cta.b64 _, [%0];" ::"r"(a) : "memory"); }
#define E1 "{.reg .pred p; elect.sync _|p, 0xffffffff;\n"
__device__ __forceinline__ void mbar_arrive_e(uint32_t a) { asm volatile(E1 "@p mbarrier.arrive.shared::cta.b64 _, [%0];}" ::"r"(a) : "memory"); }
__device__ __forceinline__ void p1_load_e(uint32_t dst, uint32_t bar, const CUtensorMap* mx, const CUtensorMap* mw, int k, int row, int atom) {
  asm volatile(E1 "@p mbarrier.arrive.expect_tx.shared::cta.b64 _, [%1], 49152;\n"
               "@p cp.async.bulk.tensor.2d.shared::cluster.global.mbarrier::complete_tx::bytes [%0], [%2, {%4, %5}], [%1];\n"
               "@p cp.async.bulk.tensor.3d.shared::cluster.global.mbarrier::complete_tx::bytes [%6], [%3, {%8, %4, %7}], [%1];}"
               ::"r"(dst), "r"(bar), "l"(mx), "l"(mw), "r"(k), "r"(row), "r"(dst + 16384), "r"(atom), "r"(0) : "memory");
}
__device__ __forceinline__ void wo_load_e(uint32_t dst, uint32_t bar, const CUtensorMap* m, int k, int atom) {
  asm volatile(E1 "@p mbarrier.arrive.expect_tx.shared::cta.b64 _, [%1], 40960;\n"
               "@p cp.async.bulk.tensor.3d.shared::cluster.global.mbarrier::complete_tx::bytes [%0], [%2, {%5, %3, %4}], [%1];}"
               ::"r"(dst), "r"(bar), "l"(m), "r"(k), "r"(atom), "r"(0) : "memory");
}
__device__ __forceinline__ void slot_load_e(uint32_t dst, uint32_t bar, const CUtensorMap* m, int chunk, int sec, int rb) {
  asm volatile(E1 "@p mbarrier.arrive.expect_tx.shared::cta.b64 _, [%1], 49152;\n"
               "@p cp.async.bulk.tensor.5d.shared::cluster.global.mbarrier::complete_tx::bytes [%0], [%2, {%6, %3, %4, %6, %5}], [%1];}"
               ::"r"(dst), "r"(bar), "l"(m), "r"(chunk), "r"(sec), "r"(rb), "r"(0) : "memory");
}
__device__ __forceinline__ void atom_store_e(const CUtensorMap* m, uint32_t src, int ga, int half, int rb) {
  asm volatile(E1 "@p cp.async.bulk.tensor.5d.global.shared::cta.bulk_group [%0, {%6, %2, %3, %4, %5}], [%1];}"
               ::"l"(m), "r"(src), "r"((ga % 10) * 8), "r"(ga / 10), "r"(half), "r"(rb), "r"(0) : "memory");
}
__device__ __forceinline__ void bulk_g2s_e(uint32_t dst, const void* src, int bytes, uint32_t bar) {
  asm volatile(E1 "@p cp.async.bulk.shared::cluster.global.mbarrier::complete_tx::bytes [%0], [%1], %2, [%3];}" ::"r"(dst), "l"(src), "r"(bytes), "r"(bar) : "memory");
}
__device__ __forceinline__ void aux_load_e(uint32_t dst, const void* src, int bytes, uint32_t bar) {
  asm volatile(E1 "@p mbarrier.arrive.expect_tx.shared::cta.b64 _, [%3], %2;\n"
               "@p cp.async.bulk.shared::cluster.global.mbarrier::complete_tx::bytes [%0], [%1], %2, [%3];}" ::"r"(dst), "l"(src), "r"(bytes), "r"(bar) : "memory");
}
__device__ __forceinline__ void bulk_s2g_e(void* dst, uint32_t src, int bytes) {
  asm volatile(E1 "@p cp.async.bulk.global.shared::cta.bulk_group [%0], [%1], %2;}" ::"l"(dst), "r"(src), "r"(bytes) : "memory");
}
__device__ __forceinline__ void bulk_or_e(void* dst, uint32_t src, int bytes) {
  asm volatile(E1 "@p cp.reduce.async.bulk.global.shared::cta.bulk_group.or.b32 [%0], [%1], %2;}" ::"l"(dst), "r"(src), "r"(bytes) : "memory");
}
__device__ __forceinline__ void bulk_addf_e(void* dst, uint32_t src, int bytes) {
  asm volatile(E1 "@p cp.reduce.async.bulk.global.shared::cta.bulk_group.add.f32 [%0], [%1], %2;}" ::"l"(dst), "r"(src), "r"(bytes) : "memory");
}
#define BULK_COMMIT() asm volatile("cp.async.bulk.commit_group;" ::: "memory")
#define BULK_WAIT() asm volatile("cp.async.bulk.wait_group 0;" ::: "memory")
#define BULK_WAIT_READ() asm volatile("cp.async.bulk.wait_group.read 0;" ::: "memory")
__device__ __forceinline__ void signal_bulk_e(uint32_t* c) {
  asm volatile(E1 "cp.async.bulk.wait_group 0; @p red.relaxed.gpu.global.add.u32 [%0], 1;}" ::"l"(c) : "memory");
}
__device__ __forceinline__ void wait_count(const uint32_t* c, uint32_t target) {
  for (int i = 0;; i++) {
    uint32_t v;
    asm volatile("ld.relaxed.gpu.global.u32 %0, [%1];" : "=r"(v) : "l"(c) : "memory");
    if ((int)(v - target) >= 0) break;
    if (i > (1 << 20)) break;
  }
  PROXY_FENCE_G();
}
__device__ __forceinline__ uint32_t pack_bf16(float lo, float hi) { uint32_t r; asm("cvt.rn.bf16x2.f32 %0, %1, %2;" : "=r"(r) : "f"(hi), "f"(lo)); return r; }
__device__ __forceinline__ uint32_t pack_f16(float lo, float hi) { uint32_t r; asm("cvt.rn.f16x2.f32 %0, %1, %2;" : "=r"(r) : "f"(hi), "f"(lo)); return r; }
__device__ __forceinline__ float ex2(float a) { float r; asm("ex2.approx.ftz.f32 %0, %1;" : "=f"(r) : "f"(a)); return r; }
__device__ __forceinline__ float ex2n(float a) { float r; asm("{.reg .f32 t; neg.ftz.f32 t, %1; ex2.approx.ftz.f32 %0, t;}" : "=f"(r) : "f"(a)); return r; }
__device__ __forceinline__ float rcp(float a) { float r; asm("rcp.approx.ftz.f32 %0, %1;" : "=f"(r) : "f"(a)); return r; }
__device__ __forceinline__ uint32_t maxabs_bf16x2(uint32_t a, uint32_t b) { uint32_t r; asm("max.NaN.xorsign.abs.bf16x2 %0, %1, %2;" : "=r"(r) : "r"(a), "r"(b)); return r; }
__device__ __forceinline__ uint32_t ldg32(const void* p) { return __ldg(reinterpret_cast<const uint32_t*>(p)); }
__device__ __forceinline__ uint32_t ldcg32(const void* p) { uint32_t v; asm volatile("ld.global.cg.u32 %0, [%1];" : "=r"(v) : "l"(p) : "memory"); return v; }
__device__ __forceinline__ uint32_t lds32(uint32_t a) { uint32_t v; asm volatile("ld.shared.b32 %0, [%1];" : "=r"(v) : "r"(a) : "memory"); return v; }
__device__ __forceinline__ void sts32(uint32_t a, uint32_t v) { asm volatile("st.shared.b32 [%0], %1;" ::"r"(a), "r"(v) : "memory"); }
__device__ __forceinline__ void sts16(uint32_t a, uint16_t v) { asm volatile("st.shared.b16 [%0], %1;" ::"r"(a), "h"(v) : "memory"); }
__device__ __forceinline__ void stsm4(uint32_t a, uint32_t r0, uint32_t r1, uint32_t r2, uint32_t r3) {
  asm volatile("stmatrix.sync.aligned.m8n8.x4.shared.b16 [%0], {%1, %2, %3, %4};" ::"r"(a), "r"(r0), "r"(r1), "r"(r2), "r"(r3) : "memory");
}
template <int N> __device__ __forceinline__ void pin(float (&d)[N]) {
#pragma unroll
  for (int i = 0; i < N; i++) asm volatile("" : "+f"(d[i])::"memory");
}

__device__ __forceinline__ void wg128_ss(float (&d)[64], uint64_t da, uint64_t db, int scale_d) {
  asm volatile("{\n.reg .pred p;\nsetp.ne.b32 p, %66, 0;\n"
    "wgmma.mma_async.sync.aligned.m64n128k16.f32.bf16.bf16 "
    "{%0, %1, %2, %3, %4, %5, %6, %7, %8, %9, %10, %11, %12, %13, %14, %15,"
    "%16, %17, %18, %19, %20, %21, %22, %23, %24, %25, %26, %27, %28, %29, %30, %31,"
    "%32, %33, %34, %35, %36, %37, %38, %39, %40, %41, %42, %43, %44, %45, %46, %47,"
    "%48, %49, %50, %51, %52, %53, %54, %55, %56, %57, %58, %59, %60, %61, %62, %63}, "
    "%64, %65, p, 1, 1, 0, 1;\n}\n"
    : "+f"(d[0]), "+f"(d[1]), "+f"(d[2]), "+f"(d[3]), "+f"(d[4]), "+f"(d[5]), "+f"(d[6]), "+f"(d[7]),
      "+f"(d[8]), "+f"(d[9]), "+f"(d[10]), "+f"(d[11]), "+f"(d[12]), "+f"(d[13]), "+f"(d[14]), "+f"(d[15]),
      "+f"(d[16]), "+f"(d[17]), "+f"(d[18]), "+f"(d[19]), "+f"(d[20]), "+f"(d[21]), "+f"(d[22]), "+f"(d[23]),
      "+f"(d[24]), "+f"(d[25]), "+f"(d[26]), "+f"(d[27]), "+f"(d[28]), "+f"(d[29]), "+f"(d[30]), "+f"(d[31]),
      "+f"(d[32]), "+f"(d[33]), "+f"(d[34]), "+f"(d[35]), "+f"(d[36]), "+f"(d[37]), "+f"(d[38]), "+f"(d[39]),
      "+f"(d[40]), "+f"(d[41]), "+f"(d[42]), "+f"(d[43]), "+f"(d[44]), "+f"(d[45]), "+f"(d[46]), "+f"(d[47]),
      "+f"(d[48]), "+f"(d[49]), "+f"(d[50]), "+f"(d[51]), "+f"(d[52]), "+f"(d[53]), "+f"(d[54]), "+f"(d[55]),
      "+f"(d[56]), "+f"(d[57]), "+f"(d[58]), "+f"(d[59]), "+f"(d[60]), "+f"(d[61]), "+f"(d[62]), "+f"(d[63])
    : "l"(da), "l"(db), "r"(scale_d));
}

__device__ __forceinline__ void wg64_ss_of64(float (&d)[64], uint64_t da, uint64_t db, int scale_d) {
  asm volatile("{\n.reg .pred p;\nsetp.ne.b32 p, %34, 0;\n"
    "wgmma.mma_async.sync.aligned.m64n64k16.f32.bf16.bf16 "
    "{%0, %1, %2, %3, %4, %5, %6, %7, %8, %9, %10, %11, %12, %13, %14, %15,"
    "%16, %17, %18, %19, %20, %21, %22, %23, %24, %25, %26, %27, %28, %29, %30, %31}, "
    "%32, %33, p, 1, 1, 0, 1;\n}\n"
    : "+f"(d[0]), "+f"(d[1]), "+f"(d[2]), "+f"(d[3]), "+f"(d[4]), "+f"(d[5]), "+f"(d[6]), "+f"(d[7]),
      "+f"(d[8]), "+f"(d[9]), "+f"(d[10]), "+f"(d[11]), "+f"(d[12]), "+f"(d[13]), "+f"(d[14]), "+f"(d[15]),
      "+f"(d[16]), "+f"(d[17]), "+f"(d[18]), "+f"(d[19]), "+f"(d[20]), "+f"(d[21]), "+f"(d[22]), "+f"(d[23]),
      "+f"(d[24]), "+f"(d[25]), "+f"(d[26]), "+f"(d[27]), "+f"(d[28]), "+f"(d[29]), "+f"(d[30]), "+f"(d[31])
    : "l"(da), "l"(db), "r"(scale_d));
}

__device__ __forceinline__ void wg192_ss(float (&d)[96], uint64_t da, uint64_t db, int scale_d) {
  asm volatile("{\n.reg .pred p;\nsetp.ne.b32 p, %98, 0;\n"
    "wgmma.mma_async.sync.aligned.m64n192k16.f32.bf16.bf16 "
    "{%0, %1, %2, %3, %4, %5, %6, %7, %8, %9, %10, %11, %12, %13, %14, %15,"
    "%16, %17, %18, %19, %20, %21, %22, %23, %24, %25, %26, %27, %28, %29, %30, %31,"
    "%32, %33, %34, %35, %36, %37, %38, %39, %40, %41, %42, %43, %44, %45, %46, %47,"
    "%48, %49, %50, %51, %52, %53, %54, %55, %56, %57, %58, %59, %60, %61, %62, %63,"
    "%64, %65, %66, %67, %68, %69, %70, %71, %72, %73, %74, %75, %76, %77, %78, %79,"
    "%80, %81, %82, %83, %84, %85, %86, %87, %88, %89, %90, %91, %92, %93, %94, %95}, "
    "%96, %97, p, 1, 1, 0, 1;\n}\n"
    : "+f"(d[0]), "+f"(d[1]), "+f"(d[2]), "+f"(d[3]), "+f"(d[4]), "+f"(d[5]), "+f"(d[6]), "+f"(d[7]),
      "+f"(d[8]), "+f"(d[9]), "+f"(d[10]), "+f"(d[11]), "+f"(d[12]), "+f"(d[13]), "+f"(d[14]), "+f"(d[15]),
      "+f"(d[16]), "+f"(d[17]), "+f"(d[18]), "+f"(d[19]), "+f"(d[20]), "+f"(d[21]), "+f"(d[22]), "+f"(d[23]),
      "+f"(d[24]), "+f"(d[25]), "+f"(d[26]), "+f"(d[27]), "+f"(d[28]), "+f"(d[29]), "+f"(d[30]), "+f"(d[31]),
      "+f"(d[32]), "+f"(d[33]), "+f"(d[34]), "+f"(d[35]), "+f"(d[36]), "+f"(d[37]), "+f"(d[38]), "+f"(d[39]),
      "+f"(d[40]), "+f"(d[41]), "+f"(d[42]), "+f"(d[43]), "+f"(d[44]), "+f"(d[45]), "+f"(d[46]), "+f"(d[47]),
      "+f"(d[48]), "+f"(d[49]), "+f"(d[50]), "+f"(d[51]), "+f"(d[52]), "+f"(d[53]), "+f"(d[54]), "+f"(d[55]),
      "+f"(d[56]), "+f"(d[57]), "+f"(d[58]), "+f"(d[59]), "+f"(d[60]), "+f"(d[61]), "+f"(d[62]), "+f"(d[63]),
      "+f"(d[64]), "+f"(d[65]), "+f"(d[66]), "+f"(d[67]), "+f"(d[68]), "+f"(d[69]), "+f"(d[70]), "+f"(d[71]),
      "+f"(d[72]), "+f"(d[73]), "+f"(d[74]), "+f"(d[75]), "+f"(d[76]), "+f"(d[77]), "+f"(d[78]), "+f"(d[79]),
      "+f"(d[80]), "+f"(d[81]), "+f"(d[82]), "+f"(d[83]), "+f"(d[84]), "+f"(d[85]), "+f"(d[86]), "+f"(d[87]),
      "+f"(d[88]), "+f"(d[89]), "+f"(d[90]), "+f"(d[91]), "+f"(d[92]), "+f"(d[93]), "+f"(d[94]), "+f"(d[95])
    : "l"(da), "l"(db), "r"(scale_d));
}

__device__ __forceinline__ void wg128_ss_of96(float (&d)[96], uint64_t da, uint64_t db, int scale_d) {
  asm volatile("{\n.reg .pred p;\nsetp.ne.b32 p, %66, 0;\n"
    "wgmma.mma_async.sync.aligned.m64n128k16.f32.bf16.bf16 "
    "{%0, %1, %2, %3, %4, %5, %6, %7, %8, %9, %10, %11, %12, %13, %14, %15,"
    "%16, %17, %18, %19, %20, %21, %22, %23, %24, %25, %26, %27, %28, %29, %30, %31,"
    "%32, %33, %34, %35, %36, %37, %38, %39, %40, %41, %42, %43, %44, %45, %46, %47,"
    "%48, %49, %50, %51, %52, %53, %54, %55, %56, %57, %58, %59, %60, %61, %62, %63}, "
    "%64, %65, p, 1, 1, 0, 1;\n}\n"
    : "+f"(d[0]), "+f"(d[1]), "+f"(d[2]), "+f"(d[3]), "+f"(d[4]), "+f"(d[5]), "+f"(d[6]), "+f"(d[7]),
      "+f"(d[8]), "+f"(d[9]), "+f"(d[10]), "+f"(d[11]), "+f"(d[12]), "+f"(d[13]), "+f"(d[14]), "+f"(d[15]),
      "+f"(d[16]), "+f"(d[17]), "+f"(d[18]), "+f"(d[19]), "+f"(d[20]), "+f"(d[21]), "+f"(d[22]), "+f"(d[23]),
      "+f"(d[24]), "+f"(d[25]), "+f"(d[26]), "+f"(d[27]), "+f"(d[28]), "+f"(d[29]), "+f"(d[30]), "+f"(d[31]),
      "+f"(d[32]), "+f"(d[33]), "+f"(d[34]), "+f"(d[35]), "+f"(d[36]), "+f"(d[37]), "+f"(d[38]), "+f"(d[39]),
      "+f"(d[40]), "+f"(d[41]), "+f"(d[42]), "+f"(d[43]), "+f"(d[44]), "+f"(d[45]), "+f"(d[46]), "+f"(d[47]),
      "+f"(d[48]), "+f"(d[49]), "+f"(d[50]), "+f"(d[51]), "+f"(d[52]), "+f"(d[53]), "+f"(d[54]), "+f"(d[55]),
      "+f"(d[56]), "+f"(d[57]), "+f"(d[58]), "+f"(d[59]), "+f"(d[60]), "+f"(d[61]), "+f"(d[62]), "+f"(d[63])
    : "l"(da), "l"(db), "r"(scale_d));
}

__device__ __forceinline__ void wg64_rs_bf16(float (&d)[32], uint32_t a0, uint32_t a1, uint32_t a2, uint32_t a3, uint64_t db, int scale_d) {
  asm volatile("{\n.reg .pred p;\nsetp.ne.b32 p, %37, 0;\n"
    "wgmma.mma_async.sync.aligned.m64n64k16.f32.bf16.bf16 "
    "{%0, %1, %2, %3, %4, %5, %6, %7, %8, %9, %10, %11, %12, %13, %14, %15,"
    "%16, %17, %18, %19, %20, %21, %22, %23, %24, %25, %26, %27, %28, %29, %30, %31}, "
    "{%32, %33, %34, %35}, %36, p, 1, 1, 0;\n}\n"
    : "+f"(d[0]), "+f"(d[1]), "+f"(d[2]), "+f"(d[3]), "+f"(d[4]), "+f"(d[5]), "+f"(d[6]), "+f"(d[7]),
      "+f"(d[8]), "+f"(d[9]), "+f"(d[10]), "+f"(d[11]), "+f"(d[12]), "+f"(d[13]), "+f"(d[14]), "+f"(d[15]),
      "+f"(d[16]), "+f"(d[17]), "+f"(d[18]), "+f"(d[19]), "+f"(d[20]), "+f"(d[21]), "+f"(d[22]), "+f"(d[23]),
      "+f"(d[24]), "+f"(d[25]), "+f"(d[26]), "+f"(d[27]), "+f"(d[28]), "+f"(d[29]), "+f"(d[30]), "+f"(d[31])
    : "r"(a0), "r"(a1), "r"(a2), "r"(a3), "l"(db), "r"(scale_d));
}

__device__ __forceinline__ void wg24_rs_f16_t(float (&d)[12], uint32_t a0, uint32_t a1, uint32_t a2, uint32_t a3, uint64_t db, int scale_d) {
  asm volatile("{\n.reg .pred p;\nsetp.ne.b32 p, %17, 0;\n"
    "wgmma.mma_async.sync.aligned.m64n24k16.f32.f16.f16 "
    "{%0, %1, %2, %3, %4, %5, %6, %7, %8, %9, %10, %11}, "
    "{%12, %13, %14, %15}, %16, p, 1, 1, 1;\n}\n"
    : "+f"(d[0]), "+f"(d[1]), "+f"(d[2]), "+f"(d[3]), "+f"(d[4]), "+f"(d[5]), "+f"(d[6]), "+f"(d[7]),
      "+f"(d[8]), "+f"(d[9]), "+f"(d[10]), "+f"(d[11])
    : "r"(a0), "r"(a1), "r"(a2), "r"(a3), "l"(db), "r"(scale_d));
}

__device__ __forceinline__ void wg24_rs_bf16(float (&d)[12], uint32_t a0, uint32_t a1, uint32_t a2, uint32_t a3, uint64_t db, int scale_d) {
  asm volatile("{\n.reg .pred p;\nsetp.ne.b32 p, %17, 0;\n"
    "wgmma.mma_async.sync.aligned.m64n24k16.f32.bf16.bf16 "
    "{%0, %1, %2, %3, %4, %5, %6, %7, %8, %9, %10, %11}, "
    "{%12, %13, %14, %15}, %16, p, 1, 1, 0;\n}\n"
    : "+f"(d[0]), "+f"(d[1]), "+f"(d[2]), "+f"(d[3]), "+f"(d[4]), "+f"(d[5]), "+f"(d[6]), "+f"(d[7]),
      "+f"(d[8]), "+f"(d[9]), "+f"(d[10]), "+f"(d[11])
    : "r"(a0), "r"(a1), "r"(a2), "r"(a3), "l"(db), "r"(scale_d));
}

__device__ __forceinline__ void wg24_ss_bf16_tt(float (&d)[12], uint64_t da, uint64_t db, int scale_d) {
  asm volatile("{\n.reg .pred p;\nsetp.ne.b32 p, %14, 0;\n"
    "wgmma.mma_async.sync.aligned.m64n24k16.f32.bf16.bf16 "
    "{%0, %1, %2, %3, %4, %5, %6, %7, %8, %9, %10, %11}, "
    "%12, %13, p, 1, 1, 1, 1;\n}\n"
    : "+f"(d[0]), "+f"(d[1]), "+f"(d[2]), "+f"(d[3]), "+f"(d[4]), "+f"(d[5]), "+f"(d[6]), "+f"(d[7]),
      "+f"(d[8]), "+f"(d[9]), "+f"(d[10]), "+f"(d[11])
    : "l"(da), "l"(db), "r"(scale_d));
}

__device__ __forceinline__ void wg64_rs_bf16_i(float (&d)[32], uint32_t a0, uint32_t a1, uint32_t a2, uint32_t a3, uint64_t db) {
  asm volatile("{\n.reg .pred p;\nsetp.ne.b32 p, 0, 0;\n"
    "wgmma.mma_async.sync.aligned.m64n64k16.f32.bf16.bf16 "
    "{%0, %1, %2, %3, %4, %5, %6, %7, %8, %9, %10, %11, %12, %13, %14, %15,"
    "%16, %17, %18, %19, %20, %21, %22, %23, %24, %25, %26, %27, %28, %29, %30, %31}, "
    "{%32, %33, %34, %35}, %36, p, 1, 1, 0;\n}\n"
    : "=f"(d[0]), "=f"(d[1]), "=f"(d[2]), "=f"(d[3]), "=f"(d[4]), "=f"(d[5]), "=f"(d[6]), "=f"(d[7]),
      "=f"(d[8]), "=f"(d[9]), "=f"(d[10]), "=f"(d[11]), "=f"(d[12]), "=f"(d[13]), "=f"(d[14]), "=f"(d[15]),
      "=f"(d[16]), "=f"(d[17]), "=f"(d[18]), "=f"(d[19]), "=f"(d[20]), "=f"(d[21]), "=f"(d[22]), "=f"(d[23]),
      "=f"(d[24]), "=f"(d[25]), "=f"(d[26]), "=f"(d[27]), "=f"(d[28]), "=f"(d[29]), "=f"(d[30]), "=f"(d[31])
    : "r"(a0), "r"(a1), "r"(a2), "r"(a3), "l"(db));
}

__device__ __forceinline__ void wg24_rs_bf16_i(float (&d)[12], uint32_t a0, uint32_t a1, uint32_t a2, uint32_t a3, uint64_t db) {
  asm volatile("{\n.reg .pred p;\nsetp.ne.b32 p, 0, 0;\n"
    "wgmma.mma_async.sync.aligned.m64n24k16.f32.bf16.bf16 "
    "{%0, %1, %2, %3, %4, %5, %6, %7, %8, %9, %10, %11}, "
    "{%12, %13, %14, %15}, %16, p, 1, 1, 0;\n}\n"
    : "=f"(d[0]), "=f"(d[1]), "=f"(d[2]), "=f"(d[3]), "=f"(d[4]), "=f"(d[5]), "=f"(d[6]), "=f"(d[7]),
      "=f"(d[8]), "=f"(d[9]), "=f"(d[10]), "=f"(d[11])
    : "r"(a0), "r"(a1), "r"(a2), "r"(a3), "l"(db));
}

__device__ __forceinline__ void wg24_ss_bf16_tt_i(float (&d)[12], uint64_t da, uint64_t db) {
  asm volatile("{\n.reg .pred p;\nsetp.ne.b32 p, 0, 0;\n"
    "wgmma.mma_async.sync.aligned.m64n24k16.f32.bf16.bf16 "
    "{%0, %1, %2, %3, %4, %5, %6, %7, %8, %9, %10, %11}, "
    "%12, %13, p, 1, 1, 1, 1;\n}\n"
    : "=f"(d[0]), "=f"(d[1]), "=f"(d[2]), "=f"(d[3]), "=f"(d[4]), "=f"(d[5]), "=f"(d[6]), "=f"(d[7]),
      "=f"(d[8]), "=f"(d[9]), "=f"(d[10]), "=f"(d[11])
    : "l"(da), "l"(db));
}

__device__ __forceinline__ void wg24_ss_bf16(float (&d)[12], uint64_t da, uint64_t db, int scale_d) {
  asm volatile("{\n.reg .pred p;\nsetp.ne.b32 p, %14, 0;\n"
    "wgmma.mma_async.sync.aligned.m64n24k16.f32.bf16.bf16 "
    "{%0, %1, %2, %3, %4, %5, %6, %7, %8, %9, %10, %11}, "
    "%12, %13, p, 1, 1, 0, 0;\n}\n"
    : "+f"(d[0]), "+f"(d[1]), "+f"(d[2]), "+f"(d[3]), "+f"(d[4]), "+f"(d[5]), "+f"(d[6]), "+f"(d[7]),
      "+f"(d[8]), "+f"(d[9]), "+f"(d[10]), "+f"(d[11])
    : "l"(da), "l"(db), "r"(scale_d));
}

__device__ __forceinline__ void wg24_ss_bf16_i(float (&d)[12], uint64_t da, uint64_t db) {
  asm volatile("{\n.reg .pred p;\nsetp.ne.b32 p, 0, 0;\n"
    "wgmma.mma_async.sync.aligned.m64n24k16.f32.bf16.bf16 "
    "{%0, %1, %2, %3, %4, %5, %6, %7, %8, %9, %10, %11}, "
    "%12, %13, p, 1, 1, 0, 0;\n}\n"
    : "=f"(d[0]), "=f"(d[1]), "=f"(d[2]), "=f"(d[3]), "=f"(d[4]), "=f"(d[5]), "=f"(d[6]), "=f"(d[7]),
      "=f"(d[8]), "=f"(d[9]), "=f"(d[10]), "=f"(d[11])
    : "l"(da), "l"(db));
}

constexpr int P1_STB = 49152, P3_STB = 40960;
constexpr int SM_X = 196608;
constexpr int SM_KVB = SM_X + 24576;
constexpr int SM_GW = SM_X + 8192, SM_WRAW = SM_GW + 1280, SM_EP = SM_WRAW + 800;
constexpr int SM_CONST = SM_X + 32768, SM_WPHI = SM_CONST + 1024, SM_BAR = SM_WPHI + 1536;
constexpr int SMEM_BYTES = SM_BAR + 512;
constexpr int B_FULL = 0, B_AUX = 4, B_KB = 5, B_QB = 6, B_KVFULL = 7, B_P3FULL = 11, B_P3EMPTY = 15, B_EMPTY = 19, B_LINK = 23, B_FREE = 25,
              B_STG = 28, B_B2 = 29, B_ZERO = 30, B_READY = 31, B_KVB = 35;

template <int V> struct Int { static constexpr int value = V; };
struct Maps { CUtensorMap x, w[2], wo[2], out, qld, qst; };

__device__ __forceinline__ int tile_atom(int t) { return (t >> 2) * 15 + ((0xB740 >> ((t & 3) * 4)) & 15); }

template <int MODE, int A>
__device__ __forceinline__ void pack_atom(const float (&acc)[64], uint32_t (&r)[32], float s0, float s1, uint32_t& m0, uint32_t& m1) {
#pragma unroll
  for (int e = A * 16; e < A * 16 + 16; e++) {
    const float s = (e & 1) ? s1 : s0;
    if (MODE == 0) r[e] = pack_bf16(acc[2 * e], acc[2 * e + 1]);
    else if (MODE == 3) r[e] = pack_f16(acc[2 * e], acc[2 * e + 1]);
    else r[e] = pack_bf16(acc[2 * e] * s, acc[2 * e + 1] * s);
    if (MODE == 2) { if (e & 1) m1 = maxabs_bf16x2(m1, r[e]); else m0 = maxabs_bf16x2(m0, r[e]); }
  }
}
template <int A>
__device__ __forceinline__ void pack_atom_a(const float (&acc)[64], uint32_t (&r)[32], int ga, float sk0, float sk1, uint32_t& m0, uint32_t& m1) {
  if (ga < 10) { const float cq = __uint_as_float(463809372u); pack_atom<1, A>(acc, r, cq, cq, m0, m1); }
  else if (ga < 20) pack_atom<2, A>(acc, r, sk0, sk1, m0, m1);
  else pack_atom<3, A>(acc, r, 0.f, 0.f, m0, m1);
}

__device__ __forceinline__ uint32_t exp2_pair(float a, float b, uint32_t wbase) {
  uint32_t z, w, h;
  asm volatile("cvt.pack.sat.s16.s32 %0, %2, %1;" : "=r"(z) : "r"(__float_as_uint(a)), "r"(__float_as_uint(b)));
  asm volatile("lop3.b32 %0, %1, 0x03ff03ff, %2, 0xEA;" : "=r"(w) : "r"(z), "r"(wbase));
  asm volatile("fma.rn.f16x2 %0, %1, %1, %2;" : "=r"(h) : "r"(w), "r"(0x36203620));
  asm volatile("fma.rn.f16x2 %0, %0, %1, %2;" : "+r"(h) : "r"(w), "r"(0x2e012e01));
  return h + z - w;
}
__device__ __forceinline__ uint32_t exp2_pair_mufu(float a, float b) {
  float x, y; uint32_t r;
  asm volatile("ex2.approx.ftz.f32 %0, %1;" : "=f"(x) : "f"(a));
  asm volatile("ex2.approx.ftz.f32 %0, %1;" : "=f"(y) : "f"(b));
  asm volatile("cvt.rn.f16x2.f32 %0, %1, %2;" : "=r"(r) : "f"(y), "f"(x));
  return r;
}
__device__ __forceinline__ void load_frag(uint32_t (&a)[6], const uint8_t* p) {
  a[0] = ldcg32(p); a[1] = ldcg32(p + 128); a[2] = ldcg32(p + 2048); a[3] = ldcg32(p + 2048 + 128); a[4] = ldcg32(p + 4096); a[5] = ldcg32(p + 4096 + 128);
}
template <bool EXACT>
__device__ __forceinline__ bool feature_rows(uint32_t (&phi)[10], const float (&p)[12]) {
  const float L = 1.4426950408889634f;
  bool ok = true;
#pragma unroll
  for (int r = 0; r < 2; r++) {
    const float v[5] = {p[2 * r], p[2 * r + 1], p[4 + 2 * r], p[5 + 2 * r], p[8 + 2 * r]};
    float ep[5], en[5];
    if (EXACT) {
      float mx = fmaxf(fmaxf(fmaxf(v[0], v[1]), fmaxf(v[2], v[3])), v[4]);
      float mn = fminf(fminf(fminf(v[0], v[1]), fminf(v[2], v[3])), v[4]);
      mx = fmaxf(mx, __shfl_xor_sync(0xffffffffu, mx, 1)); mn = fminf(mn, __shfl_xor_sync(0xffffffffu, mn, 1));
      mx = fmaxf(mx, __shfl_xor_sync(0xffffffffu, mx, 2)); mn = fminf(mn, __shfl_xor_sync(0xffffffffu, mn, 2));
#pragma unroll
      for (int i = 0; i < 5; i++) { ep[i] = ex2((v[i] - mx) * L); en[i] = ex2((mn - v[i]) * L); }
    } else {
#pragma unroll
      for (int i = 0; i < 5; i++) { const float u = v[i] * L; ep[i] = ex2(u); en[i] = ex2n(u); }
    }
    float sp = (ep[0] + ep[1]) + (ep[2] + ep[3]) + ep[4], sn = (en[0] + en[1]) + (en[2] + en[3]) + en[4];
    sp += __shfl_xor_sync(0xffffffffu, sp, 1); sn += __shfl_xor_sync(0xffffffffu, sn, 1);
    sp += __shfl_xor_sync(0xffffffffu, sp, 2); sn += __shfl_xor_sync(0xffffffffu, sn, 2);
    ok = ok && sp + sn < 1.2676506e30f;
    const float rp = rcp(sp), rn = rcp(sn);
#pragma unroll
    for (int i = 0; i < 5; i++) phi[5 * r + i] = pack_bf16(ep[i] * rp, en[i] * rn);
  }
  return ok;
}
__device__ __forceinline__ void feature_map(uint32_t (&phi)[10], const float (&p)[12]) {
  if (!__all_sync(0xffffffffu, feature_rows<false>(phi, p))) feature_rows<true>(phi, p);
}
__device__ __forceinline__ void phi_proj(float (&p0)[12], float (&p1)[12], uint32_t a, uint64_t dw) {
  const uint64_t da = mkdesc(a, 1024, 128, 0), db = mkdesc(a + 2048, 0, 128, 0);
  WG_FENCE();
  wg24_ss_bf16_i(p0, da, dw);
  wg24_ss_bf16(p0, db, dw + 48, 1);
  wg24_ss_bf16_i(p1, da + 384, dw);
  wg24_ss_bf16(p1, db + 384, dw + 48, 1);
  WG_COMMIT();
  WG_WAIT(0);
  pin(p0); pin(p1);
}
__device__ __forceinline__ void stage_o(const float (&o)[12], float s0, float s1, uint32_t a, bool v0, bool v2) {
#pragma unroll
  for (int j = 0; j < 3; j++) {
    const bool v = j == 1 || (j == 0 ? v0 : v2);
    sts32(a + j * 2048, v ? pack_bf16(o[4 * j] * s0, o[4 * j + 1] * s0) : 0u);
    sts32(a + j * 2048 + 128, v ? pack_bf16(o[4 * j + 2] * s1, o[4 * j + 3] * s1) : 0u);
  }
}
__device__ __forceinline__ void flush_o(uint8_t* dst, uint32_t src, bool odd) {
  bulk_s2g_e(dst + (odd ? 2048 : 0), src + (odd ? 2048 : 0), 4096);
  bulk_or_e(dst + (odd ? 0 : 4096), src + (odd ? 0 : 4096), 2048);
  BULK_COMMIT();
}

__device__ __forceinline__ void proj20(float (&acc)[20], const __nv_bfloat16* __restrict__ xr, const __nv_bfloat16* __restrict__ wc) {
#pragma unroll
  for (int d = 0; d < 20; d++) acc[d] = 0.f;
#pragma unroll 2
  for (int k = 0; k < 640; k++) {
    const float xv = __bfloat162float(xr[k]);
#pragma unroll
    for (int d = 0; d < 10; d++) {
      const uint32_t u = ldg32(wc + k * 1920 + 2 * d);
      acc[2 * d] = fmaf(xv, __uint_as_float(u << 16), acc[2 * d]);
      acc[2 * d + 1] = fmaf(xv, __uint_as_float(u & 0xffff0000u), acc[2 * d + 1]);
    }
  }
}
__device__ __noinline__ void attn_exact(const __nv_bfloat16* __restrict__ x, const __nv_bfloat16* __restrict__ wqkv, int h, int qt, uint32_t stg) {
  const int tid = threadIdx.x;
  uint32_t* kvs = g_fb + blockIdx.x * (2048 * 20);
  float a[20];
  for (int i = 0; i < 8; i++) {
    const int key = (i >> 1) * 512 + tid, ty = 1 + (i & 1);
    proj20(a, x + key * 640, wqkv + ty * 640 + h * 20);
#pragma unroll
    for (int d = 0; d < 10; d++) kvs[key * 20 + (i & 1) * 10 + d] = pack_bf16(a[2 * d], a[2 * d + 1]);
  }
  const int row = qt * 512 + tid;
  proj20(a, x + row * 640, wqkv + h * 20);
#pragma unroll
  for (int d = 0; d < 20; d++) a[d] = __bfloat162float(__float2bfloat16(a[d]));
  __syncthreads();
  float o[20], m = -INFINITY, l = 0.f;
#pragma unroll
  for (int d = 0; d < 20; d++) o[d] = 0.f;
  for (int key = 0; key < 2048; key++) {
    uint32_t u[20];
#pragma unroll
    for (int d = 0; d < 5; d++) {
      const uint4 t4 = *reinterpret_cast<const uint4*>(kvs + key * 20 + 4 * d);
      u[4 * d] = t4.x; u[4 * d + 1] = t4.y; u[4 * d + 2] = t4.z; u[4 * d + 3] = t4.w;
    }
    float s = 0.f;
#pragma unroll
    for (int d = 0; d < 10; d++) {
      s = fmaf(a[2 * d], __uint_as_float(u[d] << 16), s);
      s = fmaf(a[2 * d + 1], __uint_as_float(u[d] & 0xffff0000u), s);
    }
    s *= 0.22360679774997896f;
    const float mn = fmaxf(m, s), cr = __expf(m - mn), p = __expf(s - mn);
    m = mn;
    l = l * cr + p;
#pragma unroll
    for (int d = 0; d < 10; d++) {
      o[2 * d] = fmaf(p, __uint_as_float(u[10 + d] << 16), o[2 * d] * cr);
      o[2 * d + 1] = fmaf(p, __uint_as_float(u[10 + d] & 0xffff0000u), o[2 * d + 1] * cr);
    }
  }
  const float sc = __ldcg(&g_gate[row]) / l;
#pragma unroll
  for (int d = 0; d < 10; d++) {
    const int col = (h & 1) * 4 + 2 * d;
    sts32(stg + (tid >> 7) * 6144 + (col >> 3) * 2048 + (tid & 127) * 16 + (col & 7) * 2, pack_bf16(o[2 * d] * sc, o[2 * d + 1] * sc));
  }
  PROXY_FENCE();
  __syncthreads();
}

#define COORDS()                                                                                                        \
  int tid, bid;                                                                                                         \
  asm volatile("mov.u32 %0, %%tid.x;" : "=r"(tid));                                                                     \
  asm volatile("mov.u32 %0, %%ctaid.x;" : "=r"(bid));                                                                   \
  const int wi = __shfl_sync(0xffffffffu, tid >> 5, 0), wg = wi >> 2;                                                   \
  const int lane = tid & 31, w = wi & 3, g = lane >> 2, t = lane & 3, wt = tid & 127;                           \
  const int rb1 = bid >> 3, c1 = bid & 7;                                       \
  const int h = bid >> 2, qt = bid & 3, rb = qt * 4 + wg;                    \
  const bool odd = h & 1;                                                                                               \
  const int c0 = (h * 5) >> 1;                                               \
  const int lsrc = (lane & ~3) | (odd ? 0 : 2);                                                                         \
  const bool v0 = !odd || t >= 2, v2 = odd || t < 2;                                                                    \
  const uint32_t ostg = sb + SM_X + wg * 6144, orow = (w * 16 + g) * 16 + t * 4;                                        \
  const uint32_t onepos = (wt >> 6) * 6144 + 3072 + (odd ? 0 : 2048 + 8) + (wt & 63) * 16;                              \
  const int kh = bid & 1, cg = (bid >> 1) & 3, atom3 = (cg >> 1) * 5 + (cg & 1) * 2;                                    \
  auto p3_load_w = [&](int j) {                                                                                         \
    wo_load_e(sb + (j & 3) * P3_STB + 16384, bar + 8 * (B_P3FULL + (j & 3)), &maps.wo[j < 5], (kh * 5 + (j < 5 ? j : j - 5)) * 64, atom3); \
  };                                                                                                                    \
  auto p3_load_a = [&](int j) {                                                                                         \
    bulk_g2s_e(sb + (j & 3) * P3_STB, g_o + rb1 * ORB + ((j < 5 ? 10 + j : j - 5) + kh * 5) * 16384, 16384, bar + 8 * (B_P3FULL + (j & 3))); \
  };                                                                                                                    \
  (void)g; (void)t; (void)wt; (void)rb1; (void)c1; (void)rb; (void)c0; (void)lsrc; (void)v0; (void)v2; (void)ostg;      \
  (void)orow; (void)onepos; (void)atom3; (void)p3_load_w; (void)p3_load_a

#define P1_LOAD()                                                                                                       \
  auto p1_load = [&](int it) {                                                                                          \
    const int b2 = it >= 10;                                                                                            \
    p1_load_e(sb + (it & 3) * P1_STB, bar + 8 * (B_FULL + (it & 3)), &maps.x, &maps.w[b2], (it - b2 * 10) * 64, rb1 * 128, tile_atom(c1 ^ b2)); \
  }

__global__ void __launch_bounds__(512, 1)
gated_mix_kernel(const __grid_constant__ Maps maps, const __nv_bfloat16* __restrict__ x, const __nv_bfloat16* __restrict__ wqkv, const __nv_bfloat16* __restrict__ w_phi,
                 const __nv_bfloat16* __restrict__ gate_w, const void* wqkv_b, const void* wo_a, const void* wo_b, uint4* __restrict__ out) {
  extern __shared__ __align__(1024) uint8_t smem_raw[];
  const uint32_t sb = (uint32_t)__cvta_generic_to_shared(smem_raw);
  const uint32_t bar = sb + SM_BAR;
  uint32_t q[2][6], qc[5], epoch;
  uint64_t events;
  int bad;
  {
  COORDS();
  TS_INIT();

  P1_LOAD();
  if (w == 0) {
    if (lane == 0) { mbar_init(bar + 8 * (B_FULL + wg), 1); asm volatile("fence.mbarrier_init.release.cluster;" ::: "memory"); }
    __syncwarp();
    if (wg == 0) p1_load(0);
  }
  TS_REG(tsa_);
  if (wt == 32) {
#pragma unroll
    for (int u = 0; u < 4; u++)
      if (wg == u) {
#pragma unroll
        for (int i = B_AUX + u * 8; i < B_AUX + u * 8 + 8; i++)
          mbar_init(bar + 8 * i, i == B_AUX ? 3 : i < B_P3EMPTY ? 1 : i < B_EMPTY ? 2 : i < B_ZERO ? 4 : i == B_ZERO ? 16 : i < B_READY + 2 ? 512 : 128);
      }
    asm volatile("fence.mbarrier_init.release.cluster;" ::: "memory");
  }
  if (tid >= 96 && tid < 99) sts32(sb + SM_BAR + 416 + (tid - 96) * 4, tid == 96 ? 0x1c801c80u : tid == 97 ? 0u : 0x34003400u);
  TS_REG(tsc_);
  asm volatile("st.shared.v4.b32 [%0], {%1, %1, %1, %1};" ::"r"(sb + SM_X + tid * 16), "r"(0) : "memory");
  if (tid < 256) sts32(sb + SM_CONST + tid * 4, (tid & 3) ? 0u : ((tid >> 5) < NMB ? 0xdd02e192u : 0x00001ef0u));
  PROXY_FENCE();
  TS_REG(tsd_);
  __syncthreads();
  if (wg > 0 && w == 0) p1_load(wg);
  if (wi == 6) aux_load_e(sb + SM_GW, gate_w, 1280, bar + 8 * B_AUX);
  if (wi == 10) aux_load_e(sb + SM_WRAW, w_phi + h * 400, 800, bar + 8 * B_AUX);
  if (wi == 14) aux_load_e(sb + SM_EP, &g_cnt[C_EPOCH], 16, bar + 8 * B_AUX);
  TS_FIRST();

  }
  {
    float acc[64];
    uint32_t pk[32];
    float gs = 0.f;
    auto tile = [&](auto BR) {
    constexpr int br = decltype(BR)::value;
    COORDS();
    P1_LOAD();
    const int r = wg & 1, ch = wg >> 1;
    uint32_t xh[3] = {0u, 0u, 0u};
    const int grow = c1 * 16 + wi;
    const uint32_t gx = sb + grow * 128 + ((g ^ (grow & 7)) << 4) + t * 4, gw = sb + SM_GW + lane * 4;
    const uint32_t srow = (w * 16 + (lane & 15)) * 16 + (lane >> 4) * 1024;
    auto stage = [&](uint32_t stg, int e0) {
#pragma unroll
      for (int e = 0; e < 16; e += 4) stsm4(stg + srow + e * 512, pk[e0 + e], pk[e0 + e + 1], pk[e0 + e + 2], pk[e0 + e + 3]);
    };
    auto gate_fma = [&](uint32_t a, int ks) {
      const uint32_t b = lds32(gw + ks * 128);
      gs = fmaf(__uint_as_float(a << 16), __uint_as_float(b << 16), gs);
      gs = fmaf(__uint_as_float(a & 0xffff0000u), __uint_as_float(b & 0xffff0000u), gs);
    };
    auto release = [&](int it) {
      if (w == 0) {
        mbar_arrive_e(bar + 8 * (B_EMPTY + (it & 3)));
        if (wg == 3 && it < 16) {
          mbar_wait(bar + 8 * (B_EMPTY + (it & 3)), (it >> 2) & 1);
          p1_load(it + 4);
        }
      }
    };
    auto duties = [&](int it) {
      if (br == 0) {
        const uint32_t a = lds32(gx + (it & 3) * P1_STB);
        if (it < 3) { xh[0] = xh[1]; xh[1] = xh[2]; xh[2] = a; }
        else {
          if (it == 3) { mbar_wait(bar + 8 * B_AUX, 0); gate_fma(xh[0], 0); gate_fma(xh[1], 1); gate_fma(xh[2], 2); }
          gate_fma(a, it);
        }
        if (wi == 0) {
          if (it >= 1 && it <= 4) {
            bulk_s2g_e(it < 4 ? reinterpret_cast<uint8_t*>(out) + bid * 20480 + (it - 1) * 8192 : reinterpret_cast<uint8_t*>(g_kv + bid * 240), sb + SM_X,
                       it < 3 ? 8192 : it == 3 ? 4096 : 960);
            bulk_s2g_e(g_o + rb1 * ORB + ((c1 * 4 + it - 1) * 5 + 2) * 2048, sb + SM_X, 2048);
            BULK_COMMIT();
          }
          if (it == 7) BULK_WAIT_READ();
        }
        if (wi == 4 && it >= 1 && it <= 3) {
          const int bytes = it == 1 ? 19200 : 6400;
          const uint8_t* p = reinterpret_cast<const uint8_t*>(it == 1 ? wqkv_b : it == 2 ? wo_a : wo_b) + bid * bytes;
          asm volatile(E1 "@p cp.async.bulk.prefetch.L2.global [%0], %1;}" ::"l"(p), "r"(bytes) : "memory");
        }
        if (it == 5 || (it == 6 && wg < 2)) {
          const int i = tid + (it - 5) * 512, k = i / 24, n = i % 24, ii = 2 * (n >> 3) + (n & 1), f = 4 * ii + ((n & 7) >> 1), d = k - (odd ? 4 : 0);
          uint16_t v = 0;
          if (d >= 0 && d < 20 && ii < 5) asm volatile("ld.shared.u16 %0, [%1];" : "=h"(v) : "r"(sb + SM_WRAW + (d * 20 + f) * 2) : "memory");
          sts16(sb + SM_WPHI + (k >> 3) * 384 + n * 16 + (k & 7) * 2, v);
        }
        if (it == 9) { epoch = (lds32(sb + SM_EP) >> 7) + 1; __syncwarp(); mbar_arrive_e(bar + 8 * B_ZERO); }
      } else if (it <= 13) {
        if ((it & 1) == ch) {
          const bool skip_a = (c1 & 3) == 2 && wg == 0;
          const int ga_a = tile_atom(c1) + 2 * ch + skip_a;
          if (it < 12) { mbar_wait(bar + 8 * B_ZERO, 0); stage(sb + SM_X + wg * 8192, 0); }
          else { BULK_WAIT_READ(); bar_sync(1 + wg, 128); stage(sb + SM_X + wg * 8192, 16); }
          PROXY_FENCE();
          bar_sync(1 + wg, 128);
          if (w == 0) {
            if (it < 12) atom_store_e(&maps.qst, sb + SM_X + wg * 8192, ga_a, r, rb1);
            else {
              if (!(skip_a || ((c1 & 3) == 1 && wg == 3))) atom_store_e(&maps.qst, sb + SM_X + wg * 8192, ga_a + 1, r, rb1);
              bulk_s2g_e(g_gate + rb1 * 128 + c1 * 16 + wg * 4, sb + SM_BAR + 448 + wg * 16, 16);
            }
            BULK_COMMIT();
          }
        } else if (it < 12) {
#pragma unroll
          for (int o = 16; o; o >>= 1) gs += __shfl_xor_sync(0xffffffffu, gs, o);
          if (lane == 0) sts32(sb + SM_BAR + 448 + wi * 4, __float_as_uint(rcp(1.f + ex2(gs * -1.4426950408889634f))));
        }
      } else if (it == 19) {
        mbar_wait(bar + 8 * (B_KVFULL + 0), 0);
        const uint8_t* qp = g_qkv + rb * QRB + c0 * 2048 + orow;
        load_frag(q[0], qp);
        load_frag(q[1], qp + 1024);
        bad = ldcg32(&g_kbad);
        sts16(sb + wg * 12288 + onepos, 0x3c00);
        PROXY_FENCE();
        mbar_arrive(bar + 8 * (B_READY + 0));
      } else if (w == 0) {
        if (it == 15) signal_bulk_e(&g_cnt[C_TA]);
        if (wg == it - 17) {
          wait_count(&g_cnt[C_TA], epoch * 512);
          mbar_wait(bar + 8 * (B_EMPTY + wg), 0);
          slot_load_e(sb + wg * P1_STB, bar + 8 * (B_KVFULL + wg), &maps.qld, c0, 1, wg * 4);
        }
      }
    };
      const int tl = c1 ^ br, k4 = tl & 3;
      const bool narrow = (k4 == 1 && wg == 3) || (k4 == 2 && wg == 0);
      const int a0 = 2 * ch + ((k4 == 2 && wg == 0) ? 1 : 0);
      const uint32_t da = (uint32_t)mkdesc(sb + r * 8192, 16, 0, 0), db = (uint32_t)mkdesc(sb + 16384 + a0 * 8192, 8192, 0, 0);
      auto run = [&](auto NARROW) {
#pragma unroll 1
        for (int it = br * 10; it < br * 10 + 10; it++) {
          const uint32_t so = (it & 3) * (P1_STB / 16);
          mbar_wait(bar + 8 * (B_FULL + (it & 3)), (it >> 2) & 1);
          TS_MARK(20 + it);
          bar_sync(5 + wg, 256);
          WG_FENCE();
#pragma unroll
          for (int k = 0; k < 4; k++) {
            if (decltype(NARROW)::value) wg64_ss_of64(acc, desc_lohi(da + so + k * 2, 0x40000040u), desc_lohi(db + so + k * 128, 0x40000040u), k > 0 || it > br * 10);
            else wg128_ss(acc, desc_lohi(da + so + k * 2, 0x40000040u), desc_lohi(db + so + k * 128, 0x40000040u), k > 0 || it > br * 10);
          }
          WG_COMMIT();
          if (br == 0 || it < 19 || wg < 3) bar_arrive(5 + ((wg + 1) & 3), 256);
          WG_WAIT(1);
          if (it > br * 10) release(it - 1);
          duties(it);
        }
        WG_WAIT(0);
      };
      if (br == 0 && wg == 3) bar_arrive(5, 256);
      if (narrow) run(Int<1>{}); else run(Int<0>{});
      pin(acc);
      TS_MARK(2 + 2 * br);
      release(br * 10 + 9);
      const int ga0 = tile_atom(tl) + a0;
      uint32_t m0 = 0, m1 = 0;
      if (br == 0) {
        const bool mufu0 = 2 * w < NMB, mufu1 = 2 * w + 1 < NMB;
        const float sk0 = __uint_as_float(mufu0 ? (127u + 70u) << 23 : (127u - 69u) << 23);
        const float sk1 = __uint_as_float(mufu1 ? (127u + 70u) << 23 : (127u - 69u) << 23);
        pack_atom_a<0>(acc, pk, ga0, sk0, sk1, m0, m1);
        if (!narrow) pack_atom_a<1>(acc, pk, ga0 + 1, sk0, sk1, m0, m1);
        const uint32_t lim0 = (mufu0 ? 127u + 110u : 127u - 29u) << 7, lim1 = (mufu1 ? 127u + 110u : 127u - 29u) << 7;
        if ((m0 & 0x7fffu) >= lim0 || ((m0 >> 16) & 0x7fffu) >= lim0 || (m1 & 0x7fffu) >= lim1 || ((m1 >> 16) & 0x7fffu) >= lim1) { g_kbad = epoch; __threadfence(); }
      } else {
        pack_atom<0, 0>(acc, pk, 0.f, 0.f, m0, m1);
        pack_atom<0, 1>(acc, pk, 0.f, 0.f, m0, m1);
        if (ch) mbar_wait(bar + 8 * (B_EMPTY + 2), 0);
        const uint32_t stg = sb + (ch ? 2 * P1_STB : SM_X) + r * 16384;
        stage(stg, 0);
        stage(stg + 8192, 16);
        mbar_wait(bar + 8 * (B_KVFULL + 1), 0);
        sts16(sb + P1_STB + wg * 12288 + onepos, 0x3c00);
        PROXY_FENCE();
        mbar_arrive(bar + 8 * (B_READY + 1));
        bar_sync(1 + wg, 128);
        if (w == 0) {
          atom_store_e(&maps.qst, stg, ga0, r, 16 + rb1);
          if (!narrow) atom_store_e(&maps.qst, stg + 8192, ga0 + 1, r, 16 + rb1);
          BULK_COMMIT();
        }
      }
      TS_MARK(3 + 2 * br);
    };
    tile(Int<0>{});
    tile(Int<1>{});
  }

  {
  COORDS();
  if (odd ? t < 2 : t >= 2) {
    if (odd) { q[0][0] = 0; q[0][1] = 0; q[1][0] = 0; q[1][1] = 0; }
    else { q[0][4] = 0; q[0][5] = 0; q[1][4] = 0; q[1][5] = 0; }
  }
  {
    uint32_t m = 0;
#pragma unroll
    for (int i = 0; i < 6; i++) m = maxabs_bf16x2(m, maxabs_bf16x2(q[0][i], q[1][i]));
    bad = bad == (int)epoch || (m & 0x7fffu) >= ((127u - 50u) << 7) || ((m >> 16) & 0x7fffu) >= ((127u - 50u) << 7);
  }
#pragma unroll
  for (int i = 0; i < 5; i++)
    asm volatile("ld.volatile.shared.b32 %0, [%1];" : "=r"(qc[i]) : "r"(sb + SM_BAR + 416 + (i == 4 ? 8 : t == 0 ? 0 : 4)) : "memory");
  events = wg == 0 ? 0x81b65840f2881c6ull : wg == 1 ? 0x8208185d240d206ull : wg == 2 ? 0x82081d61540b206ull : 0x8206164d1409206ull;
  mbar_wait(bar + 8 * (B_READY + 0), 0);
  }
  float o[2][12];
#pragma unroll
  for (int i = 0; i < 12; i++) { o[0][i] = 0.f; o[1][i] = 0.f; }
  {
    uint32_t dk0 = (uint32_t)mkdesc(sb, 1024, 0, 0), dk1 = (uint32_t)mkdesc(sb + 2048, SM_CONST - 2048, 0, 0), dv = (uint32_t)mkdesc(sb + 3072, 128, 0, 0);
    WG_FENCE();
    TS_MARK(6);
    int i = 0;
#pragma unroll 1
    for (int seg = 0; seg < 60; seg += 6) {
      const int iend = (int)(events >> seg) & 63;
#pragma unroll 1
      do {
      if (!(i & 3)) TS_MARK(40 + (i >> 2));
#pragma unroll
      for (int m = 0; m < 2; m++) {
        float s[32];
        uint32_t p[16];
        wg64_rs_bf16_i(s, q[m][0], q[m][1], q[m][2], q[m][3], desc_lohi(dk0, 8));
        wg64_rs_bf16(s, q[m][4], q[m][5], qc[2 * m], qc[2 * m + 1], desc_lohi(dk1, 8), 1);
        WG_COMMIT();
        WG_WAIT(0);
        constexpr int A = 2 * NMB, B = 16 - A;
#pragma unroll
        for (int j = 0; j < B; j++) {
          if ((j * A) % B < A) { const int a = j * A / B; p[a] = exp2_pair_mufu(s[2 * a], s[2 * a + 1]); }
          p[A + j] = exp2_pair(s[2 * (A + j)], s[2 * (A + j) + 1], qc[4]);
        }
        WG_FENCE();
#pragma unroll
        for (int kk = 0; kk < 4; kk++) wg24_rs_f16_t(o[m], p[4 * kk], p[4 * kk + 1], p[4 * kk + 2], p[4 * kk + 3], desc_lohi(dv + kk * 16, 64), 1);
        WG_COMMIT();
      }
      dk0 += 384; dk1 += 384u - (384u << 16); dv += 384;
      } while (++i != iend);
      if (i == 32) break;
      {
        if ((i & 7) == 0 || i == 6 || i == 27) {
          COORDS();
          if (w == 0 && i != 8 && (i != 24 || wg != 0)) signal_bulk_e(&g_cnt[i == 6 ? C_TB : i == 16 ? C_KV + h : C_OB + rb * 2 + (h >> 4)]);
          if (i != 27) {
            WG_WAIT(0);
            if (w == 0) mbar_arrive_e(i == 6 ? bar + 8 * B_STG : bar + 8 * (B_FREE - 1) + i);
            if (i != 6) mbar_wait(bar + 8 * B_READY + i, 0);
          }
        } else if (i == 7 || i == 10 || i == 17 || i == 22 || i == 29) {
          COORDS();
          if (i == 7) {
            if (w < 2) {
              mbar_wait(bar + 8 * B_STG, 0);
              if (w == 1) wait_count(&g_cnt[C_TB], epoch * 512);
              slot_load_e(sb + (2 + w) * P1_STB, bar + 8 * (w ? B_KB : B_KVFULL + 2), &maps.qld, c0, 1, w ? 16 + qt * 4 : 8);
            }
          } else if (i == 29) {
            if (w < 3) {
              mbar_wait(bar + 8 * (B_FREE + 2), 0);
              mbar_wait(bar + 8 * B_B2, 0);
              p3_load_w(w);
              wait_count(&g_cnt[C_OB + rb1 * 2 + kh], epoch * 16);
              p3_load_a(w);
            }
          } else {
            if (i != 22 && w == 0) {
              const int u = i == 17;
              mbar_wait(bar + 8 * (B_FREE + u), 0);
              slot_load_e(sb + u * 3 * P1_STB, bar + 8 * (u ? B_KVFULL + 3 : B_QB), &maps.qld, c0, u, u ? 12 : 16 + qt * 4);
            }
            if (i != 17) {
              const int u = i == 10 ? 2 : 3;
              mbar_wait(bar + 8 * (B_KVFULL + u), 0);
#pragma unroll
              for (int e = 0; e < 4; e++) sts16(sb + u * P1_STB + e * 12288 + onepos, 0x3c00);
              PROXY_FENCE();
              mbar_arrive(bar + 8 * (B_READY + u));
            }
          }
        } else if (i < 16) {
          WG_WAIT(0);
          COORDS();
          const uint64_t dw = mkdesc(sb + SM_WPHI, 384, 128, 0);
          TS_MARK(7);
          const uint32_t kb = sb + 3 * P1_STB + wg * 12288, ph = sb + SM_X + (wg & 1) * 10240;
          mbar_wait(bar + 8 * B_KB, 0);
          sts16(kb + onepos, 0x3f80);
          float p0[12], p1[12];
          phi_proj(p0, p1, kb, dw);
          if (wg < 2) mbar_wait(bar + 8 * (B_LINK + wg), 0);
          uint32_t phi[10];
          feature_map(phi, p0);
#pragma unroll
          for (int u = 0; u < 10; u++) sts32(ph + (u % 5) * 2048 + orow + (u / 5) * 128, phi[u]);
          feature_map(phi, p1);
#pragma unroll
          for (int u = 0; u < 10; u++) sts32(ph + (u % 5) * 2048 + orow + (u / 5) * 128 + 1024, phi[u]);
          PROXY_FENCE();
          bar_sync(1 + wg, 128);
          const uint64_t da = mkdesc(ph, 128, 2048, 0), db = mkdesc(kb + 3072, 128, 1024, 0);
          WG_FENCE();
#pragma unroll
          for (int kk = 0; kk < 8; kk++) {
            if (kk == 0) wg24_ss_bf16_tt_i(p0, da, db);
            else wg24_ss_bf16_tt(p0, da + kk * 16, db + (kk & 3) * 16 + (kk >> 2) * 384, 1);
          }
          WG_COMMIT();
          WG_WAIT(0);
          pin(p0);
          if (wg >= 2) mbar_arrive_e(bar + 8 * (B_LINK + (wg & 1)));
          bar_sync(1 + wg, 128);
          const uint32_t ks = kb + ((w * 16 + g) * 24 + 2 * t) * 4;
#pragma unroll
          for (int j = 0; j < 3; j++) {
            if (w < 3) asm volatile("st.shared.v2.f32 [%0], {%1, %2};" ::"r"(ks + 32 * j), "f"(p0[4 * j]), "f"(p0[4 * j + 1]) : "memory");
            if (w < 2) asm volatile("st.shared.v2.f32 [%0], {%1, %2};" ::"r"(ks + 768 + 32 * j), "f"(p0[4 * j + 2]), "f"(p0[4 * j + 3]) : "memory");
          }
          PROXY_FENCE();
          bar_sync(1 + wg, 128);
          if (w == 0) { bulk_addf_e(g_kv + h * 960, kb, 3840); BULK_COMMIT(); }
          TS_MARK(8);
        } else if (i == 18) {
          COORDS();
          wait_count(&g_cnt[C_KV + h], epoch * 16);
          float v[8];
#pragma unroll
          for (int u = 0; u < 8; u++) v[u] = (u < 7 || wt < 64) ? __ldcg(&g_kv[h * 960 + u * 128 + wt]) : 0.f;
#pragma unroll
          for (int u = 0; u < 9; u++) {
            const int e = u * 128 + wt, f = e / 24, d = e % 24;
            sts16(sb + SM_KVB + (f >> 3) * 384 + d * 16 + (f & 7) * 2, u < 8 ? __bfloat16_as_ushort(__float2bfloat16(v[u < 8 ? u : 0])) : (uint16_t)0);
          }
          PROXY_FENCE();
          mbar_arrive(bar + 8 * B_KVB);
        } else {
          WG_WAIT(0);
          COORDS();
          const uint64_t dw = mkdesc(sb + SM_WPHI, 384, 128, 0);
          TS_MARK(9);
          float gt[4];
#pragma unroll
          for (int u = 0; u < 4; u++) gt[u] = 1.f - __ldcg(&g_gate[rb * 128 + (u >> 1) * 64 + w * 16 + g + (u & 1) * 8]);
          mbar_wait(bar + 8 * B_QB, 0);
          float p0[12], p1[12];
          phi_proj(p0, p1, sb + wg * 12288, dw);
          const uint64_t dkv = mkdesc(sb + SM_KVB, 384, 128, 0);
          auto readout = [&](float (&p)[12], float g0, float g1, uint32_t a) {
            uint32_t phi[10];
            feature_map(phi, p);
            WG_FENCE();
            wg24_rs_bf16_i(p, phi[0], phi[5], phi[1], phi[6], dkv);
            wg24_rs_bf16(p, phi[2], phi[7], phi[3], phi[8], dkv + 48, 1);
            wg24_rs_bf16(p, phi[4], phi[9], 0u, 0u, dkv + 96, 1);
            WG_COMMIT();
            WG_WAIT(0);
            pin(p);
            const float l0 = __shfl_sync(0xffffffffu, odd ? p[0] : p[8], lsrc), l1 = __shfl_sync(0xffffffffu, odd ? p[2] : p[10], lsrc);
            stage_o(p, __fdividef(g0, l0 + 1e-6f), __fdividef(g1, l1 + 1e-6f), a, v0, v2);
          };
          mbar_wait(bar + 8 * B_KVB, 0);
          readout(p0, gt[0], gt[1], ostg + orow);
          readout(p1, gt[2], gt[3], ostg + orow + 1024);
          PROXY_FENCE();
          bar_sync(1 + wg, 128);
          if (w == 0) { mbar_arrive_e(bar + 8 * B_B2); flush_o(g_o + rb * ORB + (80 + c0) * 2048, ostg, odd); }
          TS_MARK(10);
        }
      }
    }
  }
  {
    COORDS();
    float gt[4];
#pragma unroll
    for (int u = 0; u < 4; u++) gt[u] = __ldcg(&g_gate[rb * 128 + (u >> 1) * 64 + w * 16 + g + (u & 1) * 8]);
    WG_WAIT(0);
    pin(o[0]); pin(o[1]);
    TS_MARK(11);
    int big = 0;
#pragma unroll
    for (int m = 0; m < 2; m++) {
      const float l0 = __shfl_sync(0xffffffffu, odd ? o[m][0] : o[m][8], lsrc), l1 = __shfl_sync(0xffffffffu, odd ? o[m][2] : o[m][10], lsrc);
      const float r0 = rcp(l0), r1 = rcp(l1);
      float chk = 0.f, mx0 = 0.f, mx1 = 0.f;
#pragma unroll
      for (int i = 0; i < 12; i++) chk = fmaf(o[m][i], 0.f, chk);
#pragma unroll
      for (int i = 4; i < 6; i++) { mx0 = fmaxf(mx0, fabsf(o[m][i])); mx1 = fmaxf(mx1, fabsf(o[m][i + 2])); }
      bad |= !(chk == 0.f) || !(l0 >= 32.f) || !(l1 >= 32.f);
      big |= fmaxf(mx0 * r0, mx1 * r1) >= 1.220703125e-4f;
      stage_o(o[m], r0 * gt[2 * m], r1 * gt[2 * m + 1], ostg + orow + m * 1024, v0, v2);
    }
    PROXY_FENCE();
    const int anybad = __syncthreads_or(bad), anybig = __syncthreads_or(big);
    if (anybad || !anybig) attn_exact(x, wqkv, h, qt, sb + SM_X);
  }
  TS_MARK(12);

  COORDS();
  if (wg == 3) {
    if (w == 3) { p3_load_w(3); p3_load_a(3); }
    bar_sync(4, 128);
    flush_o(g_o + (qt * 4 + w) * ORB + c0 * 2048, sb + SM_X + w * 6144, odd);
    signal_bulk_e(&g_cnt[C_OA + (qt * 4 + w) * 2 + (h >> 4)]);
    if (wt == 0) atomicAdd(&g_cnt[C_EPOCH], 1);
  } else if (wg == 2) {
    mbar_wait(bar + 8 * (B_P3EMPTY + w), 0);
    p3_load_w(4 + w);
    if (w > 0) wait_count(&g_cnt[C_OA + rb1 * 2 + kh], epoch * 16);
    p3_load_a(4 + w);
    if (w < 2) {
      mbar_wait(bar + 8 * (B_P3EMPTY + w), 1);
      p3_load_w(8 + w);
      if (w == 0) wait_count(&g_cnt[C_OA + rb1 * 2 + kh], epoch * 16);
      p3_load_a(8 + w);
    }
  } else {
    float acc[96];
    const bool wide = (cg & 1) == wg;
    const int skip = (!wide && (cg & 1)) ? 1 : 0;
    if (wide) {
#pragma unroll 1
      for (int j = 0; j < 10; j++) {
        mbar_wait(bar + 8 * (B_P3FULL + (j & 3)), (j >> 2) & 1);
        if (j == 5) TS_MARK(13);
        if (j < 5) TS_MARK(j == 0 ? 1 : 15 + j);
        const uint32_t dst = sb + (j & 3) * P3_STB;
        const uint64_t da = mkdesc(dst + wg * 1024, 2048, 128, 0), db = mkdesc(dst + 16384, 8192, 1024, 1);
        WG_FENCE();
#pragma unroll
        for (int k = 0; k < 4; k++) wg192_ss(acc, da + k * 256, db + k * 128, (j | k) != 0);
        WG_COMMIT();
        WG_WAIT(1);
        if (j > 0 && w == 0) mbar_arrive_e(bar + 8 * (B_P3EMPTY + ((j - 1) & 3)));
      }
      WG_WAIT(0);
    } else {
#pragma unroll 1
      for (int j = 0; j < 10; j++) {
        mbar_wait(bar + 8 * (B_P3FULL + (j & 3)), (j >> 2) & 1);
        if (j == 5) TS_MARK(13);
        if (j < 5) TS_MARK(j == 0 ? 1 : 15 + j);
        const uint32_t dst = sb + (j & 3) * P3_STB;
        const uint64_t da = mkdesc(dst + wg * 1024, 2048, 128, 0), db = mkdesc(dst + 16384 + skip * 8192, 8192, 1024, 1);
        WG_FENCE();
#pragma unroll
        for (int k = 0; k < 4; k++) wg128_ss_of96(acc, da + k * 256, db + k * 128, (j | k) != 0);
        WG_COMMIT();
        WG_WAIT(1);
        if (j > 0 && w == 0) mbar_arrive_e(bar + 8 * (B_P3EMPTY + ((j - 1) & 3)));
      }
      WG_WAIT(0);
    }
    pin(acc);
    TS_MARK(14);
    if (!wide) mbar_wait(bar + 8 * (B_P3EMPTY + 2), 1);
    const uint32_t stg = sb + (wide ? 4 : 2) * P3_STB;
    const int r = w * 16 + (lane & 15);
#pragma unroll
    for (int i = 0; i < 24; i += 2)
      if (i < 16 || wide) {
        const int ch = (i & 7) + (lane >> 4);
        stsm4(stg + (i >> 3) * 8192 + r * 128 + ((ch ^ (r & 7)) << 4), pack_bf16(acc[4 * i], acc[4 * i + 1]), pack_bf16(acc[4 * i + 2], acc[4 * i + 3]),
              pack_bf16(acc[4 * i + 4], acc[4 * i + 5]), pack_bf16(acc[4 * i + 6], acc[4 * i + 7]));
      }
    PROXY_FENCE();
    bar_sync(1 + wg, 128);
    if (w < (wide ? 3 : 2)) {
      PROXY_FENCE_G();
      asm volatile(E1 "@p cp.reduce.async.bulk.tensor.2d.global.shared::cta.add.bulk_group [%0, {%2, %3}], [%1];}" ::"l"(&maps.out), "r"(stg + w * 8192),
                   "r"((atom3 + skip + w) * 64), "r"(rb1 * 128 + wg * 64) : "memory");
      BULK_COMMIT();
      BULK_WAIT();
    }
    TS_MARK(15);
  }
  TS_DUMP();
}

typedef CUresult (*EncodeFn)(CUtensorMap*, CUtensorMapDataType, cuuint32_t, void*, const cuuint64_t*, const cuuint64_t*, const cuuint32_t*, const cuuint32_t*,
                             CUtensorMapInterleave, CUtensorMapSwizzle, CUtensorMapL2promotion, CUtensorMapFloatOOBfill);
void encode(EncodeFn enc, CUtensorMap* m, void* p, int rank, const cuuint64_t* gd, const cuuint64_t* gs, const cuuint32_t* bd) {
  const cuuint32_t es[3] = {1, 1, 1};
  enc(m, CU_TENSOR_MAP_DATA_TYPE_BFLOAT16, rank, p, gd, gs, bd, es, CU_TENSOR_MAP_INTERLEAVE_NONE, CU_TENSOR_MAP_SWIZZLE_128B,
      CU_TENSOR_MAP_L2_PROMOTION_L2_128B, CU_TENSOR_MAP_FLOAT_OOB_FILL_NONE);
}

}

extern "C" void kernel_launch(void* const* d_in, const int* in_sizes, int n_in, void* d_out, int out_size) {
  static EncodeFn enc = nullptr;
  if (!enc) {
    cudaDriverEntryPointQueryResult qr;
    cudaGetDriverEntryPoint("cuTensorMapEncodeTiled", (void**)&enc, cudaEnableDefault, &qr);
    cudaFuncSetAttribute(gated_mix_kernel, cudaFuncAttributeMaxDynamicSharedMemorySize, SMEM_BYTES);
  }
  Maps m;
  {
    const cuuint64_t gd[2] = {640, 2048}, gs[1] = {1280};
    const cuuint32_t bx[2] = {64, 128}, bo[2] = {64, 64};
    encode(enc, &m.x, d_in[0], 2, gd, gs, bx);
    encode(enc, &m.out, d_out, 2, gd, gs, bo);
  }
  for (int b = 0; b < 2; b++) {
    const cuuint64_t gd[3] = {64, 640, 30}, gs[2] = {3840, 128}, gd3[3] = {64, 640, 10}, gs3[2] = {1280, 128};
    const cuuint32_t bd[3] = {64, 64, 4}, bd3[3] = {64, 64, 3};
    encode(enc, &m.w[b], d_in[b ? 4 : 1], 3, gd, gs, bd);
    encode(enc, &m.wo[b], d_in[b ? 6 : 2], 3, gd3, gs3, bd3);
  }
  {
    void* qp = nullptr;
    cudaGetSymbolAddress(&qp, g_qkv);
    const cuuint64_t gd[5] = {128, 80, 3, 2, 32}, gs[4] = {2048, QTY, 1024, QRB};
    const cuuint32_t bl[5] = {128, 3, 2, 2, 4}, bs[5] = {128, 8, 1, 1, 1}, es[5] = {1, 1, 1, 1, 1};
    enc(&m.qld, CU_TENSOR_MAP_DATA_TYPE_UINT64, 5, qp, gd, gs, bl, es, CU_TENSOR_MAP_INTERLEAVE_NONE, CU_TENSOR_MAP_SWIZZLE_NONE, CU_TENSOR_MAP_L2_PROMOTION_L2_128B, CU_TENSOR_MAP_FLOAT_OOB_FILL_NONE);
    enc(&m.qst, CU_TENSOR_MAP_DATA_TYPE_UINT64, 5, qp, gd, gs, bs, es, CU_TENSOR_MAP_INTERLEAVE_NONE, CU_TENSOR_MAP_SWIZZLE_NONE, CU_TENSOR_MAP_L2_PROMOTION_NONE, CU_TENSOR_MAP_FLOAT_OOB_FILL_NONE);
  }
  gated_mix_kernel<<<128, 512, SMEM_BYTES, cudaStreamPerThread>>>(m, (const __nv_bfloat16*)d_in[0], (const __nv_bfloat16*)d_in[1], (const __nv_bfloat16*)d_in[5],
                                                                 (const __nv_bfloat16*)d_in[7], d_in[4], d_in[2], d_in[6], (uint4*)d_out);
}
```
